```python
import torch

def _softmax(x, axis=-1):
    return torch.softmax(x, dim=axis)
def _gelu(x):
    return torch.nn.functional.gelu(x, approximate="tanh")
def _silu(x):
    return torch.nn.functional.silu(x)
def _sigmoid(x):
    return torch.sigmoid(x)
def _layernorm(x, axis=-1, eps=1e-5):
    m = x.mean(dim=axis, keepdim=True)
    v = x.var(dim=axis, keepdim=True, unbiased=False)
    return (x - m) / torch.sqrt(v + eps)
def _scatter_add(tgt, idx, src, axis=0):
    return tgt.clone().index_add_(axis, idx, src)
def _segment_sum(src, seg, n):
    out = torch.zeros((n,) + src.shape[1:], dtype=src.dtype)
    return out.index_add_(0, seg, src)
def _pad(x, pw):
    flat = tuple(v for pair in reversed(pw) for v in pair)
    return torch.nn.functional.pad(x, flat)

kernel_name = 'interleave_layers__sliding_block_cached__glu_gated_swiglu__decode'

def setup_inputs():

    _w = (lambda a: (lambda t: t.to(torch.bfloat16) if t.is_floating_point() else t)(torch.as_tensor(a)))
    def _A_setup():
        B, Sq, D = 1, 1, 640
        Hq, Hkv, Sk, Dh = 32, 32, 32768, 192
        assert Hq % Hkv == 0, (Hq, Hkv)
        return {
            "x": _w((lambda *s: torch.randn(*s, dtype=torch.bfloat16) * 0.05)(B, Sq, D)),
            "k_cache": _w((lambda *s: torch.randn(*s, dtype=torch.bfloat16) * 0.8)(B, Hkv, Sk, Dh)),
            "v_cache": _w((lambda *s: torch.randn(*s, dtype=torch.bfloat16) * 1.6)(B, Hkv, Sk, Dh)),
            "wq": _w((lambda *s: torch.randn(*s, dtype=torch.bfloat16) * 0.8)(D, Hq * Dh) * (D ** -0.5)),
            "wo": _w((lambda *s: torch.randn(*s, dtype=torch.bfloat16) * 1.6)(Hq * Dh, D) * ((Hq * Dh) ** -0.5)),
        }
    _A_in = _A_setup()

    def _B_setup():
        B, S, D, F = 1, 1, 640, 1536
        return {
            "x": _w((lambda *s: torch.randn(*s, dtype=torch.bfloat16) * 0.05)(B, S, D)),
            "w1": _w((lambda *s: torch.randn(*s, dtype=torch.bfloat16) * 0.4)(D, F) * (2.0 / D) ** 0.5),
            "w3": _w((lambda *s: torch.randn(*s, dtype=torch.bfloat16) * 0.4)(D, F) * (2.0 / D) ** 0.5),
            "w2": _w((lambda *s: torch.randn(*s, dtype=torch.bfloat16) * 0.4)(F, D) * (2.0 / F) ** 0.5),
        }
    _B_in = _B_setup()

    return {
        "A_x": _A_in["x"],
        "A_k_cache": _A_in["k_cache"],
        "A_v_cache": _A_in["v_cache"],
        "A_wq": _A_in["wq"],
        "A_wo": _A_in["wo"],
        "B_x": _B_in["x"],
        "B_w1": _B_in["w1"],
        "B_w3": _B_in["w3"],
        "B_w2": _B_in["w2"],
    }

def reference(A_x, A_k_cache, A_v_cache, A_wq, A_wo, B_x, B_w1, B_w3, B_w2):
    def _A_ref(x, k_cache, v_cache, wq, wo):
        B, Sq, D = x.shape
        Hq, Dh = 32, 192
        Hkv, Sk = k_cache.shape[1], k_cache.shape[2]
        W = min(4096, max(256, Sk // 4))
        rep = Hq // Hkv
        q = (lambda x, *d: x.permute(*d))((x @ wq).reshape(B, Sq, Hq, Dh), 0, 2, 1, 3)
        k = (lambda x, n, axis: torch.repeat_interleave(x, n, dim=axis))(k_cache[:, :, Sk - W:, :], rep, axis=1)
        v = (lambda x, n, axis: torch.repeat_interleave(x, n, dim=axis))(v_cache[:, :, Sk - W:, :], rep, axis=1)
        scores = torch.einsum("bhqd,bhkd->bhqk", q, k) * (Dh ** -0.5)
        p = _softmax(scores, axis=-1)
        o = torch.einsum("bhqk,bhkd->bhqd", p, v)
        return (lambda x, *d: x.permute(*d))(o, 0, 2, 1, 3).reshape(B, Sq, Hq * Dh) @ wo

    def _B_ref(x, w1, w3, w2):
        gate = torch.einsum("bsd,df->bsf", x, w1)
        up = torch.einsum("bsd,df->bsf", x, w3)
        h = _silu(gate) * up
        out = torch.einsum("bsf,fd->bsd", h, w2)
        return out

    x = A_x
    x = x + _A_ref(_layernorm(x, axis=-1), A_k_cache, A_v_cache, A_wq, A_wo)
    x = x + _B_ref(_layernorm(x, axis=-1), B_w1, B_w3, B_w2)
    x = x + _A_ref(_layernorm(x, axis=-1), A_k_cache, A_v_cache, A_wq, A_wo)
    x = x + _B_ref(_layernorm(x, axis=-1), B_w1, B_w3, B_w2)
    return x
```

```cpp
#include <cuda_runtime.h>
#include <cuda_bf16.h>
#include <cuda.h>
#include <stdint.h>
#include <math.h>

namespace {

constexpr int DM = 640;
constexpr int NH = 32;
constexpr int DH = 192;
constexpr int SK = 32768;
constexpr int WIN = 4096;
constexpr int FF = 1536;
constexpr int NCTA = 128;
constexpr int NT = 256;
constexpr int TILE = 6144;
constexpr int NG = 64;
constexpr int DN0 = 64;
constexpr int NDN = 40;

constexpr int SM_RING = 0;
constexpr int SM_B = 8 * 2 * TILE;
constexpr int SM_Q = SM_B + 61440;
__host__ __device__ constexpr int c_slot(int w) { return w < 2 ? 4096 + 10240 * w : 12288 + 6144 * w; }
__host__ __device__ constexpr int v1_pos(int n) { return 10240 * (n >> 3) + 512 * (n & 7); }
constexpr int SM_XS = SM_Q + 61440;
constexpr int SM_R = SM_XS + 1280;
constexpr int SM_ST = SM_R + 4096;
constexpr int SM_QS = SM_R + 6272;
constexpr int SM_OS = SM_QS + 384;
constexpr int SM_BAR = SM_OS + 384;
constexpr int SM_XBAR = SM_BAR + 24 * 8;
constexpr int SM_MISC = SM_XBAR + 8 * 8;
constexpr int SM_ONE = SM_MISC + 16;
constexpr int SM_ZERO = SM_ONE + 160;
constexpr int XCAP = 48;
constexpr int XSTR = 16 + 4 * XCAP;
constexpr int SM_XL = SM_ZERO + 160;
constexpr int SM_TOTAL = SM_XL + 8 * XSTR;
static_assert(SM_TOTAL <= 232448, "shared memory");

constexpr unsigned long long POL_EF = 0x12F0000000000000ull;
constexpr unsigned long long POL_EN = 0x16F0000000000000ull;

#define RT_MASK 0xF2E0u
#define RT_MASK2 0xEAE0u
#define WO_AT1 5
#define FFN_PROMO CU_TENSOR_MAP_L2_PROMOTION_NONE
#define FFN_POL POL_EF
#define HAS_FFN (__float_as_uint(misc[1]) < DN0 + NDN)
#define ACC_STR 1
#define NPRE 6

#define STAG 200
#define L1R 3
#define PRE1 13
#define HOLD 2
#define DNTH 23
constexpr int V0_AT = 8;
constexpr unsigned long long SEQ1 = 0x2765431076543210ull;
constexpr uint32_t IN_S1 = 0xAA49, IN_S0 = 0x124, PARITY1 = 0x6638, PARITY2 = 0xCE;
#define KEEP4 1
constexpr int NQ = 48;
constexpr int SPIN_CAP = 1 << 19;
constexpr uint32_t ONES = 0x3F803F80u;

struct alignas(1024) Scratch {
    uint4 hx[NCTA * 48];
    uint4 pad0[32 * 5 * 32 + 160];
    uint4 acc[2][216 * 8];
    uint4 ay[160];
    uint4 ah[NG * 8];
    uint2 mx[NH * 32];
    uint32_t ticket[32];
    uint32_t pad1[32];
};
__device__ Scratch g_scr;
#define PROF_T(i)
#define PROF_X(i)
#define PC(i)

__device__ __forceinline__ uint32_t smem_u32(const void* p) { return (uint32_t)__cvta_generic_to_shared(p); }
__device__ __forceinline__ void mbar_init(uint32_t bar, uint32_t cnt) {
    asm volatile("mbarrier.init.shared::cta.b64 [%0], %1;" ::"r"(bar), "r"(cnt) : "memory");
}
__device__ __forceinline__ void mbar_expect_tx(uint32_t bar, uint32_t bytes) {
    asm volatile("mbarrier.arrive.expect_tx.shared::cta.b64 _, [%0], %1;" ::"r"(bar), "r"(bytes) : "memory");
}
__device__ __forceinline__ bool mbar_test(uint32_t bar, uint32_t parity) {
    uint32_t done;
    asm volatile("{\n.reg .pred p;\nmbarrier.try_wait.parity.shared::cta.b64 p, [%1], %2;\nselp.u32 %0, 1, 0, p;\n}"
                 : "=r"(done) : "r"(bar), "r"(parity) : "memory");
    return done;
}
__device__ __forceinline__ void mbar_wait(uint32_t bar, uint32_t parity) {
    int it = 0;
    while (!mbar_test(bar, parity) && ++it < SPIN_CAP) {}
}
__device__ __forceinline__ void tma2d(uint32_t dst, const CUtensorMap* map, int c0, int c1, uint32_t bar, unsigned long long pol) {
    asm volatile("cp.async.bulk.tensor.2d.shared::cluster.global.mbarrier::complete_tx::bytes.L2::cache_hint [%0], [%1, {%3, %4}], [%2], %5;"
                 ::"r"(dst), "l"(map), "r"(bar), "r"(c0), "r"(c1), "l"(pol) : "memory");
}
__device__ __forceinline__ void tma3d(uint32_t dst, const CUtensorMap* map, int c0, int c1, int c2, uint32_t bar, unsigned long long pol) {
    asm volatile("cp.async.bulk.tensor.3d.shared::cluster.global.mbarrier::complete_tx::bytes.L2::cache_hint [%0], [%1, {%3, %4, %5}], [%2], %6;"
                 ::"r"(dst), "l"(map), "r"(bar), "r"(c0), "r"(c1), "r"(c2), "l"(pol) : "memory");
}
__device__ __forceinline__ void tile_load(uint32_t dst, const CUtensorMap* map, int row, uint32_t bar, uint32_t dep, uint32_t zero) {
    asm volatile("{\n.reg .pred p;\n.reg .b32 n;\nmad.lo.u32 n, %5, %6, 6144;\nelect.sync _|p, 0xffffffff;\n"
                 "@p mbarrier.arrive.expect_tx.shared::cta.b64 _, [%2], n;\n"
                 "@p cp.async.bulk.tensor.2d.shared::cluster.global.mbarrier::complete_tx::bytes.L2::cache_hint [%0], [%1, {0, %3}], [%2], %4;\n}"
                 ::"r"(dst), "l"(map), "r"(bar), "r"(row), "l"(POL_EF), "r"(dep), "r"(zero) : "memory");
}
__device__ __forceinline__ void tile_keep(const CUtensorMap* map, int row) {
    asm volatile("{\n.reg .pred p;\nelect.sync _|p, 0xffffffff;\n"
                 "@p cp.async.bulk.prefetch.tensor.2d.L2.global.L2::cache_hint [%0, {0, %1}], %2;\n}"
                 ::"l"(map), "r"(row), "l"(POL_EN) : "memory");
}
__device__ __forceinline__ void tile_load_l1(uint32_t dst, const void* base, int row, uint32_t bar, int lane) {
    const char* g = static_cast<const char*>(base) + (size_t)row * 128 + lane * 16;
    const uint32_t s0 = dst + (lane >> 3) * 128 + (((lane & 7) ^ (lane >> 3)) << 4), s1 = s0 ^ 64;
#pragma unroll
    for (int k = 0; k < 12; k++)
        asm volatile("cp.async.ca.shared.global.L2::cache_hint [%0], [%1], 16, %2;" ::"r"(((k & 1) ? s1 : s0) + k * 512), "l"(g + k * 512), "l"(POL_EF) : "memory");
    asm volatile("cp.async.mbarrier.arrive.shared::cta.b64 [%0];" ::"r"(bar) : "memory");
    __syncwarp();
    if (lane == 0) asm volatile("mbarrier.arrive.shared::cta.b64 _, [%0];" ::"r"(bar) : "memory");
}
__device__ __forceinline__ bool elect_one() {
    uint32_t p;
    asm volatile("{\n.reg .pred p;\nelect.sync _|p, 0xffffffff;\nselp.u32 %0, 1, 0, p;\n}" : "=r"(p));
    return p;
}
__device__ __forceinline__ void lds128(uint32_t addr, uint32_t& a, uint32_t& b, uint32_t& c, uint32_t& d) {
    asm volatile("ld.shared.v4.u32 {%0,%1,%2,%3}, [%4];" : "=r"(a), "=r"(b), "=r"(c), "=r"(d) : "r"(addr) : "memory");
}
__device__ __forceinline__ void lds128p(uint32_t addr, uint32_t on, uint32_t& a, uint32_t& b, uint32_t& c, uint32_t& d) {
    asm volatile("{\n.reg .pred p;\nsetp.ne.u32 p, %5, 0;\n@p ld.shared.v4.u32 {%0,%1,%2,%3}, [%4];\n}" : "+r"(a), "+r"(b), "+r"(c), "+r"(d) : "r"(addr), "r"(on) : "memory");
}
__device__ __forceinline__ void lds64(uint32_t addr, uint32_t& a, uint32_t& b) {
    asm volatile("ld.shared.v2.u32 {%0,%1}, [%2];" : "=r"(a), "=r"(b) : "r"(addr) : "memory");
}
__device__ __forceinline__ void ldsm4t(uint32_t addr, uint32_t (&a)[4]) {
    asm volatile("ldmatrix.sync.aligned.m8n8.x4.trans.shared.b16 {%0,%1,%2,%3}, [%4];" : "=r"(a[0]), "=r"(a[1]), "=r"(a[2]), "=r"(a[3]) : "r"(addr) : "memory");
}
__device__ __forceinline__ void mma16816(float (&c)[4], uint32_t a0, uint32_t a1, uint32_t a2, uint32_t a3, uint32_t b0, uint32_t b1) {
    asm("mma.sync.aligned.m16n8k16.row.col.f32.bf16.bf16.f32 {%0,%1,%2,%3}, {%4,%5,%6,%7}, {%8,%9}, {%0,%1,%2,%3};"
        : "+f"(c[0]), "+f"(c[1]), "+f"(c[2]), "+f"(c[3]) : "r"(a0), "r"(a1), "r"(a2), "r"(a3), "r"(b0), "r"(b1));
}
__device__ __forceinline__ void mma16816v(float (&c)[4], uint32_t a0, uint32_t a1, uint32_t a2, uint32_t a3, uint32_t b0, uint32_t b1) {
    asm volatile("mma.sync.aligned.m16n8k16.row.col.f32.bf16.bf16.f32 {%0,%1,%2,%3}, {%4,%5,%6,%7}, {%8,%9}, {%0,%1,%2,%3};"
        : "+f"(c[0]), "+f"(c[1]), "+f"(c[2]), "+f"(c[3]) : "r"(a0), "r"(a1), "r"(a2), "r"(a3), "r"(b0), "r"(b1));
}
__device__ __forceinline__ int xpos(int w) {
    const int seg = w / 40, r = w - 40 * seg;
    return 40 * seg + (r < 32 ? (r & 16) + 4 * (r & 3) + ((r >> 2) & 3) : 32 + 2 * (r & 3) + ((r >> 2) & 1));
}
#define NA_LD ""
#define NA_ST ""
__device__ __forceinline__ void st_pkt(uint4* p, uint32_t a, uint32_t b, uint32_t c, uint32_t d) {
    asm volatile("{\n.reg .b128 t;\n.reg .b64 lo, hi;\nmov.b64 lo, {%1,%2};\nmov.b64 hi, {%3,%4};\nmov.b128 t, {lo,hi};\nst.relaxed.gpu.global" NA_ST ".b128 [%0], t;\n}"
                 ::"l"(p), "r"(a), "r"(b), "r"(c), "r"(d) : "memory");
}
__device__ __forceinline__ void st_pktf(uint4* p, float a, float b, float c, float d, uint32_t bit) {
    st_pkt(p, __float_as_uint(a), __float_as_uint(b), __float_as_uint(c), (__float_as_uint(d) & ~1u) | bit);
}
__device__ __forceinline__ void red_pkt(uint4* p, float a, float b, float c) {
    asm volatile("red.relaxed.gpu.global.add.v4.f32 [%0], {%1,%2,%3,%4};" ::"l"(p), "f"(a), "f"(b), "f"(c), "f"(1.0f) : "memory");
}
__device__ __forceinline__ uint4 ld_pkt(const uint4* p) {
    uint4 v;
    asm volatile("{\n.reg .b128 t;\n.reg .b64 lo, hi;\nld.relaxed.gpu.global" NA_LD ".b128 t, [%4];\nmov.b128 {lo,hi}, t;\nmov.b64 {%0,%1}, lo;\nmov.b64 {%2,%3}, hi;\n}"
                 : "=r"(v.x), "=r"(v.y), "=r"(v.z), "=r"(v.w) : "l"(p) : "memory");
    return v;
}
__device__ __forceinline__ uint2 ld_pkt2(const uint2* p) {
    unsigned long long v;
    asm volatile("ld.relaxed.gpu.global" NA_LD ".b64 %0, [%1];" : "=l"(v) : "l"(p) : "memory");
    return make_uint2((uint32_t)v, (uint32_t)(v >> 32));
}
__device__ __forceinline__ void st_pkt2(uint2* p, uint32_t a, uint32_t b) {
    asm volatile("st.relaxed.gpu.global" NA_ST ".b64 [%0], %1;" ::"l"(p), "l"((unsigned long long)a | ((unsigned long long)b << 32)) : "memory");
}
__device__ __forceinline__ float ex2(float x) { float y; asm("ex2.approx.ftz.f32 %0, %1;" : "=f"(y) : "f"(x)); return y; }
__device__ __forceinline__ float rcp(float x) { float y; asm("rcp.approx.ftz.f32 %0, %1;" : "=f"(y) : "f"(x)); return y; }
__device__ __forceinline__ uint32_t pack2(float lo, float hi) {
    uint32_t r; asm("cvt.rn.bf16x2.f32 %0, %1, %2;" : "=r"(r) : "f"(hi), "f"(lo)); return r;
}
__device__ __forceinline__ float bf_lo(uint32_t w) { return __uint_as_float(w << 16); }
__device__ __forceinline__ float bf_hi(uint32_t w) { return __uint_as_float(w & 0xffff0000u); }
__device__ __forceinline__ float bfr(float x) { return bf_lo(pack2(x, 0.f)); }
__device__ __forceinline__ float f_(uint32_t u) { return __uint_as_float(u); }

template <int SK, typename AddrF>
__device__ __forceinline__ void gemv15(float (&cc)[3][4], uint32_t (&pre)[6][4], AddrF ad, uint32_t px, uint32_t px2, float& sv, float so) {
    uint32_t x0[4], x1[4], a[3][4];
    asm volatile("ld.shared.v4.u32 {%0,%1,%2,%3}, [%20];\nld.shared.v4.u32 {%4,%5,%6,%7}, [%20+64];\n"
                 "ldmatrix.sync.aligned.m8n8.x4.trans.shared.b16 {%8,%9,%10,%11}, [%21];\n"
                 "ldmatrix.sync.aligned.m8n8.x4.trans.shared.b16 {%12,%13,%14,%15}, [%22];\n"
                 "ldmatrix.sync.aligned.m8n8.x4.trans.shared.b16 {%16,%17,%18,%19}, [%23];\nbar.warp.sync 0xffffffff;"
                 : "=r"(x0[0]), "=r"(x0[1]), "=r"(x0[2]), "=r"(x0[3]), "=r"(x1[0]), "=r"(x1[1]), "=r"(x1[2]), "=r"(x1[3]),
                   "=r"(a[0][0]), "=r"(a[0][1]), "=r"(a[0][2]), "=r"(a[0][3]), "=r"(a[1][0]), "=r"(a[1][1]), "=r"(a[1][2]), "=r"(a[1][3]),
                   "=r"(a[2][0]), "=r"(a[2][1]), "=r"(a[2][2]), "=r"(a[2][3])
                 : "r"(px), "r"(ad(0) + 2 * SK), "r"(ad(1) + 2 * SK), "r"(ad(2) + 2 * SK) : "memory");
    __syncwarp();
    sv += __shfl_xor_sync(0xffffffffu, so, 16);
#pragma unroll
    for (int i = 0; i < 3; i++) {
        cc[i][0] = cc[i][1] = cc[i][2] = cc[i][3] = 0.f;
        mma16816v(cc[i], pre[i][0], pre[i][1], pre[i][2], pre[i][3], x0[0], x0[1]);
    }
    sv += __shfl_xor_sync(0xffffffffu, sv, 8);
#pragma unroll
    for (int i = 0; i < 3; i++) {
        mma16816v(cc[i], pre[3 + i][0], pre[3 + i][1], pre[3 + i][2], pre[3 + i][3], x0[2], x0[3]);
        ldsm4t(ad(i) + 3 * SK, pre[i]);
    }
    lds64(px2, x0[0], x0[1]);
    __syncwarp();
    sv += __shfl_xor_sync(0xffffffffu, sv, 4);
#pragma unroll
    for (int i = 0; i < 3; i++) {
        mma16816v(cc[i], a[i][0], a[i][1], a[i][2], a[i][3], x1[0], x1[1]);
        ldsm4t(ad(i) + 4 * SK, pre[3 + i]);
    }
    __syncwarp();
    sv += __shfl_xor_sync(0xffffffffu, sv, 2);
#pragma unroll
    for (int i = 0; i < 3; i++) mma16816v(cc[i], pre[i][0], pre[i][1], pre[i][2], pre[i][3], x1[2], x1[3]);
    sv += __shfl_xor_sync(0xffffffffu, sv, 1);
#pragma unroll
    for (int i = 0; i < 3; i++) mma16816v(cc[i], pre[3 + i][0], pre[3 + i][1], pre[3 + i][2], pre[3 + i][3], x0[0], x0[1]);
}
__device__ __forceinline__ void gemv15r(float (&cc)[3][4], const uint32_t (&pre)[6][4], const uint32_t (&ext)[NQ][4], uint32_t px, uint32_t px2, float& sv, float so) {
    uint32_t x0[4], x1[4], x2[2];
    float cd[3][4];
    lds128(px, x0[0], x0[1], x0[2], x0[3]);
    lds128(px + 64, x1[0], x1[1], x1[2], x1[3]);
    lds64(px2, x2[0], x2[1]);
    sv += __shfl_xor_sync(0xffffffffu, so, 16);
#pragma unroll
    for (int i = 0; i < 3; i++) {
        cc[i][0] = cc[i][1] = cc[i][2] = cc[i][3] = cd[i][0] = cd[i][1] = cd[i][2] = cd[i][3] = 0.f;
        mma16816v(cc[i], pre[i][0], pre[i][1], pre[i][2], pre[i][3], x0[0], x0[1]);
        mma16816v(cd[i], pre[3 + i][0], pre[3 + i][1], pre[3 + i][2], pre[3 + i][3], x0[2], x0[3]);
    }
    sv += __shfl_xor_sync(0xffffffffu, sv, 8);
#pragma unroll
    for (int i = 0; i < 3; i++) {
        mma16816v(cc[i], ext[i][0], ext[i][1], ext[i][2], ext[i][3], x1[0], x1[1]);
        mma16816v(cd[i], ext[3 + i][0], ext[3 + i][1], ext[3 + i][2], ext[3 + i][3], x1[2], x1[3]);
    }
    sv += __shfl_xor_sync(0xffffffffu, sv, 4);
#pragma unroll
    for (int i = 0; i < 3; i++) mma16816v(cc[i], ext[6 + i][0], ext[6 + i][1], ext[6 + i][2], ext[6 + i][3], x2[0], x2[1]);
    sv += __shfl_xor_sync(0xffffffffu, sv, 2);
    sv += __shfl_xor_sync(0xffffffffu, sv, 1);
#pragma unroll
    for (int i = 0; i < 3; i++) { cc[i][0] += cd[i][0]; cc[i][1] += cd[i][1]; cc[i][2] += cd[i][2]; cc[i][3] += cd[i][3]; }
}

__device__ __forceinline__ float warp_max(float x) {
    int i = __float_as_int(x);
    i = __reduce_max_sync(0xffffffffu, i ^ ((i >> 31) & 0x7fffffff));
    return __int_as_float(i ^ ((i >> 31) & 0x7fffffff));
}
__device__ __forceinline__ void idle(uint32_t clk) {
    uint32_t t0, t;
    asm volatile("mov.u32 %0, %%clock;" : "=r"(t0) :: "memory");
    do asm volatile("mov.u32 %0, %%clock;" : "=r"(t) :: "memory"); while (t - t0 < clk);
}
__device__ __forceinline__ uint32_t now_ns() { uint32_t t; asm volatile("mov.u32 %0, %%globaltimer_lo;" : "=r"(t)); return t; }
__device__ __forceinline__ int opq(int x) { asm volatile("" : "+r"(x)); return x; }
__device__ __forceinline__ uint32_t opq(uint32_t x) { asm volatile("" : "+r"(x)); return x; }
__device__ __forceinline__ uint32_t pin(uint32_t x) { return __shfl_sync(0xffffffffu, x, threadIdx.x & 31); }
template <typename T> __device__ __forceinline__ T* pin(T* p) {
    const unsigned long long v = (unsigned long long)p;
    return (T*)((unsigned long long)pin((uint32_t)v) | (unsigned long long)pin((uint32_t)(v >> 32)) << 32);
}
template <typename T> __device__ __forceinline__ T* opq(T* p) { asm volatile("" : "+l"(p)); return p; }
__device__ __forceinline__ float4 lds4f(uint32_t a) { float4 v; asm volatile("ld.shared.v4.f32 {%0,%1,%2,%3}, [%4];" : "=f"(v.x), "=f"(v.y), "=f"(v.z), "=f"(v.w) : "r"(a) : "memory"); return v; }
__device__ __forceinline__ float2 lds2f(uint32_t a) { float2 v; asm volatile("ld.shared.v2.f32 {%0,%1}, [%2];" : "=f"(v.x), "=f"(v.y) : "r"(a) : "memory"); return v; }
__device__ __forceinline__ void ln_stats(uint32_t st, float& mean, float& inv) {
    const float4 a = lds4f(st), b = lds4f(st + 16), c = lds4f(st + 32), d = lds4f(st + 48);
    const float s2 = ((a.x + a.z) + (b.x + b.z)) + ((c.x + c.z) + (d.x + d.z));
    const float md = (((a.y + a.w) + (b.y + b.w)) + ((c.y + c.w) + (d.y + d.w))) * (1.0f / DM);
    const float var = fmaxf(s2 * (1.0f / DM) - md * md, 0.f);
    mean = bfr(md);
    asm("rsqrt.approx.ftz.f32 %0, %1;" : "=f"(inv) : "f"(var + 1e-5f));
}
__device__ __forceinline__ void sts32(uint32_t a, float v) { asm volatile("st.shared.f32 [%0], %1;" ::"r"(a), "f"(v) : "memory"); }
__device__ __forceinline__ void sts64(uint32_t a, float v, float w) { asm volatile("st.shared.v2.f32 [%0], {%1,%2};" ::"r"(a), "f"(v), "f"(w) : "memory"); }

__device__ __forceinline__ uint32_t prmt(uint32_t a, uint32_t b, uint32_t s) { uint32_t r; asm("prmt.b32 %0, %1, %2, %3;" : "=r"(r) : "r"(a), "r"(b), "r"(s)); return r; }
__device__ __forceinline__ uint32_t bmul2(uint32_t a, uint32_t b) { uint32_t r; asm("mul.rn.bf16x2 %0, %1, %2;" : "=r"(r) : "r"(a), "r"(b)); return r; }
__device__ __forceinline__ void sts128(uint32_t addr, uint32_t a, uint32_t b, uint32_t c, uint32_t d) {
    asm volatile("st.shared.v4.u32 [%0], {%1,%2,%3,%4};" ::"r"(addr), "r"(a), "r"(b), "r"(c), "r"(d) : "memory");
}
__device__ __forceinline__ uint4 ldg128(const uint4* p) {
    uint4 v;
    asm volatile("ld.volatile.global.v4.u32 {%0,%1,%2,%3}, [%4];" : "=r"(v.x), "=r"(v.y), "=r"(v.z), "=r"(v.w) : "l"(p) : "memory");
    return v;
}
__device__ __forceinline__ uint32_t lds32(uint32_t a) { uint32_t v; asm volatile("ld.shared.u32 %0, [%1];" : "=r"(v) : "r"(a) : "memory"); return v; }
__device__ __forceinline__ uint32_t lds16(uint32_t a) { unsigned short v; asm volatile("ld.shared.u16 %0, [%1];" : "=h"(v) : "r"(a) : "memory"); return v; }
__device__ __forceinline__ void unpack8(uint32_t la, uint32_t lb, uint32_t c, uint32_t (&w)[4]) {
    const uint32_t ha = c & 0x87878787u, hb = __funnelshift_l(c, c, 4) & 0x87878787u;
    w[0] = prmt(la, ha, 0x5140); w[1] = prmt(la, ha, 0x7362); w[2] = prmt(lb, hb, 0x5140); w[3] = prmt(lb, hb, 0x7362);
}
__device__ __forceinline__ uint32_t bdiff2(uint32_t y, uint32_t inv, uint32_t x) {
    uint32_t r;
    asm("{\n.reg .b32 n;\nneg.bf16x2 n, %3;\nfma.rn.bf16x2 %0, %1, %2, n;\n}" : "=r"(r) : "r"(y), "r"(inv), "r"(x));
    return r;
}
__device__ __forceinline__ uint32_t pack_scale(uint32_t tile, int lane, uint32_t inv_addr) {
    uint32_t m = 0;
#pragma unroll 1
    for (int k = 0; k < 12; k++) {
        uint32_t a, b, c, d;
        lds128(tile + k * 512 + lane * 16, a, b, c, d);
        asm("max.xorsign.abs.bf16x2 %0, %0, %1;" : "+r"(a) : "r"(b));
        asm("max.xorsign.abs.bf16x2 %0, %0, %1;" : "+r"(c) : "r"(d));
        asm("max.xorsign.abs.bf16x2 %0, %0, %1;" : "+r"(a) : "r"(c));
        asm("max.xorsign.abs.bf16x2 %0, %0, %1;" : "+r"(m) : "r"(a));
    }
    m = __reduce_max_sync(0xffffffffu, max(m & 0x7fffu, (m >> 16) & 0x7fffu));
    const uint32_t inv = (112u + min((m + 0x28u) >> 7, 141u)) * 0x00800080u;
    if (lane == 0) asm volatile("st.shared.u32 [%0], %1;" ::"r"(inv_addr), "r"(inv) : "memory");
    return inv;
}

#define K_OFF(i) ((uint32_t)((3 * ((g >> 1) + 4 * (g & 1)) + ((i) >> 1)) * 128 + ((t ^ ((3 * ((g >> 1) + 4 * (g & 1)) + ((i) >> 1)) & 7) ^ (((i) & 1) << 2)) << 4)))
#define V_OFF(i) ((uint32_t)((6 * t + (i)) * 128 + ((g ^ ((6 * t + (i)) & 7)) << 4)))
template <bool ISV, typename DST>
__device__ __forceinline__ void pack_tile(uint32_t tile, int tau, int nm, uint32_t inv, uint32_t xl, int lane, DST dst) {
    const int g = lane >> 2, t = lane & 3;
    const uint32_t scl = 254u * 0x00800080u - inv;
#pragma unroll 1
    for (int m = 0; m < nm; m++) {
        const int row = ISV ? 6 * t + 2 * m : 3 * ((g >> 1) + 4 * (g & 1)) + m;
        const uint32_t a0 = tile + row * 128 + (((ISV ? g : t) ^ (row & 7)) << 4), a1 = ISV ? (a0 ^ 16) + 128 : a0 ^ 64;
        uint32_t l[8], cw[4], ck = 0, cd = 0;
#pragma unroll
        for (int r = 0; r < 4; r++) {
            uint32_t w0, w1, w2, w3;
            lds128(((r & 1) ? a1 : a0) + (r >> 1) * 3072, w0, w1, w2, w3);
            const uint32_t y0 = bmul2(w0, scl), y1 = bmul2(w1, scl), y2 = bmul2(w2, scl), y3 = bmul2(w3, scl);
            cd |= bdiff2(y0, inv, w0) | bdiff2(y1, inv, w1);
            cd |= bdiff2(y2, inv, w2) | bdiff2(y3, inv, w3);
            const uint32_t ha = prmt(y0, y1, 0x7531), hb = prmt(y2, y3, 0x7531);
            l[2 * r] = prmt(y0, y1, 0x6420); l[2 * r + 1] = prmt(y2, y3, 0x6420);
            asm("lop3.b32 %0, %1, 0x87878787, %2, 0xe2;" : "=r"(cw[r]) : "r"(ha), "r"(__funnelshift_r(hb, hb, 4)));
            ck |= ha | hb;
        }
        const uint32_t bad = __ballot_sync(0xffffffffu, (ck & 0x78787878u) | cd);
        if (bad) {
            const int src = __ffs(bad) - 1;
            const uint32_t b0 = __shfl_sync(0xffffffffu, a0, src), b1 = __shfl_sync(0xffffffffu, a1, src), n0 = lds32(xl);
            const uint32_t ax = ((lane & 8) ? b1 : b0) + (lane >> 4) * 3072 + 2 * (lane & 7), x = lds16(ax), y = bmul2(x, scl);
            const bool out = (y & 0x7800u) | bdiff2(y, inv, x);
            const uint32_t n = n0 + __popc(__ballot_sync(0xffffffffu, out) << (31 - lane)) - 1;
            if (out) {
                asm volatile("st.shared.u16 [%0], %1;" ::"r"(ax), "h"((unsigned short)0) : "memory");
                if (n < XCAP) sts32(xl + 16 + 4 * n, f_(x << 16 | tau << 12 | src << 7 | m << 5 | lane));
            }
            if (lane == 31) sts32(xl, f_(n + 1));
            __syncwarp();
            if (n0 <= XCAP) { m--; continue; }
        }
        uint32_t d[3] = {a0, a1, a0 + 3072};
        dst(m, d);
        sts128(d[0], l[0], l[1], l[2], l[3]);
        sts128(d[1], l[4], l[5], l[6], l[7]);
        sts128(d[2], cw[0], cw[1], cw[2], cw[3]);
    }
}

struct Maps { CUtensorMap k, v, wq, wo, w1, w3, w2, vr; const void* vp; const void* kp; uint32_t zero; };
#define RT_SEL ((wu & 1) ? RT_MASK2 : RT_MASK)
#define PFK 5
#define Q_AT 3
#define WO_T0 32200
#define K5D 370
#define PK_AT 6

__device__ __forceinline__ void load_ffn(const Maps& maps, int b, uint32_t dst, uint32_t bar) {
    const bool gu = b < NG;
    mbar_expect_tx(bar, gu ? 61440 : 49152);
    tma3d(dst, gu ? (b < NG / 2 ? &maps.w1 : &maps.w3) : &maps.w2, gu ? 48 * (b & (NG / 2 - 1)) : 16 * (b - DN0), 0, 0, bar, FFN_POL);
}

__device__ __forceinline__ void load_wo(const Maps& maps, uint32_t dst, int h, int c, uint32_t bar, int nbox) {
#pragma unroll 1
    for (int i = 0; i < nbox; i++) {
        if (!(i & 1)) mbar_expect_tx(bar + 4 * i, i + 1 < nbox ? 20480 : 10240);
        tma3d(dst + i * 10240, &maps.wo, 0, 5 * c, h * DH + 32 * i, bar + 4 * (i & 6), POL_EF);
    }
}

__global__ void __launch_bounds__(NT, 1)
decode_kernel(const __grid_constant__ Maps maps, const __nv_bfloat16* __restrict__ x_in, __nv_bfloat16* __restrict__ out) {
    extern __shared__ __align__(1024) unsigned char smem[];
    const int tid = threadIdx.x, warp = tid >> 5, lane = tid & 31;
    const int wu = __shfl_sync(0xffffffffu, tid >> 5, 0);
    const int b = blockIdx.x, h = b >> 2, c = b & 3;
    const uint32_t sb = smem_u32(smem);
    const uint32_t qbar = sb + SM_BAR + 16 * 8, fbar = qbar + 8, wbar = qbar + 16;
    uint32_t* xs32 = reinterpret_cast<uint32_t*>(smem + SM_XS);
    float* rr = reinterpret_cast<float*>(smem + SM_R);
    float* misc = reinterpret_cast<float*>(smem + SM_MISC);

    PROF_T(0);
    {
        uint2 xv = make_uint2(0u, 0u);
        const uint32_t t_start = now_ns();
        if (elect_one()) {
            const uint32_t rb = sb + SM_BAR + wu * 16, xb = sb + SM_XBAR + wu * 8;
            mbar_init(rb, 1); mbar_init(rb + 8, 1); mbar_init(xb, 1);
            if (wu == 0) mbar_init(qbar, 1);
            asm volatile("fence.mbarrier_init.release.cluster;" ::: "memory");
            const int row = (h * SK + (SK - WIN) + c * 1024 + wu * 128) * 3;
            const uint32_t ring = sb + SM_RING + wu * 2 * TILE;
#pragma unroll
            for (int n = 0; n < 3; n++) {
                const uint32_t bar = ((IN_S1 >> n) & 1) ? rb + 8 : ((IN_S0 >> n) & 1) ? rb : xb;
                mbar_expect_tx(bar, TILE);
                tma2d(((IN_S1 >> n) & 1) ? ring + TILE : ((IN_S0 >> n) & 1) ? ring : sb + SM_B + wu * TILE, &maps.k, 0, row + 48 * n, bar, POL_EF);
                if (n == 0 && wu == 0) {
                    mbar_expect_tx(qbar, 61440);
                    tma3d(sb + SM_Q, &maps.wq, 0, 160 * c, 3 * h, qbar, POL_EF);
                }
            }
            if (wu == 1) {
                mbar_init(fbar, 1);
#pragma unroll
                for (int i = 0; i < 3; i++) mbar_init(wbar + 8 * i, 1);
                asm volatile("fence.mbarrier_init.release.cluster;" ::: "memory");
            }
            if (wu >= 2) {
                const CUtensorMap* mp = wu == 2 ? &maps.v : wu == 3 ? &maps.wo : wu == 4 ? &maps.w1 : wu == 5 ? &maps.w3 : wu == 6 ? &maps.w2 : &maps.vr;
                asm volatile("prefetch.tensormap [%0];" ::"l"(mp) : "memory");
            }
        }
        if (tid < 160) asm volatile("ld.global.nc.v2.u32 {%0,%1}, [%2];" : "=r"(xv.x), "=r"(xv.y) : "l"(x_in + 4 * tid) : "memory");
        if (tid == 96) { misc[2] = 0.f; misc[3] = 0.f; }
        if (lane == 1) *reinterpret_cast<uint2*>(smem + SM_XL + warp * XSTR) = make_uint2(0u, t_start + WO_T0);
        if (tid >= 128 && tid < 148) {
            const uint32_t v = tid < 138 ? ONES : 0u;
            reinterpret_cast<uint4*>(smem + SM_ONE)[tid - 128] = make_uint4(v, v, v, v);
        }
        if (tid < 160) { xs32[xpos(2 * tid)] = xv.x; xs32[xpos(2 * tid + 1)] = xv.y; }
        __syncthreads();
        PROF_T(14);
        if (b == 0 && tid >= 232) asm volatile("st.relaxed.gpu.global.u32 [%0], %1;" ::"l"(g_scr.ticket + tid - 232), "r"(0) : "memory");
        if (tid == 64 || (tid == 65 && b < 216 - NCTA)) st_pkt(&g_scr.acc[1][(b + NCTA * (tid - 64)) * ACC_STR], 0, 0, 0, 0);
    }

    uint32_t kq[NQ][4];
    const float SC = 0.07216878364870322f * 1.4426950408889634f;

#pragma unroll 1
    for (int ph = 0; ph < 3; ph++) {
        const int layer = ph >> 1;
        const uint32_t tag = layer + 1;
        PROF_T(1 + layer * 16);
        if (ph) {
        {
            const int tl = opq(tid), warp = tl >> 5, lane = tl & 31, g = lane >> 2, t = lane & 3, mat = lane >> 3, r8 = lane & 7;
            const int kh = warp >> 2, mg = warp & 3;
            uint32_t aq[3];
#pragma unroll
            for (int i = 0; i < 3; i++) {
                const int ch = 6 * mg + 2 * i + (mat & 1);
                aq[i] = sb + SM_Q + (80 * kh + (mat >> 1) * 8 + r8) * 128 + (ch >> 3) * 20480 + (((ch & 7) ^ r8) << 4);
            }
#define PF_K5 if (layer == 1 && PFK) tile_keep(&maps.k, (h * SK + (SK - WIN) + c * 1024 + wu * 128 + PFK * 16) * 3);
            uint2 xv = make_uint2(0u, 0u);
            mbar_wait(qbar, 0);
            uint32_t pre[6][4];
#pragma unroll
            for (int n = 0; n < 6; n++) ldsm4t(aq[n % 3] + (n / 3) * 2048, pre[n]);
            if (layer == 1) {
                __syncthreads();
                if (elect_one()) {
                    const uint32_t bar = sb + SM_BAR + wu * 16;
                    asm volatile("mbarrier.expect_tx.relaxed.cta.shared::cta.b64 [%0], 1536;" ::"r"(bar) : "memory");
#pragma unroll
                    for (int k = 0; k < 3; k++)
                        tma2d(sb + SM_Q + v1_pos(3 * wu + k), &maps.vr, 0, (h * SK + (SK - WIN) + c * 1024 + wu * 128) / 2 + 8 + 2 * k, bar, POL_EF);
                }
            }
            const uint32_t pm = opq(g == 1 ? sb + SM_ONE : sb + SM_XS + 160 * (2 * c + kh) + 16 * t), pm2 = opq(pm + 128 - (g == 1 ? 0 : 8 * t));
            const uint32_t dq = opq(sb + SM_R + 8 * (kh * 192 + 48 * mg + g)), ds = opq(sb + SM_ST + 8 * warp + (lane < 16 ? 4 : 0));
            const bool wr = t == 0, ws = (lane & 15) == 0, lo = lane < 16;
            if (tl < 160) {
                const int p0 = xpos(2 * tl), p1 = xpos(2 * tl + 1);
                if (layer == 1) {
                    uint4 v;
                    int it = 0;
                    do { v = ld_pkt(&g_scr.ay[tl]); } while (!__all_sync(0xffffffffu, v.w == 1) && ++it < SPIN_CAP);
                    xv = make_uint2(v.x, v.y);
                    xs32[p0] = xv.x; xs32[p1] = xv.y;
                } else xv = make_uint2(xs32[p0], xs32[p1]);
            }
            if (layer) PC(24);
            if (layer) __syncthreads();
            PF_K5
            if (layer) PC(25);
            PROF_T(13 + layer * 16);
            const float e0 = bf_lo(xv.x), e1 = bf_hi(xv.x), e2 = bf_lo(xv.y), e3 = bf_hi(xv.y);
            const float s1 = (e0 + e1) + (e2 + e3), s2 = (e0 * e0 + e1 * e1) + (e2 * e2 + e3 * e3);
            float sv = lo ? s1 : s2, cc[3][4];
            gemv15<2048>(cc, pre, [&](int i) { return aq[i]; }, pm, pm2, sv, lo ? s2 : s1);
            if (wr) {
#pragma unroll
                for (int i = 0; i < 3; i++) { sts64(dq + 128 * i, cc[i][0], cc[i][1]); sts64(dq + 128 * i + 64, cc[i][2], cc[i][3]); }
            }
            if (ws) sts32(ds, sv);
        }
        const uint32_t pa = opq(sb + SM_R + 32 * opq(tid)), st = opq(sb + SM_ST);
        uint4* const pq = opq(&g_scr.hx[b * 48 + opq(tid)]);
        if (layer) PC(26);
        __syncthreads();
        if (layer) PC(27);
        PROF_T(33 + layer * 16);
        if (tid < 48) {
            float mean, inv;
            ln_stats(st, mean, inv);
            const float4 a0 = lds4f(pa), a1 = lds4f(pa + 16), b0 = lds4f(pa + 1536), b1 = lds4f(pa + 1552);
            float q0 = inv * ((a0.x + b0.x) - mean * (a0.y + b0.y)), q1 = inv * ((a0.z + b0.z) - mean * (a0.w + b0.w));
            float q2 = inv * ((a1.x + b1.x) - mean * (a1.y + b1.y)), q3 = inv * ((a1.z + b1.z) - mean * (a1.w + b1.w));
            st_pktf(pq, q0, q1, q2, q3, 1);
        }
        if (layer == 1 && tid >= 192 && tid < 194 && b < 108) st_pkt(&g_scr.acc[0][(2 * b + opq(tid) - 192) * ACC_STR], 0, 0, 0, 0);
        }
        if (layer) PC(28);
        if (layer == 1 && (wu & 2)) {
            idle(K5D);
#pragma unroll 1
            for (int w = wu; w >= (wu > 4 ? wu - 2 : wu); w -= 2)
                tile_load(sb + SM_Q + c_slot(w), &maps.k, (h * SK + (SK - WIN) + c * 1024 + w * 128 + 5 * 16) * 3, sb + SM_XBAR + w * 8, 0, 0);
        }

        float sc0 = -INFINITY, sc1 = -INFINITY, sc2 = 0.f, sc3 = 0.f, mw;
        uint32_t pk0, pk1;
        float acc[3][4];
        {
            const uint32_t ring = sb + SM_RING + wu * 2 * TILE, rb = sb + SM_BAR + wu * 16;
            const uint32_t xtile = sb + SM_Q + c_slot(wu), xb = sb + SM_XBAR + wu * 8;
#define V_SEQ(n) ((int)(SEQ1 >> (4 * (n))) & 7)
#define SLOT1(n) (((IN_S1 >> (n)) & 1) ? ring + TILE : ((IN_S0 >> (n)) & 1) ? ring : sb + SM_B + wu * TILE)
#define BAR1(n) (((IN_S1 >> (n)) & 1) ? rb + 8 : ((IN_S0 >> (n)) & 1) ? rb : xb)
#define PAR1(n) ((PARITY1 >> (n)) & 1)
#define PAR2(n) ((PARITY2 >> (n)) & 1)
            const int row0 = (h * SK + (SK - WIN) + c * 1024 + wu * 128) * 3;
            auto issue1 = [&](int n, uint32_t dep, bool vph = false) {
                const CUtensorMap* mp = n < 8 ? &maps.k : &maps.v;
                const int tl = V_SEQ(n), row = row0 + tl * 48;
                const uint32_t dst = SLOT1(n), bar = BAR1(n);
                if (vph && wu < L1R && tl == 7 - (wu & 1)) {
                    tile_load_l1(dst, maps.vp, row, bar, opq(tid) & 31);
                    return;
                }
                tile_load(dst, mp, row, bar, dep, maps.zero);
                if ((RT_SEL >> (tl + (n & 8))) & 1) {
                    if (n != V0_AT + 1) tile_keep(mp, row);
                    else if ((opq(tid) & 31) < 8)
                        asm volatile("cp.async.bulk.prefetch.L2.global.L2::cache_hint [%0], 256, %1;"
                                     ::"l"(static_cast<const char*>(maps.vp) + (size_t)(row + 4 + 6 * (opq(tid) & 31)) * 128), "l"(POL_EN) : "memory");
                }
            };
            auto refill1 = [&](int s, uint32_t dep, bool vph = false) { issue1(s + (!vph || s < V0_AT ? 3 : 2), dep, vph); };
#define LANE_IDS const int tl = opq(tid), lane = tl & 31, g = lane >> 2, t = lane & 3; (void)tl; (void)lane; (void)g; (void)t;
            const uint32_t xl = sb + SM_XL + wu * XSTR;
            if (layer == 0) {
#pragma unroll 1
                for (int s = ph ? Q_AT : 0; s < (ph ? 5 : Q_AT); s++) {
                    LANE_IDS
                    const uint32_t tile = SLOT1(s);
                    mbar_wait(BAR1(s), PAR1(s));
                    const uint32_t scl = s == 0 ? pack_scale(tile, lane, xl + 8) : lds32(xl + 8);
                    pack_tile<false>(tile, s, 3, scl, xl, lane, [](int, uint32_t (&)[3]) {});
#pragma unroll
                    for (int n = 0; n < 5; n++) {
                        if (s == n) {
#pragma unroll
                            for (int m = 0; m < 3; m++) {
                                const uint32_t a = tile + K_OFF(2 * m);
                                lds128(a, kq[9 * n + 3 * m][0], kq[9 * n + 3 * m][1], kq[9 * n + 3 * m][2], kq[9 * n + 3 * m][3]);
                                lds128(a ^ 64, kq[9 * n + 3 * m + 1][0], kq[9 * n + 3 * m + 1][1], kq[9 * n + 3 * m + 1][2], kq[9 * n + 3 * m + 1][3]);
                                lds128(a + 3072, kq[9 * n + 3 * m + 2][0], kq[9 * n + 3 * m + 2][1], kq[9 * n + 3 * m + 2][2], kq[9 * n + 3 * m + 2][3]);
                            }
                        }
                    }
                    __syncwarp();
                    refill1(s, lds32(tile));
                }
                if (!ph) continue;
            }
            {
                const int tl = opq(tid);
                if (tl < 48) {
                    const int w = 2 * tl;
                    const uint32_t pos = opq(sb + SM_QS + 4 * (((w >> 2) & 3) * 24 + 2 * (w >> 4) + ((w >> 1) & 1)));
                    uint4 v[4];
                    int it = 0;
                    bool ok;
                    do {
#pragma unroll
                        for (int k = 0; k < 4; k++) v[k] = ld_pkt(&g_scr.hx[(h * 4 + k) * 48 + tl]);
                        ok = ~((v[0].w & v[1].w) & (v[2].w & v[3].w)) & 1;
                    } while (ok && ++it < SPIN_CAP);
                    sts32(pos, f_(pack2((f_(v[0].x) + f_(v[1].x)) + (f_(v[2].x) + f_(v[3].x)), (f_(v[0].y) + f_(v[1].y)) + (f_(v[2].y) + f_(v[3].y)))));
                    sts32(pos + 48, f_(pack2((f_(v[0].z) + f_(v[1].z)) + (f_(v[2].z) + f_(v[3].z)), (f_(v[0].w) + f_(v[1].w)) + (f_(v[2].w) + f_(v[3].w)))));
                }
            }
            if (layer) PC(29);
            __syncthreads();
            if (layer) PC(30);
            PROF_T(2 + layer * 16);
#define V1_REST(p) ((p) < 6 ? sb + SM_Q + v1_pos(3 * wu + ((p) >> 1)) + 256 * ((p) & 1) : ((sb + SM_R + wu * 784 + 127) & ~127u) - 1536 + 256 * (p))
#define V1_LOAD(bar) if (elect_one()) tma2d(V1_REST(6), &maps.vr, 0, row0 / 6 + 14, bar, POL_EF);
#define V1_EXPECT(bar) { if ((opq(tid) & 31) == 0) asm volatile("mbarrier.expect_tx.relaxed.cta.shared::cta.b64 [%0], 512;" ::"r"(bar) : "memory"); }
            if (layer == 1 && wu < 2) tile_load(xtile, &maps.k, row0 + 5 * 48, xb, 0, 0);
            if (layer == 1 && wu >= 4) idle(STAG);
            {
                uint32_t qf[12];
                int t;
                {
                    const int lane = opq(tid) & 31;
                    t = lane & 3;
                    const uint32_t qa = sb + SM_QS + (2 * t + ((lane >> 2) & 1)) * 48;
#pragma unroll
                    for (int i = 0; i < 3; i++) lds128(qa + 16 * i, qf[4 * i], qf[4 * i + 1], qf[4 * i + 2], qf[4 * i + 3]);
                }
                const uint32_t sq = lds32(xl + 8) - 64u * 0x00800080u;
#pragma unroll
                for (int i = 0; i < 12; i++) qf[i] = bmul2(qf[i], sq);
#define KR_STEP(tau, m) \
                    _Pragma("unroll") for (int i = 2 * (m); i < 2 * (m) + 2; i++) { \
                        const int q0 = 9 * tau + 3 * (i >> 1), r = i & 1; \
                        uint32_t w[4]; \
                        unpack8(kq[q0][2 * r], kq[q0][2 * r + 1], kq[q0 + 2][r], w); \
                        mma16816(cA, w[0], w[1], w[2], w[3], qf[2 * i], qf[2 * i + 1]); \
                        unpack8(kq[q0 + 1][2 * r], kq[q0 + 1][2 * r + 1], kq[q0 + 2][2 + r], w); \
                        mma16816(cB, w[0], w[1], w[2], w[3], qf[2 * i], qf[2 * i + 1]); \
                    }
#define KR_BEGIN float cA[4] = {0.f, 0.f, 0.f, 0.f}, cB[4] = {0.f, 0.f, 0.f, 0.f};
#define KR_END(tau) \
                    const float sA = (cA[0] + cA[3]) * 18446744073709551616.f, sB = (cB[0] + cB[3]) * 18446744073709551616.f; \
                    if (t == (tau & 3)) { if (tau < 4) { sc0 = sA; sc1 = sB; } else { sc2 = sA; sc3 = sB; } }
#define KR_SCORES(tau) { KR_BEGIN KR_STEP(tau, 0) KR_STEP(tau, 1) KR_STEP(tau, 2) KR_END(tau) }
                uint32_t va[3];
                {
                    const int lane = opq(tid) & 31, g = lane >> 2, t = lane & 3;
#pragma unroll
                    for (int i = 0; i < 3; i++) va[i] = ring + V_OFF(2 * i);
                }
#define V_STG(n) _Pragma("unroll") for (int j = 3 * (n); j < 3 * (n) + 3; j++) { \
                    const int i = (j % 12) >> 1; \
                    lds128p(((i & 1) ? (va[i >> 1] ^ 16) + 128 : va[i >> 1]) + (j / 12) * TILE + (j & 1) * 3072, layer, kq[j][0], kq[j][1], kq[j][2], kq[j][3]); }
                uint32_t dep = 0;
                {
                    KR_BEGIN
                    KR_STEP(0, 0) V_STG(0) KR_STEP(0, 1) V_STG(1) KR_STEP(0, 2) V_STG(2)
                    KR_END(0)
                }
                {
                    KR_BEGIN
                    KR_STEP(1, 0) V_STG(3)
                    __syncwarp();
                    dep = lds32(ring);
                    if (layer == 1) tile_load(ring, &maps.k, row0 + 6 * 48, rb, dep, maps.zero);
                    KR_STEP(1, 1) V_STG(4) KR_STEP(1, 2) V_STG(5)
                    KR_END(1)
                }
                {
                    KR_BEGIN
                    KR_STEP(2, 0) V_STG(6) KR_STEP(2, 1) V_STG(7)
                    __syncwarp();
                    dep = lds32(ring + TILE);
                    KR_STEP(2, 2)
                    if (layer == 1) {
                        V1_EXPECT(rb + 8)
                        tile_load(ring + TILE, &maps.k, row0 + 7 * 48, rb + 8, dep, maps.zero);
                        V1_LOAD(rb + 8)
                    }
                    KR_END(2)
                }
#pragma unroll 1
                for (int s = 5; s < 8; s++) {
                    {
                        LANE_IDS
                        const uint32_t tile = !layer ? SLOT1(s) : s == 5 ? xtile : ring + (s - 6) * TILE, tb = !layer ? BAR1(s) : s == 5 ? xb : rb + (s - 6) * 8;
                        const float ur = f_((318u << 23) - (lds32(xl + 8) << 16));
                        mbar_wait(tb, layer ? PAR2(s - 5) : PAR1(s));
                        if (layer) PROF_T(29 + s);
                        float cA[4] = {0.f, 0.f, 0.f, 0.f}, cB[4] = {0.f, 0.f, 0.f, 0.f};
#pragma unroll
                        for (int i = 0; i < 6; i++) {
                            uint32_t a0, a1, a2, a3;
                            lds128(tile + K_OFF(i), a0, a1, a2, a3);
                            mma16816(cA, a0, a1, a2, a3, qf[2 * i], qf[2 * i + 1]);
                            lds128(tile + K_OFF(i) + 3072, a0, a1, a2, a3);
                            mma16816(cB, a0, a1, a2, a3, qf[2 * i], qf[2 * i + 1]);
                        }
                        __syncwarp();
                        const uint32_t last = lds32(tile);
                        if (layer) tile_load(tile, &maps.v, row0 + (s - 2) * 48, tb, last, maps.zero);
                        else refill1(s, last);
                        if (t == (s & 3)) { sc2 = (cA[0] + cA[3]) * ur; sc3 = (cB[0] + cB[3]) * ur; }
                    }
                    if (s == 5) KR_SCORES(3)
                    if (s == 6) {
                        KR_SCORES(4)
                        const int lane = opq(tid) & 31;
                        const uint32_t nx = min(lds32(xl), (uint32_t)XCAP);
#pragma unroll 1
                        for (uint32_t n = 0; n < nx; n++) {
                            const uint32_t id = lds32(xl + 16 + 4 * n);
                            const uint32_t qo = 96 * ((id >> 7) & 3) + 48 * ((id >> 1) & 1) + 16 * ((id >> 5) & 3) + (id & 12) + 2 * (id & 1);
                            const float cr = bf_hi(id) * f_(lds16(sb + SM_QS + qo) << 16);
                            const int d = (int)(16 * ((id >> 9) & 7) + 4 * ((id >> 12) & 3) + ((id >> 13) & 2) + ((id >> 4) & 1) + ((id >> 8) & 128)) - 4 * lane;
                            if (d == 0) sc0 += cr;
                            if (d == 1) sc1 += cr;
                            if (d == 2) sc2 += cr;
                            if (d == 3) sc3 += cr;
                        }
                    }
                }
#undef KR_SCORES
#undef KR_STEP
#undef KR_BEGIN
#undef KR_END
#undef V_STG
                {
                    LANE_IDS
                    if (lds32(xl) > XCAP || !__all_sync(0xffffffffu, (fabsf(sc0) + fabsf(sc1)) + (fabsf(sc2) + fabsf(sc3)) < INFINITY)) {
                        const uint32_t qa = sb + SM_QS + (2 * t + (g & 1)) * 48;
#pragma unroll
                        for (int i = 0; i < 3; i++) lds128(qa + 16 * i, qf[4 * i], qf[4 * i + 1], qf[4 * i + 2], qf[4 * i + 3]);
                        const uint4* kg = reinterpret_cast<const uint4*>(static_cast<const char*>(maps.kp) + (size_t)row0 * 128) + ((g >> 1) + 4 * (g & 1)) * 24 + t;
#pragma unroll 1
                        for (int s = 0; s < 8; s++) {
                            float cA[4] = {0.f, 0.f, 0.f, 0.f}, cB[4] = {0.f, 0.f, 0.f, 0.f};
#pragma unroll
                            for (int i = 0; i < 6; i++) {
                                uint4 u = ldg128(kg + s * 384 + 4 * i);
                                mma16816v(cA, u.x, u.y, u.z, u.w, qf[2 * i], qf[2 * i + 1]);
                                u = ldg128(kg + s * 384 + 4 * i + 192);
                                mma16816v(cB, u.x, u.y, u.z, u.w, qf[2 * i], qf[2 * i + 1]);
                            }
                            if (t == s) { sc0 = cA[0] + cA[3]; sc1 = cB[0] + cB[3]; }
                            if (t + 4 == s) { sc2 = cA[0] + cA[3]; sc3 = cB[0] + cB[3]; }
                        }
                    }
                }
            }
            mw = warp_max(fmaxf(fmaxf(sc0, sc1), fmaxf(sc2, sc3)));
            pk0 = pack2(ex2((sc0 - mw) * SC), ex2((sc1 - mw) * SC));
            pk1 = pack2(ex2((sc2 - mw) * SC), ex2((sc3 - mw) * SC));
            sc2 = (bf_lo(pk0) + bf_hi(pk0)) + (bf_lo(pk1) + bf_hi(pk1));
            sc2 = (float)__reduce_add_sync(0xffffffffu, __float2uint_rn(sc2 * 16777216.f)) * (1.0f / 16777216.f);
            if ((opq(tid) & 31) == 0) st_pkt2(&g_scr.mx[h * 32 + c * 8 + wu], __float_as_uint(mw), (__float_as_uint(sc2) & ~3u) | tag);
            auto head_factor = [&]() {
                const int lane = opq(tid) & 31;
                int it = 0;
                while (!__all_sync(0xffffffffu, (__float_as_uint(sc1) & 3u) == tag) && ++it < SPIN_CAP) {
                    const uint2 mv = ld_pkt2(&g_scr.mx[h * 32 + lane]); sc0 = f_(mv.x); sc1 = f_(mv.y);
                }
                const float e = ex2((sc0 - warp_max(sc0)) * SC);
                const uint32_t d = __reduce_add_sync(0xffffffffu, __float2uint_rn(sc1 * e * 524288.f));
                sc3 = __shfl_sync(0xffffffffu, e, c * 8 + wu) * 524288.f * rcp((float)d);
            };
#pragma unroll
            for (int s = 0; s < 3; s++) { acc[s][0] = acc[s][1] = acc[s][2] = acc[s][3] = 0.f; }
#define P_CONSTS \
                const uint32_t sel0 = g == 0 ? 0x4410u : (g == 1 ? 0x1044u : 0x4444u); \
                const uint32_t sel1 = g == 2 ? 0x4410u : (g == 3 ? 0x1044u : 0x4444u); \
                const int src00 = 4 * (t < 2 ? 4 * t : 4 * (t - 2) + 1);
#define P_FRAGS(tau) \
                const uint32_t pk = ((tau) & 4) ? pk1 : pk0; \
                const uint32_t w0 = __shfl_sync(0xffffffffu, pk, src00 + ((tau) & 3)); \
                const uint32_t w1 = __shfl_sync(0xffffffffu, pk, src00 + ((tau) & 3) + 8); \
                uint32_t pb[4][2]; \
                _Pragma("unroll") for (int j = 0; j < 4; j++) { \
                    const uint32_t src = ((j & 1) ? w1 : w0) >> ((j >> 1) * 16); \
                    pb[j][0] = __byte_perm(src, 0, sel0); pb[j][1] = __byte_perm(src, 0, sel1); \
                }
            if (layer == 0) {
#pragma unroll 1
                for (int s = 8; s < 16; s++) {
                    LANE_IDS
                    P_CONSTS
                    if (s == 13) { const uint2 mv = ld_pkt2(&g_scr.mx[h * 32 + lane]); sc0 = f_(mv.x); sc1 = f_(mv.y); }
                    P_FRAGS(V_SEQ(s))
                    mbar_wait(BAR1(s), PAR1(s));
                    const uint32_t tile = SLOT1(s);
#pragma unroll
                    for (int j = 0; j < 4; j++) {
#pragma unroll
                        for (int u = 0; u < 3; u++) {
                            uint32_t a0, a1, a2, a3;
                            lds128(tile + (j >> 1) * 3072 + V_OFF(3 * (j & 1) + u), a0, a1, a2, a3);
                            mma16816(acc[u], a0, a1, a2, a3, pb[j][0], pb[j][1]);

                        }
                    }
                    __syncwarp();
                    if (s < V0_AT || (s > V0_AT + 1 && s < 14)) refill1(s, lds32(tile), true);
                    if (s == V0_AT || s == V0_AT + 1) {
                        {
                            const uint32_t ar = sb + SM_R + wu * 784 + 32 * g + 16 * t;
                            if (t < 2) {
#pragma unroll
                                for (int u = 0; u < 3; u++) sts128(ar + 256 * u, __float_as_uint(acc[u][0]), __float_as_uint(acc[u][1]), __float_as_uint(acc[u][2]), __float_as_uint(acc[u][3]));
                            }
                        }
                        const uint32_t scl = s == V0_AT ? pack_scale(tile, lane, xl + 12) : lds32(xl + 12);
                        pack_tile<true>(tile, s + 8 - V0_AT, V0_AT + 3 - s, scl, xl, lane, [&](int m, uint32_t (&d)[3]) {
                            if (s != V0_AT && m == 0) {
#pragma unroll
                                for (int k = 0; k < 3; k++) d[k] = ring + 3072 + V_OFF(2 * k + 1);
                            }
                        });
                        if (s != V0_AT) {
                            lds128(tile + V_OFF(2), kq[45][0], kq[45][1], kq[45][2], kq[45][3]);
                            lds128(tile + V_OFF(3), kq[46][0], kq[46][1], kq[46][2], kq[46][3]);
                            lds128(tile + V_OFF(2) + 3072, kq[47][0], kq[47][1], kq[47][2], kq[47][3]);
                            __syncwarp();
                            issue1(V0_AT + 3, lds32(tile));
                        }
                        const int ln = opq(tid) & 31;
                        const uint32_t ar = sb + SM_R + wu * 784 + 8 * (ln & 28) + 16 * (ln & 1);
#pragma unroll
                        for (int u = 0; u < 3; u++) {
                            uint32_t a0, a1, a2, a3;
                            lds128(ar + 256 * u, a0, a1, a2, a3);
                            acc[u][0] = f_(a0); acc[u][1] = f_(a1); acc[u][2] = f_(a2); acc[u][3] = f_(a3);
                        }
                    }
                    if (s == 13) head_factor();
                    if (s >= 14 && elect_one()) {
                        if (atomicAdd(reinterpret_cast<unsigned*>(misc + 3), 1u) == 14u && (int)(now_ns() - lds32(xl + 4)) >= 0) {
                            PROF_X(47);
                            load_wo(maps, sb + SM_B, h, c, wbar, 6);
                            atomicAdd(reinterpret_cast<unsigned*>(misc + 3), 256u);
                        }
                    }
                }
            } else {
                LANE_IDS
                P_CONSTS
#pragma unroll
                for (int k = 0; k < 4; k++) lds128(V1_REST(t + 4 * (k >> 1)) + 16 * g + 128 * (k & 1), kq[36 + k][0], kq[36 + k][1], kq[36 + k][2], kq[36 + k][3]);
#pragma unroll 1
                for (int i = 3; i < 8; i++) {
                    const uint32_t tile = i > 3 ? ring + (i & 1) * TILE : xtile, tb = i > 3 ? rb + (i & 1) * 8 : xb;
                    if (i == 6) { const uint2 mv = ld_pkt2(&g_scr.mx[h * 32 + lane]); sc0 = f_(mv.x); sc1 = f_(mv.y); }
                    if (i == 7) head_factor();
                    if (i == PK_AT) {
                uint32_t nx, nk, ik, iv;
                lds128(xl, nx, nk, ik, iv);
                if (nx <= XCAP) {
                    const uint32_t pks = bmul2(pk0, iv);
#pragma unroll
                    for (int s = 0; s < 2; s++) {
                        const uint32_t pk1 = 0, pk0 = pks;
                        P_FRAGS(s)
#pragma unroll
                        for (int j = 0; j < 4; j++) {
#pragma unroll
                            for (int u = 0; u < 3; u++) {
                                const int i = 3 * (j & 1) + u, m = i >> 1, r = i & 1, hf = j >> 1;
                                if (s == 1 && m == 2) continue;
                                const int ql = s == 0 ? 4 * m + 2 * hf : m == 0 ? 3 + 4 * hf : 45 + hf, qc = s == 0 ? 4 * m + 1 : m == 0 ? 11 : 47;
                                uint32_t w[4];
                                unpack8(kq[ql][2 * r], kq[ql][2 * r + 1], kq[qc][2 * hf + r], w);
                                mma16816(acc[u], w[0], w[1], w[2], w[3], pb[j][0], pb[j][1]);
                            }
                        }
                    }
#pragma unroll 1
                    for (uint32_t n = 0; n < nx; n++) {
                        const uint32_t id = lds32(xl + 16 + 4 * n);
                        const int i = ((id >> 4) & 6) + ((id >> 3) & 1), key = ((id >> 6) & 6) + (i >= 3);
                        const uint32_t pw = __shfl_sync(0xffffffffu, pk0, 8 * (key & 3) + (key & 4) + ((id >> 12) & 3));
                        const float cr = bf_hi(id) * ((id & 16) ? bf_hi(pw) : bf_lo(pw));
                        const int d = (int)(64 * ((id >> 9) & 7) + 4 * (id & 4) + 4 * (i >= 3 ? i - 3 : i) + (id & 3) + ((~id >> 5) & 1024)) - 16 * lane;
#pragma unroll
                        for (int k = 0; k < 12; k++) if (d == k) acc[k >> 2][k & 3] += cr;
                    }
                } else {
                    const uint4* vg = reinterpret_cast<const uint4*>(static_cast<const char*>(maps.vp) + (size_t)row0 * 128) + 48 * t + g;
#pragma unroll 1
                    for (int s = 0; s < 2; s++) {
                        P_FRAGS(s)
#pragma unroll
                        for (int j = 0; j < 4; j++) {
#pragma unroll
                            for (int u = 0; u < 3; u++) {
                                if (s == 1 && (j & 1) && u) continue;
                                const uint4 w = ldg128(vg + 384 * s + 192 * (j >> 1) + 24 * (j & 1) + 8 * u);
                                mma16816v(acc[u], w.x, w.y, w.z, w.w, pb[j][0], pb[j][1]);
                            }
                        }
                    }
                }
#pragma unroll
                for (int s = 2; s > 0; s--) {
                    P_FRAGS(s)
#pragma unroll
                    for (int j = 0; j < 4; j++) {
#pragma unroll
                        for (int u = 0; u < 3; u++) {
                            if (s == 1 && !((j & 1) && u)) continue;
                            const int k = s == 2 ? 12 + 2 * (3 * (j & 1) + u) + (j >> 1) : 35 + (j >> 1) * 2 + u;
                            mma16816(acc[u], kq[k][0], kq[k][1], kq[k][2], kq[k][3], pb[j][0], pb[j][1]);
                        }
                    }
                }
                    }
                    P_FRAGS(i)
                    mbar_wait(tb, PAR2(i));
                    PROF_T(34 + i);
#pragma unroll
                    for (int k = 0; k < 6; k++) {
                        const uint32_t a = tile + V_OFF(k);
                        lds128(a, kq[24 + k][0], kq[24 + k][1], kq[24 + k][2], kq[24 + k][3]);
                        lds128(a + 3072, kq[30 + k][0], kq[30 + k][1], kq[30 + k][2], kq[30 + k][3]);
                    }
#pragma unroll
                    for (int j = 0; j < 4; j++) {
#pragma unroll
                        for (int u = 0; u < 3; u++) {
                            const int k = 24 + 6 * (j >> 1) + 3 * (j & 1) + u;
                            mma16816(acc[u], kq[k][0], kq[k][1], kq[k][2], kq[k][3], pb[j][0], pb[j][1]);
                        }
                    }
                    __syncwarp();
                    if (wu < L1R && i == 5 - (wu & 1)) tile_load_l1(tile, maps.vp, row0 + (i + 2) * 48, tb, lane);
                    else if (i == 4 || i == 5) tile_load(tile, &maps.v, row0 + (i + 2) * 48, tb, lds32(tile), maps.zero);
                    if (i == WO_AT1 && HAS_FFN && elect_one()) {
                        if (atomicAdd(reinterpret_cast<unsigned*>(misc + 2), 1u) == 7u) {
                            PROF_X(63);
                            load_wo(maps, sb + SM_Q, h, c, wbar, KEEP4 && __float_as_uint(misc[1]) >= DN0 ? 5 : 6);
                        }
                    }
                }
            }
#undef P_FRAGS
#undef P_CONSTS
#undef LANE_IDS
        }
        PROF_T(3 + layer * 16);
        PC(layer * 32 + 1);

        {
            const int tl = opq(tid), warp = tl >> 5, lane = tl & 31, g = lane >> 2, t = lane & 3;
            if (t < 2) {
#pragma unroll
                for (int u = 0; u < 3; u++)
                    *reinterpret_cast<float4*>(rr + warp * 196 + 64 * u + 8 * g + 4 * t) = make_float4(acc[u][0] * sc3, acc[u][1] * sc3, acc[u][2] * sc3, acc[u][3] * sc3);
            }
        }
        const uint32_t role1 = layer ? lds32(sb + SM_MISC + 4) : DN0 + NDN;
        const uint32_t pc = opq(sb + SM_R + 16 * opq(tid));
        uint4* const px0 = opq(&g_scr.hx[b * 48 + opq(tid)]);
        __syncthreads();
        PROF_T(4 + layer * 16);
        PC(layer * 32 + 2);
        uint32_t ticket = 0;
        if (layer == 0 && tid == 224)
            asm volatile("atom.relaxed.gpu.global.inc.u32 %0, [%1], 0x7fffffff;" : "=r"(ticket) : "l"(g_scr.ticket + 8 + (b >> 3)) : "memory");
        if (layer == 0 && tid == 224 && lds32(sb + SM_MISC + 12) < 256u) {
            int it = 0;
            while ((int)(now_ns() - lds32(sb + SM_XL + 4)) < 0 && ++it < SPIN_CAP) {}
            PROF_X(47);
            load_wo(maps, sb + SM_B, h, c, wbar, 6);
        }
        uint32_t pr;
        uint4* pacc;
        {
            const int tid = opq(threadIdx.x), warp = tid >> 5, lane = tid & 31, g = lane >> 2, t = lane & 3, mat = lane >> 3, r8 = lane & 7;
            const int kg = warp >> 1, mg = warp & 1;
            const bool wo2 = role1 < DN0 + NDN;
            const uint32_t aw2 = 40960 + (wo2 && KEEP4 && role1 >= DN0 && kg >= 2 ? SM_B - SM_Q : 0);
            uint32_t aw[5];
#pragma unroll
            for (int i = 0; i < 5; i++) {
                const uint32_t lin = ((mat >> 1) * 8 + r8) * 320 + 64 * i + 32 * mg + 16 * (mat & 1);
                aw[i] = sb + (wo2 ? SM_Q : SM_B) + 5120 * kg + (lin ^ ((lin >> 3) & 48));
            }
            float4 o = make_float4(0.f, 0.f, 0.f, 0.f);
            if (threadIdx.x < 48) {
                float4 v[8];
#pragma unroll
                for (int w = 0; w < 8; w++) v[w] = lds4f(pc + w * 784);
                o.x = ((v[0].x + v[1].x) + (v[2].x + v[3].x)) + ((v[4].x + v[5].x) + (v[6].x + v[7].x));
                o.y = ((v[0].y + v[1].y) + (v[2].y + v[3].y)) + ((v[4].y + v[5].y) + (v[6].y + v[7].y));
                o.z = ((v[0].z + v[1].z) + (v[2].z + v[3].z)) + ((v[4].z + v[5].z) + (v[6].z + v[7].z));
                o.w = ((v[0].w + v[1].w) + (v[2].w + v[3].w)) + ((v[4].w + v[5].w) + (v[6].w + v[7].w));
                st_pktf(px0, o.x, o.y, o.z, o.w, 0);
            }
#define CXE 1
            const uint32_t ao = pin(sb + SM_OS + 96 * kg + 16 * t), dw = pin(sb + SM_R + 16 * (16 * mg + g) + 4 * kg);
            pr = pin(sb + SM_R + 48 * tid); pacc = pin(&g_scr.acc[layer][(54 * c + tid) * ACC_STR]);
            const int w = 2 * tid;
            const uint32_t d0 = pin(sb + SM_OS + 4 * (24 * ((w >> 3) & 3) + ((w >> 2) & 1) + (w < 64 ? 4 * (w & 3) + 2 * (w >> 5) : 16 + 2 * (w & 3))));
            const uint32_t d1 = pin(d0 + (w < 64 ? 16 : 8));
            const uint4* pp[3];
#pragma unroll
            for (int k = 0; k < 3; k++) pp[k] = pin(&g_scr.hx[(h * 4 + ((c + 1 + k) & 3)) * 48 + min(tid, 47)]);
            bool ok = true;
            if ((PRE1 & 8) && layer) {
#pragma unroll
                for (int ks = 0; ks < 3; ks++) {
                    mbar_wait(wbar + 8 * ks, wo2);
#pragma unroll
                    for (int i = 0; i < 5; i++) ldsm4t(aw[i] + (ks == 2 ? aw2 : 20480 * ks), kq[3 * i + ks]);
                    if (ks == CXE && threadIdx.x < 48) {
#pragma unroll
                        for (int k = 0; k < 3; k++) { const uint4 v = ld_pkt(pp[k]); kq[20 + k][0] = v.x; kq[20 + k][1] = v.y; kq[20 + k][2] = v.z; kq[20 + k][3] = v.w; }
                    }
                }
                PROF_T(50);
                if (CXE < 3 && threadIdx.x < 48) {
                    ok = (kq[20][3] | kq[21][3] | kq[22][3]) & 1;
                    if (!ok) {
#pragma unroll
                        for (int k = 0; k < 3; k++) { o.x += f_(kq[20 + k][0]); o.y += f_(kq[20 + k][1]); o.z += f_(kq[20 + k][2]); o.w += f_(kq[20 + k][3]); }
                    }
                }
            }
            if (tid < 48) {
                if (ok) {
                    uint4 v3[3];
                    int it = 0;
                    do {
#pragma unroll
                        for (int k = 0; k < 3; k++) v3[k] = ld_pkt(pp[k]);
                        ok = (v3[0].w | v3[1].w | v3[2].w) & 1;
                    } while (ok && ++it < SPIN_CAP);
#pragma unroll
                    for (int k = 0; k < 3; k++) { o.x += f_(v3[k].x); o.y += f_(v3[k].y); o.z += f_(v3[k].z); o.w += f_(v3[k].w); }
                }
                sts32(d0, f_(pack2(o.x, o.y)));
                sts32(d1, f_(pack2(o.z, o.w)));
            }
            PC(layer * 32 + 3);
            __syncthreads();
            PROF_T(5 + layer * 16);
            PC(layer * 32 + 5);
            if (tid == 224 && layer == 0) {
                if (ticket >= 6 + ((b >> 3) & 1)) ticket = DN0 + NDN;
                else asm volatile("atom.relaxed.gpu.global.inc.u32 %0, [%1], 0x7fffffff;" : "=r"(ticket) : "l"(g_scr.ticket) : "memory");
            }
            uint32_t ob[6];
            lds128(ao, ob[0], ob[1], ob[2], ob[3]);
            lds64(ao + 64 - 8 * t, ob[4], ob[5]);
            float cc[5][4];
#pragma unroll
            for (int i = 0; i < 5; i++) cc[i][0] = cc[i][1] = cc[i][2] = cc[i][3] = 0.f;
            if ((PRE1 & 8) && layer) {
#pragma unroll
                for (int ks = 0; ks < 3; ks++) {
#pragma unroll
                    for (int i = 0; i < 5; i++) mma16816(cc[i], kq[3 * i + ks][0], kq[3 * i + ks][1], kq[3 * i + ks][2], kq[3 * i + ks][3], ob[2 * ks], ob[2 * ks + 1]);
                }
            } else {
#pragma unroll
                for (int ks = 0; ks < 3; ks++) {
                    mbar_wait(wbar + 8 * ks, wo2);
                    if (ks == 2) { PC(layer * 32 + 4); PROF_T(48 + layer * 2); }
                    uint32_t a[5][4];
#pragma unroll
                    for (int i = 0; i < 5; i++) ldsm4t(aw[i] + (ks == 2 ? aw2 : 20480 * ks), a[i]);
#pragma unroll
                    for (int i = 0; i < 5; i++) mma16816(cc[i], a[i][0], a[i][1], a[i][2], a[i][3], ob[2 * ks], ob[2 * ks + 1]);
                }
            }
            if (t == 0) {
#pragma unroll
                for (int i = 0; i < 5; i++) { sts32(dw + 512 * i, cc[i][0]); sts32(dw + 512 * i + 128, cc[i][2]); }
            }
        }
        PC(layer * 32 + 6);
        __syncthreads();
        PROF_T(6 + layer * 16);
        PC(layer * 32 + 7);
        if (tid < 54) {
            const float4 v0 = lds4f(pr), v1 = lds4f(pr + 16), v2 = lds4f(pr + 32);
            const float y0 = (v0.x + v0.y) + (v0.z + v0.w), y1 = (v1.x + v1.y) + (v1.z + v1.w), y2 = (v2.x + v2.y) + (v2.z + v2.w);
            red_pkt(pacc, y0, tid == 53 ? 0.f : y1, tid == 53 ? 0.f : y2);
        }
        if (tid == 224 && layer == 0) {
            misc[1] = __uint_as_float(ticket);
            if (ticket < DN0 + NDN && (ticket < NG || !DNTH)) load_ffn(maps, ticket, sb + SM_B, fbar);
        }
        PROF_T(7 + layer * 16);
        PC(layer * 32 + 8);
        __syncthreads();
        const int role = (int)__float_as_uint(misc[1]);
        PC(layer * 32 + 9);
        const uint32_t fbase = sb + SM_B;
        const uint32_t DONE32 = 0x42000000u;
        if (role < NG) {
            const int tid = opq(threadIdx.x), warp = tid >> 5, lane = tid & 31, g = lane >> 2, t = lane & 3, mat = lane >> 3, r8 = lane & 7;
            const uint32_t ag = fbase + (80 * warp + (mat >> 1) * 8 + r8) * 96 + (((mat & 1) ^ (r8 >> 2)) << 4);
            constexpr int GI = 32, GK = 16 * 96;
            const bool on = (g & 1) == (t >> 1), isx = on && g < 2;
            const uint32_t pm = opq(isx ? sb + SM_XS + 160 * warp + 16 * t : sb + (on ? SM_ONE : SM_ZERO)), pm2 = opq(pm + 128 - (isx ? 8 * t : 0));
            const uint32_t dg = opq(sb + SM_R + 4 * (2 * (warp * 48 + g) + t)), ds = opq(sb + SM_ST + 8 * warp + (lane < 16 ? 4 : 0));
            const bool wr = t < 2, ws = (lane & 15) == 0, lo = lane < 16;
            uint32_t pre[6][4];
            float s1 = 0.f, s2 = 0.f;
            {
                bool hx = tid >= 224;
                int it = 0;
                const uint4* px = &g_scr.acc[layer][min(tid, 215) * ACC_STR];
                const int cq = tid / 54, r = tid - 54 * cq, k0 = min(160 * cq + 3 * r, DM - 1);
                const uint32_t w0 = sb + SM_XS + 4 * xpos(k0 >> 1), w1 = sb + SM_XS + 4 * xpos(min((k0 >> 1) + 1, DM / 2 - 1));
                const uint32_t e0 = w0 + 2 * (k0 & 1), e1 = (k0 & 1) ? w1 : w0 + 2, e2 = w1 + 2 * (k0 & 1);
                                auto sts16 = [](uint32_t a, uint32_t x, bool on) {
                    asm volatile("{\n.reg .pred p;\nsetp.ne.u32 p, %2, 0;\n@p st.shared.u16 [%0], %1;\n}" ::"r"(a), "h"((unsigned short)x), "r"((uint32_t)on) : "memory");
                };
                const bool on0 = tid < 216, on1 = on0 && r != 53;
                const float x0 = on0 ? f_(lds16(e0) << 16) : 0.f, x1 = on1 ? f_(lds16(e1) << 16) : 0.f, x2 = on1 ? f_(lds16(e2) << 16) : 0.f;
                auto take_x = [&](const uint4 v) {
                    if (__all_sync(0xffffffffu, v.w == DONE32)) {
                        hx = true;
                        const uint32_t a = pack2(f_(v.x), f_(v.y)), p = pack2(x0 + bf_lo(a), x1 + bf_hi(a)), q = pack2(x2 + bfr(f_(v.z)), 0.f);
                        sts16(e0, p, on0); sts16(e1, p >> 16, on1); sts16(e2, q, on1);
                        const float y0 = on0 ? bf_lo(p) : 0.f, y1 = on0 ? bf_hi(p) : 0.f, y2 = on0 ? bf_lo(q) : 0.f;
                        s1 = y0 + (y1 + y2); s2 = y0 * y0 + (y1 * y1 + y2 * y2);
                    }
                };
                auto try_x = [&]() { take_x(ld_pkt(px)); };
                while (!mbar_test(fbar, 0) && ++it < SPIN_CAP) { if (!hx) try_x(); }
                uint4 v0 = make_uint4(0u, 0u, 0u, 0u);
                if ((PRE1 & 4) && !hx) v0 = ld_pkt(px);
#pragma unroll
                for (int n = 0; n < 6; n++) ldsm4t(ag + (n % 3) * GI + (n / 3) * GK, pre[n]);
                if ((PRE1 & 1) && layer) {
#pragma unroll
                    for (int n = 6; n < 15; n++) ldsm4t(ag + (n % 3) * GI + (n / 3) * GK, kq[n - 6]);
                }
                if ((PRE1 & 4) && !hx) take_x(v0);
                PC(layer * 32 + 10);
                while (!hx && ++it < SPIN_CAP) try_x();
                PC(layer * 32 + 11);
            __syncthreads();
            PC(layer * 32 + 12);
            PROF_T(9 + layer * 16);
            float sv = lo ? s1 : s2, cc[3][4];
            if ((PRE1 & 1) && layer) gemv15r(cc, pre, kq, pm, pm2, sv, lo ? s2 : s1);
            else gemv15<GK>(cc, pre, [&](int i) { return ag + i * GI; }, pm, pm2, sv, lo ? s2 : s1);
            if (wr) {
#pragma unroll
                for (int i = 0; i < 3; i++) { sts32(dg + 128 * i, cc[i][0] + cc[i][3]); sts32(dg + 128 * i + 64, cc[i][1] + cc[i][2]); }
            }
            if (ws) sts32(ds, sv);
            const uint32_t pg = opq(sb + SM_R + 8 * (24 * warp + (lane < 24 ? lane : 0))), st = opq(sb + SM_ST);
            uint4* const ph = opq(lane < 24 && lane % 6 == 0 ? &g_scr.ah[role * 8 + 4 * warp + lane / 6] : nullptr);
            PC(layer * 32 + 13);
            __syncthreads();
            PC(layer * 32 + 14);
            PROF_T(43 + layer * 16);
            if (warp < 2) {
                float mean, inv;
                ln_stats(st, mean, inv);
                float2 v[8];
#pragma unroll
                for (int w = 0; w < 8; w++) v[w] = lds2f(pg + w * 384);
                const float gx = ((v[0].x + v[1].x) + (v[2].x + v[3].x)) + ((v[4].x + v[5].x) + (v[6].x + v[7].x));
                const float gs = ((v[0].y + v[1].y) + (v[2].y + v[3].y)) + ((v[4].y + v[5].y) + (v[6].y + v[7].y));
                float ga = inv * (gx - mean * gs);
                if (role < NG / 2) { ga = bfr(ga); ga *= rcp(1.0f + ex2(-1.4426950408889634f * ga)); }
                const uint32_t wd = pack2(ga, __shfl_down_sync(0xffffffffu, ga, 1));
                const uint32_t wa = __shfl_down_sync(0xffffffffu, wd, 2), wb = __shfl_down_sync(0xffffffffu, wd, 4);
                if (ph) st_pkt(ph, wd, wa, wb, tag);
            }
            if (HOLD & 2) __syncthreads();
            }
            PROF_T(10 + layer * 16);
            PC(layer * 32 + 15);
        } else if (role < DN0 + NDN) {
            const int j = role - DN0;
            const int tid = opq(threadIdx.x), warp = tid >> 5, lane = tid & 31, g = lane >> 2, t = lane & 3, mat = lane >> 3, r8 = lane & 7;
            float xres = 0.f;
            uint32_t xr0 = 0, xr1 = 0;
            if (warp == 0) {
                const int col = 16 * j + (lane & 15), cc = col / 160, r = col - 160 * cc, e = r % 3;
                const uint4* px = &g_scr.acc[layer][(54 * cc + r / 3) * ACC_STR];
                const float x0 = __bfloat162float(reinterpret_cast<const __nv_bfloat16*>(xs32)[2 * xpos(col >> 1) + (col & 1)]);
                uint4 v;
                int it = 0;
                bool ld = DNTH && layer == 0;
                do {
                    v = ld_pkt(px);
                    if (ld && f_(__shfl_sync(0xffffffffu, v.w, 0)) >= (float)DNTH) { ld = false; if (lane == 0) load_ffn(maps, role, sb + SM_B, fbar); }
                } while (!__all_sync(0xffffffffu, v.w == DONE32) && ++it < SPIN_CAP);
                if (ld && lane == 0) load_ffn(maps, role, sb + SM_B, fbar);
                xres = x0 + bfr(f_(e == 0 ? v.x : (e == 1 ? v.y : v.z)));
                const int p4 = 4 * (lane & 3);
                xr0 = pack2(__shfl_sync(0xffffffffu, xres, p4), __shfl_sync(0xffffffffu, xres, p4 + 1));
                xr1 = pack2(__shfl_sync(0xffffffffu, xres, p4 + 2), __shfl_sync(0xffffffffu, xres, p4 + 3));
            }
            PC(layer * 32 + 17);
            PROF_T(9 + layer * 16);
            const uint32_t ad = fbase + (192 * warp + (mat >> 1) * 8 + r8) * 32 + (((mat & 1) ^ (r8 >> 2)) << 4);
            uint32_t* hs = reinterpret_cast<uint32_t*>(rr) + warp * 96;
            uint32_t pre[NPRE][4];
            {
                uint32_t pos[3];
#pragma unroll
                for (int i = 0; i < 3; i++) { const int w = 3 * lane + i; pos[i] = pin(sb + SM_R + 384 * warp + 4 * ((w & ~15) + 4 * (w & 3) + ((w >> 2) & 1) + ((w >> 2) & 2))); }
                uint4 v = make_uint4(0u, 0u, 0u, 0u), u = v;
                if (layer == 0) { v = ld_pkt(&g_scr.ah[tid]); u = ld_pkt(&g_scr.ah[256 + tid]); }
                mbar_wait(fbar, 0);
#pragma unroll
                for (int n = 0; n < NPRE; n++) ldsm4t(ad + n * 512, pre[n]);
                if ((PRE1 & 2) && layer) {
#pragma unroll
                    for (int n = NPRE; n < 12; n++) ldsm4t(ad + n * 512, kq[12 + n]);
                }
                PC(layer * 32 + 18);
                int it = 0;
                while (!__all_sync(0xffffffffu, v.w == tag && u.w == tag) && ++it < SPIN_CAP) { v = ld_pkt(&g_scr.ah[tid]); u = ld_pkt(&g_scr.ah[256 + tid]); }
                PC(layer * 32 + 19);
                sts32(pos[0], f_(bmul2(v.x, u.x))); sts32(pos[1], f_(bmul2(v.y, u.y))); sts32(pos[2], f_(bmul2(v.z, u.z)));
            __syncwarp();
            PROF_T(11 + layer * 16);
            PC(layer * 32 + 20);
            float ca[4] = {0.f, 0.f, 0.f, 0.f}, cb[4] = {0.f, 0.f, 0.f, 0.f};
            if ((PRE1 & 2) && layer) {
                float cc[4] = {0.f, 0.f, 0.f, 0.f}, cd[4] = {0.f, 0.f, 0.f, 0.f};
#pragma unroll
                for (int jj = 0; jj < 6; jj++) {
                    const uint4 hv = *reinterpret_cast<const uint4*>(hs + 16 * jj + 4 * t);
                    const uint32_t (&f0)[4] = 2 * jj < NPRE ? pre[2 * jj < NPRE ? 2 * jj : 0] : kq[12 + 2 * jj];
                    const uint32_t (&f1)[4] = 2 * jj + 1 < NPRE ? pre[2 * jj + 1 < NPRE ? 2 * jj + 1 : 0] : kq[13 + 2 * jj];
                    if (jj & 1) { mma16816(cc, f0[0], f0[1], f0[2], f0[3], hv.x, hv.y); mma16816(cd, f1[0], f1[1], f1[2], f1[3], hv.z, hv.w); }
                    else { mma16816(ca, f0[0], f0[1], f0[2], f0[3], hv.x, hv.y); mma16816(cb, f1[0], f1[1], f1[2], f1[3], hv.z, hv.w); }
                }
#pragma unroll
                for (int e = 0; e < 4; e++) { ca[e] += cc[e]; cb[e] += cd[e]; }
            } else {
#pragma unroll
                for (int jj = 0; jj < 6; jj++) {
                    const uint4 hv = *reinterpret_cast<const uint4*>(hs + 16 * jj + 4 * t);
                    uint32_t a[4];
                    if (2 * jj < NPRE) { a[0] = pre[2 * jj][0]; a[1] = pre[2 * jj][1]; a[2] = pre[2 * jj][2]; a[3] = pre[2 * jj][3]; }
                    else ldsm4t(ad + 2 * jj * 512, a);
                    mma16816(ca, a[0], a[1], a[2], a[3], hv.x, hv.y);
                    if (2 * jj + 1 < NPRE) { a[0] = pre[2 * jj + 1][0]; a[1] = pre[2 * jj + 1][1]; a[2] = pre[2 * jj + 1][2]; a[3] = pre[2 * jj + 1][3]; }
                    else ldsm4t(ad + (2 * jj + 1) * 512, a);
                    mma16816(cb, a[0], a[1], a[2], a[3], hv.z, hv.w);
                }
            }
            if (t == 0) { rr[768 + warp * 16 + g] = ca[0] + cb[0]; rr[768 + warp * 16 + 8 + g] = ca[2] + cb[2]; }
            const uint32_t pd = opq(sb + SM_R + 3072 + 16 * (lane & 3));
            uint4* const py = opq(&g_scr.ay[j * 4 + lane]);
            uint2* const po = opq(reinterpret_cast<uint2*>(out + 16 * j) + lane);
            PC(layer * 32 + 21);
            __syncthreads();
            PC(layer * 32 + 22);
            if (tid < 4) {
                float4 p[8];
#pragma unroll
                for (int w = 0; w < 8; w++) p[w] = lds4f(pd + 64 * w);
                const uint32_t y0 = pack2(((p[0].x + p[1].x) + (p[2].x + p[3].x)) + ((p[4].x + p[5].x) + (p[6].x + p[7].x)),
                                          ((p[0].y + p[1].y) + (p[2].y + p[3].y)) + ((p[4].y + p[5].y) + (p[6].y + p[7].y)));
                const uint32_t y1 = pack2(((p[0].z + p[1].z) + (p[2].z + p[3].z)) + ((p[4].z + p[5].z) + (p[6].z + p[7].z)),
                                          ((p[0].w + p[1].w) + (p[2].w + p[3].w)) + ((p[4].w + p[5].w) + (p[6].w + p[7].w)));
                uint32_t wd, wn;
                asm("add.rn.bf16x2 %0, %1, %2;" : "=r"(wd) : "r"(xr0), "r"(y0));
                asm("add.rn.bf16x2 %0, %1, %2;" : "=r"(wn) : "r"(xr1), "r"(y1));
                if (layer) asm volatile("st.global.v2.u32 [%0], {%1,%2};" ::"l"(po), "r"(wd), "r"(wn) : "memory");
                st_pkt(py, wd, wn, 0, tag);
            }
            if (HOLD & 1) __syncthreads();
            }
            PROF_T(12 + layer * 16);
            PC(layer * 32 + 23);
        }
    }
}

typedef CUresult (*EncodeFn)(CUtensorMap*, CUtensorMapDataType, cuuint32_t, void*, const cuuint64_t*, const cuuint64_t*, const cuuint32_t*,
                             const cuuint32_t*, CUtensorMapInterleave, CUtensorMapSwizzle, CUtensorMapL2promotion, CUtensorMapFloatOOBfill);

void make_map(EncodeFn enc, CUtensorMap* m, const void* base, int rank, uint64_t d0, uint64_t d1, uint64_t d2, uint64_t s1, uint64_t s2,
              uint32_t b0, uint32_t b1, uint32_t b2, CUtensorMapSwizzle sw, CUtensorMapL2promotion pr = CU_TENSOR_MAP_L2_PROMOTION_NONE) {
    cuuint64_t dims[3] = {d0, d1, d2};
    cuuint64_t strides[2] = {s1, s2};
    cuuint32_t box[3] = {b0, b1, b2};
    cuuint32_t es[3] = {1, 1, 1};
    enc(m, CU_TENSOR_MAP_DATA_TYPE_BFLOAT16, rank, const_cast<void*>(base), dims, strides, box, es, CU_TENSOR_MAP_INTERLEAVE_NONE, sw,
        pr, CU_TENSOR_MAP_FLOAT_OOB_FILL_NONE);
}

}

extern "C" void kernel_launch(void* const* d_in, const int* in_sizes, int n_in, void* d_out, int out_size) {
    (void)in_sizes; (void)n_in; (void)out_size;
    static EncodeFn enc = nullptr;
    if (!enc) {
        void* fn = nullptr;
        cudaDriverEntryPointQueryResult qr;
        cudaGetDriverEntryPoint("cuTensorMapEncodeTiled", &fn, cudaEnableDefault, &qr);
        enc = reinterpret_cast<EncodeFn>(fn);
        cudaFuncSetAttribute(decode_kernel, cudaFuncAttributeMaxDynamicSharedMemorySize, SM_TOTAL);
    }
    Maps maps;
    make_map(enc, &maps.k, d_in[1], 2, 64, (uint64_t)NH * SK * 3, 1, 128, 0, 64, 48, 1, CU_TENSOR_MAP_SWIZZLE_128B);
    make_map(enc, &maps.v, d_in[2], 2, 64, (uint64_t)NH * SK * 3, 1, 128, 0, 64, 48, 1, CU_TENSOR_MAP_SWIZZLE_128B);
    make_map(enc, &maps.wq, d_in[3], 3, 64, DM, NH * DH / 64, NH * DH * 2, 128, 64, 160, 3, CU_TENSOR_MAP_SWIZZLE_128B);
    make_map(enc, &maps.wo, d_in[4], 3, 32, DM / 32, NH * DH, 64, DM * 2, 32, 5, 32, CU_TENSOR_MAP_SWIZZLE_64B);
    make_map(enc, &maps.vr, (const char*)d_in[2] + 512, 2, 128, (uint64_t)NH * SK / 2, 1, 768, 0, 128, 2, 1, CU_TENSOR_MAP_SWIZZLE_NONE);
    constexpr int GW = 48;
    make_map(enc, &maps.w1, d_in[6], 3, FF, 160, 4, FF * 2, 160 * FF * 2, GW, 160, 4, CU_TENSOR_MAP_SWIZZLE_NONE, FFN_PROMO);
    make_map(enc, &maps.w3, d_in[7], 3, FF, 160, 4, FF * 2, 160 * FF * 2, GW, 160, 4, CU_TENSOR_MAP_SWIZZLE_NONE, FFN_PROMO);
    make_map(enc, &maps.w2, d_in[8], 3, DM, 256, 6, DM * 2, 256 * DM * 2, 16, 256, 6, CU_TENSOR_MAP_SWIZZLE_32B, FFN_PROMO);
    maps.vp = d_in[2];
    maps.kp = d_in[1];
    maps.zero = 0;
    decode_kernel<<<NCTA, NT, SM_TOTAL, cudaStreamPerThread>>>(maps, (const __nv_bfloat16*)d_in[0], (__nv_bfloat16*)d_out);
}
```

```cpp
#include <cuda_runtime.h>
#include <cuda_bf16.h>
#include <cuda.h>
#include <stdint.h>
#include <math.h>

namespace {

constexpr int DM = 640;
constexpr int NH = 32;
constexpr int DH = 192;
constexpr int SK = 32768;
constexpr int WIN = 4096;
constexpr int FF = 1536;
constexpr int NCTA = 128;
constexpr int NT = 256;
constexpr int TILE = 6144;
constexpr int NG = 64;
constexpr int DN0 = 64;
constexpr int NDN = 40;

constexpr int SM_RING = 0;
constexpr int SM_B = 8 * 2 * TILE;
constexpr int SM_Q = SM_B + 61440;
__host__ __device__ constexpr int c_slot(int w) { return w < 2 ? 4096 + 10240 * w : 12288 + 6144 * w; }
__host__ __device__ constexpr int v1_pos(int n) { return 10240 * (n >> 3) + 512 * (n & 7); }
constexpr int SM_XS = SM_Q + 61440;
constexpr int SM_R = SM_XS + 1280;
constexpr int SM_ST = SM_R + 4096;
constexpr int SM_QS = SM_R + 6272;
constexpr int SM_OS = SM_QS + 384;
constexpr int SM_BAR = SM_OS + 384;
constexpr int SM_XBAR = SM_BAR + 24 * 8;
constexpr int SM_MISC = SM_XBAR + 8 * 8;
constexpr int SM_ONE = SM_MISC + 16;
constexpr int SM_ZERO = SM_ONE + 160;
constexpr int XCAP = 48;
constexpr int XSTR = 16 + 4 * XCAP;
constexpr int SM_XL = SM_ZERO + 160;
constexpr int SM_TOTAL = SM_XL + 8 * XSTR;
static_assert(SM_TOTAL <= 232448, "shared memory");

constexpr unsigned long long POL_EF = 0x12F0000000000000ull;
constexpr unsigned long long POL_EN = 0x16F0000000000000ull;

#define RT_MASK 0xF2E0u
#define RT_MASK2 0xEAE0u
#define WO_AT1 5
#define FFN_PROMO CU_TENSOR_MAP_L2_PROMOTION_NONE
#define FFN_POL POL_EF
#define HAS_FFN (__float_as_uint(misc[1]) < DN0 + NDN)
#define ACC_STR 1
#define NPRE 6

#define STAG 200
#define L1R 3
#define PRE1 13
#define HOLD 2
#define DNTH 23
constexpr int V0_AT = 8;
constexpr unsigned long long SEQ1 = 0x2765431076543210ull;
constexpr uint32_t IN_S1 = 0xAA49, IN_S0 = 0x124, PARITY1 = 0x6638, PARITY2 = 0xCE;
#define KEEP4 1
constexpr int NQ = 48;
constexpr int SPIN_CAP = 1 << 19;
constexpr uint32_t ONES = 0x3F803F80u;

struct alignas(1024) Scratch {
    uint4 hx[NCTA * 48];
    uint4 pad0[32 * 5 * 32 + 160];
    uint4 acc[2][216 * 8];
    uint4 ay[160];
    uint4 ah[NG * 8];
    uint2 mx[NH * 32];
    uint32_t ticket[32];
    uint32_t pad1[32];
};
__device__ Scratch g_scr;
#define PROF_T(i)
#define PROF_X(i)
#define PC(i)

__device__ __forceinline__ uint32_t smem_u32(const void* p) { return (uint32_t)__cvta_generic_to_shared(p); }
__device__ __forceinline__ void mbar_init(uint32_t bar, uint32_t cnt) {
    asm volatile("mbarrier.init.shared::cta.b64 [%0], %1;" ::"r"(bar), "r"(cnt) : "memory");
}
__device__ __forceinline__ void mbar_expect_tx(uint32_t bar, uint32_t bytes) {
    asm volatile("mbarrier.arrive.expect_tx.shared::cta.b64 _, [%0], %1;" ::"r"(bar), "r"(bytes) : "memory");
}
__device__ __forceinline__ bool mbar_test(uint32_t bar, uint32_t parity) {
    uint32_t done;
    asm volatile("{\n.reg .pred p;\nmbarrier.try_wait.parity.shared::cta.b64 p, [%1], %2;\nselp.u32 %0, 1, 0, p;\n}"
                 : "=r"(done) : "r"(bar), "r"(parity) : "memory");
    return done;
}
__device__ __forceinline__ void mbar_wait(uint32_t bar, uint32_t parity) {
    int it = 0;
    while (!mbar_test(bar, parity) && ++it < SPIN_CAP) {}
}
__device__ __forceinline__ void tma2d(uint32_t dst, const CUtensorMap* map, int c0, int c1, uint32_t bar, unsigned long long pol) {
    asm volatile("cp.async.bulk.tensor.2d.shared::cluster.global.mbarrier::complete_tx::bytes.L2::cache_hint [%0], [%1, {%3, %4}], [%2], %5;"
                 ::"r"(dst), "l"(map), "r"(bar), "r"(c0), "r"(c1), "l"(pol) : "memory");
}
__device__ __forceinline__ void tma3d(uint32_t dst, const CUtensorMap* map, int c0, int c1, int c2, uint32_t bar, unsigned long long pol) {
    asm volatile("cp.async.bulk.tensor.3d.shared::cluster.global.mbarrier::complete_tx::bytes.L2::cache_hint [%0], [%1, {%3, %4, %5}], [%2], %6;"
                 ::"r"(dst), "l"(map), "r"(bar), "r"(c0), "r"(c1), "r"(c2), "l"(pol) : "memory");
}
__device__ __forceinline__ void tile_load(uint32_t dst, const CUtensorMap* map, int row, uint32_t bar, uint32_t dep, uint32_t zero) {
    asm volatile("{\n.reg .pred p;\n.reg .b32 n;\nmad.lo.u32 n, %5, %6, 6144;\nelect.sync _|p, 0xffffffff;\n"
                 "@p mbarrier.arrive.expect_tx.shared::cta.b64 _, [%2], n;\n"
                 "@p cp.async.bulk.tensor.2d.shared::cluster.global.mbarrier::complete_tx::bytes.L2::cache_hint [%0], [%1, {0, %3}], [%2], %4;\n}"
                 ::"r"(dst), "l"(map), "r"(bar), "r"(row), "l"(POL_EF), "r"(dep), "r"(zero) : "memory");
}
__device__ __forceinline__ void tile_keep(const CUtensorMap* map, int row) {
    asm volatile("{\n.reg .pred p;\nelect.sync _|p, 0xffffffff;\n"
                 "@p cp.async.bulk.prefetch.tensor.2d.L2.global.L2::cache_hint [%0, {0, %1}], %2;\n}"
                 ::"l"(map), "r"(row), "l"(POL_EN) : "memory");
}
__device__ __forceinline__ void tile_load_l1(uint32_t dst, const void* base, int row, uint32_t bar, int lane) {
    const char* g = static_cast<const char*>(base) + (size_t)row * 128 + lane * 16;
    const uint32_t s0 = dst + (lane >> 3) * 128 + (((lane & 7) ^ (lane >> 3)) << 4), s1 = s0 ^ 64;
#pragma unroll
    for (int k = 0; k < 12; k++)
        asm volatile("cp.async.ca.shared.global.L2::cache_hint [%0], [%1], 16, %2;" ::"r"(((k & 1) ? s1 : s0) + k * 512), "l"(g + k * 512), "l"(POL_EF) : "memory");
    asm volatile("cp.async.mbarrier.arrive.shared::cta.b64 [%0];" ::"r"(bar) : "memory");
    __syncwarp();
    if (lane == 0) asm volatile("mbarrier.arrive.shared::cta.b64 _, [%0];" ::"r"(bar) : "memory");
}
__device__ __forceinline__ bool elect_one() {
    uint32_t p;
    asm volatile("{\n.reg .pred p;\nelect.sync _|p, 0xffffffff;\nselp.u32 %0, 1, 0, p;\n}" : "=r"(p));
    return p;
}
__device__ __forceinline__ void lds128(uint32_t addr, uint32_t& a, uint32_t& b, uint32_t& c, uint32_t& d) {
    asm volatile("ld.shared.v4.u32 {%0,%1,%2,%3}, [%4];" : "=r"(a), "=r"(b), "=r"(c), "=r"(d) : "r"(addr) : "memory");
}
__device__ __forceinline__ void lds128p(uint32_t addr, uint32_t on, uint32_t& a, uint32_t& b, uint32_t& c, uint32_t& d) {
    asm volatile("{\n.reg .pred p;\nsetp.ne.u32 p, %5, 0;\n@p ld.shared.v4.u32 {%0,%1,%2,%3}, [%4];\n}" : "+r"(a), "+r"(b), "+r"(c), "+r"(d) : "r"(addr), "r"(on) : "memory");
}
__device__ __forceinline__ void lds64(uint32_t addr, uint32_t& a, uint32_t& b) {
    asm volatile("ld.shared.v2.u32 {%0,%1}, [%2];" : "=r"(a), "=r"(b) : "r"(addr) : "memory");
}
__device__ __forceinline__ void ldsm4t(uint32_t addr, uint32_t (&a)[4]) {
    asm volatile("ldmatrix.sync.aligned.m8n8.x4.trans.shared.b16 {%0,%1,%2,%3}, [%4];" : "=r"(a[0]), "=r"(a[1]), "=r"(a[2]), "=r"(a[3]) : "r"(addr) : "memory");
}
__device__ __forceinline__ void mma16816(float (&c)[4], uint32_t a0, uint32_t a1, uint32_t a2, uint32_t a3, uint32_t b0, uint32_t b1) {
    asm("mma.sync.aligned.m16n8k16.row.col.f32.bf16.bf16.f32 {%0,%1,%2,%3}, {%4,%5,%6,%7}, {%8,%9}, {%0,%1,%2,%3};"
        : "+f"(c[0]), "+f"(c[1]), "+f"(c[2]), "+f"(c[3]) : "r"(a0), "r"(a1), "r"(a2), "r"(a3), "r"(b0), "r"(b1));
}
__device__ __forceinline__ void mma16816v(float (&c)[4], uint32_t a0, uint32_t a1, uint32_t a2, uint32_t a3, uint32_t b0, uint32_t b1) {
    asm volatile("mma.sync.aligned.m16n8k16.row.col.f32.bf16.bf16.f32 {%0,%1,%2,%3}, {%4,%5,%6,%7}, {%8,%9}, {%0,%1,%2,%3};"
        : "+f"(c[0]), "+f"(c[1]), "+f"(c[2]), "+f"(c[3]) : "r"(a0), "r"(a1), "r"(a2), "r"(a3), "r"(b0), "r"(b1));
}
__device__ __forceinline__ int xpos(int w) {
    const int seg = w / 40, r = w - 40 * seg;
    return 40 * seg + (r < 32 ? (r & 16) + 4 * (r & 3) + ((r >> 2) & 3) : 32 + 2 * (r & 3) + ((r >> 2) & 1));
}
#define NA_LD ""
#define NA_ST ""
__device__ __forceinline__ void st_pkt(uint4* p, uint32_t a, uint32_t b, uint32_t c, uint32_t d) {
    asm volatile("{\n.reg .b128 t;\n.reg .b64 lo, hi;\nmov.b64 lo, {%1,%2};\nmov.b64 hi, {%3,%4};\nmov.b128 t, {lo,hi};\nst.relaxed.gpu.global" NA_ST ".b128 [%0], t;\n}"
                 ::"l"(p), "r"(a), "r"(b), "r"(c), "r"(d) : "memory");
}
__device__ __forceinline__ void st_pktf(uint4* p, float a, float b, float c, float d, uint32_t bit) {
    st_pkt(p, __float_as_uint(a), __float_as_uint(b), __float_as_uint(c), (__float_as_uint(d) & ~1u) | bit);
}
__device__ __forceinline__ void red_pkt(uint4* p, float a, float b, float c) {
    asm volatile("red.relaxed.gpu.global.add.v4.f32 [%0], {%1,%2,%3,%4};" ::"l"(p), "f"(a), "f"(b), "f"(c), "f"(1.0f) : "memory");
}
__device__ __forceinline__ uint4 ld_pkt(const uint4* p) {
    uint4 v;
    asm volatile("{\n.reg .b128 t;\n.reg .b64 lo, hi;\nld.relaxed.gpu.global" NA_LD ".b128 t, [%4];\nmov.b128 {lo,hi}, t;\nmov.b64 {%0,%1}, lo;\nmov.b64 {%2,%3}, hi;\n}"
                 : "=r"(v.x), "=r"(v.y), "=r"(v.z), "=r"(v.w) : "l"(p) : "memory");
    return v;
}
__device__ __forceinline__ uint2 ld_pkt2(const uint2* p) {
    unsigned long long v;
    asm volatile("ld.relaxed.gpu.global" NA_LD ".b64 %0, [%1];" : "=l"(v) : "l"(p) : "memory");
    return make_uint2((uint32_t)v, (uint32_t)(v >> 32));
}
__device__ __forceinline__ void st_pkt2(uint2* p, uint32_t a, uint32_t b) {
    asm volatile("st.relaxed.gpu.global" NA_ST ".b64 [%0], %1;" ::"l"(p), "l"((unsigned long long)a | ((unsigned long long)b << 32)) : "memory");
}
__device__ __forceinline__ float ex2(float x) { float y; asm("ex2.approx.ftz.f32 %0, %1;" : "=f"(y) : "f"(x)); return y; }
__device__ __forceinline__ float rcp(float x) { float y; asm("rcp.approx.ftz.f32 %0, %1;" : "=f"(y) : "f"(x)); return y; }
__device__ __forceinline__ uint32_t pack2(float lo, float hi) {
    uint32_t r; asm("cvt.rn.bf16x2.f32 %0, %1, %2;" : "=r"(r) : "f"(hi), "f"(lo)); return r;
}
__device__ __forceinline__ float bf_lo(uint32_t w) { return __uint_as_float(w << 16); }
__device__ __forceinline__ float bf_hi(uint32_t w) { return __uint_as_float(w & 0xffff0000u); }
__device__ __forceinline__ float bfr(float x) { return bf_lo(pack2(x, 0.f)); }
__device__ __forceinline__ float f_(uint32_t u) { return __uint_as_float(u); }

template <int SK, typename AddrF>
__device__ __forceinline__ void gemv15(float (&cc)[3][4], uint32_t (&pre)[6][4], AddrF ad, uint32_t px, uint32_t px2, float& sv, float so) {
    uint32_t x0[4], x1[4], a[3][4];
    asm volatile("ld.shared.v4.u32 {%0,%1,%2,%3}, [%20];\nld.shared.v4.u32 {%4,%5,%6,%7}, [%20+64];\n"
                 "ldmatrix.sync.aligned.m8n8.x4.trans.shared.b16 {%8,%9,%10,%11}, [%21];\n"
                 "ldmatrix.sync.aligned.m8n8.x4.trans.shared.b16 {%12,%13,%14,%15}, [%22];\n"
                 "ldmatrix.sync.aligned.m8n8.x4.trans.shared.b16 {%16,%17,%18,%19}, [%23];\nbar.warp.sync 0xffffffff;"
                 : "=r"(x0[0]), "=r"(x0[1]), "=r"(x0[2]), "=r"(x0[3]), "=r"(x1[0]), "=r"(x1[1]), "=r"(x1[2]), "=r"(x1[3]),
                   "=r"(a[0][0]), "=r"(a[0][1]), "=r"(a[0][2]), "=r"(a[0][3]), "=r"(a[1][0]), "=r"(a[1][1]), "=r"(a[1][2]), "=r"(a[1][3]),
                   "=r"(a[2][0]), "=r"(a[2][1]), "=r"(a[2][2]), "=r"(a[2][3])
                 : "r"(px), "r"(ad(0) + 2 * SK), "r"(ad(1) + 2 * SK), "r"(ad(2) + 2 * SK) : "memory");
    __syncwarp();
    sv += __shfl_xor_sync(0xffffffffu, so, 16);
#pragma unroll
    for (int i = 0; i < 3; i++) {
        cc[i][0] = cc[i][1] = cc[i][2] = cc[i][3] = 0.f;
        mma16816v(cc[i], pre[i][0], pre[i][1], pre[i][2], pre[i][3], x0[0], x0[1]);
    }
    sv += __shfl_xor_sync(0xffffffffu, sv, 8);
#pragma unroll
    for (int i = 0; i < 3; i++) {
        mma16816v(cc[i], pre[3 + i][0], pre[3 + i][1], pre[3 + i][2], pre[3 + i][3], x0[2], x0[3]);
        ldsm4t(ad(i) + 3 * SK, pre[i]);
    }
    lds64(px2, x0[0], x0[1]);
    __syncwarp();
    sv += __shfl_xor_sync(0xffffffffu, sv, 4);
#pragma unroll
    for (int i = 0; i < 3; i++) {
        mma16816v(cc[i], a[i][0], a[i][1], a[i][2], a[i][3], x1[0], x1[1]);
        ldsm4t(ad(i) + 4 * SK, pre[3 + i]);
    }
    __syncwarp();
    sv += __shfl_xor_sync(0xffffffffu, sv, 2);
#pragma unroll
    for (int i = 0; i < 3; i++) mma16816v(cc[i], pre[i][0], pre[i][1], pre[i][2], pre[i][3], x1[2], x1[3]);
    sv += __shfl_xor_sync(0xffffffffu, sv, 1);
#pragma unroll
    for (int i = 0; i < 3; i++) mma16816v(cc[i], pre[3 + i][0], pre[3 + i][1], pre[3 + i][2], pre[3 + i][3], x0[0], x0[1]);
}
__device__ __forceinline__ void gemv15r(float (&cc)[3][4], const uint32_t (&pre)[6][4], const uint32_t (&ext)[NQ][4], uint32_t px, uint32_t px2, float& sv, float so) {
    uint32_t x0[4], x1[4], x2[2];
    float cd[3][4];
    lds128(px, x0[0], x0[1], x0[2], x0[3]);
    lds128(px + 64, x1[0], x1[1], x1[2], x1[3]);
    lds64(px2, x2[0], x2[1]);
    sv += __shfl_xor_sync(0xffffffffu, so, 16);
#pragma unroll
    for (int i = 0; i < 3; i++) {
        cc[i][0] = cc[i][1] = cc[i][2] = cc[i][3] = cd[i][0] = cd[i][1] = cd[i][2] = cd[i][3] = 0.f;
        mma16816v(cc[i], pre[i][0], pre[i][1], pre[i][2], pre[i][3], x0[0], x0[1]);
        mma16816v(cd[i], pre[3 + i][0], pre[3 + i][1], pre[3 + i][2], pre[3 + i][3], x0[2], x0[3]);
    }
    sv += __shfl_xor_sync(0xffffffffu, sv, 8);
#pragma unroll
    for (int i = 0; i < 3; i++) {
        mma16816v(cc[i], ext[i][0], ext[i][1], ext[i][2], ext[i][3], x1[0], x1[1]);
        mma16816v(cd[i], ext[3 + i][0], ext[3 + i][1], ext[3 + i][2], ext[3 + i][3], x1[2], x1[3]);
    }
    sv += __shfl_xor_sync(0xffffffffu, sv, 4);
#pragma unroll
    for (int i = 0; i < 3; i++) mma16816v(cc[i], ext[6 + i][0], ext[6 + i][1], ext[6 + i][2], ext[6 + i][3], x2[0], x2[1]);
    sv += __shfl_xor_sync(0xffffffffu, sv, 2);
    sv += __shfl_xor_sync(0xffffffffu, sv, 1);
#pragma unroll
    for (int i = 0; i < 3; i++) { cc[i][0] += cd[i][0]; cc[i][1] += cd[i][1]; cc[i][2] += cd[i][2]; cc[i][3] += cd[i][3]; }
}

__device__ __forceinline__ float warp_max(float x) {
    int i = __float_as_int(x);
    i = __reduce_max_sync(0xffffffffu, i ^ ((i >> 31) & 0x7fffffff));
    return __int_as_float(i ^ ((i >> 31) & 0x7fffffff));
}
__device__ __forceinline__ void idle(uint32_t clk) {
    uint32_t t0, t;
    asm volatile("mov.u32 %0, %%clock;" : "=r"(t0) :: "memory");
    do asm volatile("mov.u32 %0, %%clock;" : "=r"(t) :: "memory"); while (t - t0 < clk);
}
__device__ __forceinline__ uint32_t now_ns() { uint32_t t; asm volatile("mov.u32 %0, %%globaltimer_lo;" : "=r"(t)); return t; }
__device__ __forceinline__ int opq(int x) { asm volatile("" : "+r"(x)); return x; }
__device__ __forceinline__ uint32_t opq(uint32_t x) { asm volatile("" : "+r"(x)); return x; }
__device__ __forceinline__ uint32_t pin(uint32_t x) { return __shfl_sync(0xffffffffu, x, threadIdx.x & 31); }
template <typename T> __device__ __forceinline__ T* pin(T* p) {
    const unsigned long long v = (unsigned long long)p;
    return (T*)((unsigned long long)pin((uint32_t)v) | (unsigned long long)pin((uint32_t)(v >> 32)) << 32);
}
template <typename T> __device__ __forceinline__ T* opq(T* p) { asm volatile("" : "+l"(p)); return p; }
__device__ __forceinline__ float4 lds4f(uint32_t a) { float4 v; asm volatile("ld.shared.v4.f32 {%0,%1,%2,%3}, [%4];" : "=f"(v.x), "=f"(v.y), "=f"(v.z), "=f"(v.w) : "r"(a) : "memory"); return v; }
__device__ __forceinline__ float2 lds2f(uint32_t a) { float2 v; asm volatile("ld.shared.v2.f32 {%0,%1}, [%2];" : "=f"(v.x), "=f"(v.y) : "r"(a) : "memory"); return v; }
__device__ __forceinline__ void ln_stats(uint32_t st, float& mean, float& inv) {
    const float4 a = lds4f(st), b = lds4f(st + 16), c = lds4f(st + 32), d = lds4f(st + 48);
    const float s2 = ((a.x + a.z) + (b.x + b.z)) + ((c.x + c.z) + (d.x + d.z));
    const float md = (((a.y + a.w) + (b.y + b.w)) + ((c.y + c.w) + (d.y + d.w))) * (1.0f / DM);
    const float var = fmaxf(s2 * (1.0f / DM) - md * md, 0.f);
    mean = bfr(md);
    asm("rsqrt.approx.ftz.f32 %0, %1;" : "=f"(inv) : "f"(var + 1e-5f));
}
__device__ __forceinline__ void sts32(uint32_t a, float v) { asm volatile("st.shared.f32 [%0], %1;" ::"r"(a), "f"(v) : "memory"); }
__device__ __forceinline__ void sts64(uint32_t a, float v, float w) { asm volatile("st.shared.v2.f32 [%0], {%1,%2};" ::"r"(a), "f"(v), "f"(w) : "memory"); }

__device__ __forceinline__ uint32_t prmt(uint32_t a, uint32_t b, uint32_t s) { uint32_t r; asm("prmt.b32 %0, %1, %2, %3;" : "=r"(r) : "r"(a), "r"(b), "r"(s)); return r; }
__device__ __forceinline__ uint32_t bmul2(uint32_t a, uint32_t b) { uint32_t r; asm("mul.rn.bf16x2 %0, %1, %2;" : "=r"(r) : "r"(a), "r"(b)); return r; }
__device__ __forceinline__ void sts128(uint32_t addr, uint32_t a, uint32_t b, uint32_t c, uint32_t d) {
    asm volatile("st.shared.v4.u32 [%0], {%1,%2,%3,%4};" ::"r"(addr), "r"(a), "r"(b), "r"(c), "r"(d) : "memory");
}
__device__ __forceinline__ uint4 ldg128(const uint4* p) {
    uint4 v;
    asm volatile("ld.volatile.global.v4.u32 {%0,%1,%2,%3}, [%4];" : "=r"(v.x), "=r"(v.y), "=r"(v.z), "=r"(v.w) : "l"(p) : "memory");
    return v;
}
__device__ __forceinline__ uint32_t lds32(uint32_t a) { uint32_t v; asm volatile("ld.shared.u32 %0, [%1];" : "=r"(v) : "r"(a) : "memory"); return v; }
__device__ __forceinline__ uint32_t lds16(uint32_t a) { unsigned short v; asm volatile("ld.shared.u16 %0, [%1];" : "=h"(v) : "r"(a) : "memory"); return v; }
__device__ __forceinline__ void unpack8(uint32_t la, uint32_t lb, uint32_t c, uint32_t (&w)[4]) {
    const uint32_t ha = c & 0x87878787u, hb = __funnelshift_l(c, c, 4) & 0x87878787u;
    w[0] = prmt(la, ha, 0x5140); w[1] = prmt(la, ha, 0x7362); w[2] = prmt(lb, hb, 0x5140); w[3] = prmt(lb, hb, 0x7362);
}
__device__ __forceinline__ uint32_t bdiff2(uint32_t y, uint32_t inv, uint32_t x) {
    uint32_t r;
    asm("{\n.reg .b32 n;\nneg.bf16x2 n, %3;\nfma.rn.bf16x2 %0, %1, %2, n;\n}" : "=r"(r) : "r"(y), "r"(inv), "r"(x));
    return r;
}
__device__ __forceinline__ uint32_t pack_scale(uint32_t tile, int lane, uint32_t inv_addr) {
    uint32_t m = 0;
#pragma unroll 1
    for (int k = 0; k < 12; k++) {
        uint32_t a, b, c, d;
        lds128(tile + k * 512 + lane * 16, a, b, c, d);
        asm("max.xorsign.abs.bf16x2 %0, %0, %1;" : "+r"(a) : "r"(b));
        asm("max.xorsign.abs.bf16x2 %0, %0, %1;" : "+r"(c) : "r"(d));
        asm("max.xorsign.abs.bf16x2 %0, %0, %1;" : "+r"(a) : "r"(c));
        asm("max.xorsign.abs.bf16x2 %0, %0, %1;" : "+r"(m) : "r"(a));
    }
    m = __reduce_max_sync(0xffffffffu, max(m & 0x7fffu, (m >> 16) & 0x7fffu));
    const uint32_t inv = (112u + min((m + 0x28u) >> 7, 141u)) * 0x00800080u;
    if (lane == 0) asm volatile("st.shared.u32 [%0], %1;" ::"r"(inv_addr), "r"(inv) : "memory");
    return inv;
}

#define K_OFF(i) ((uint32_t)((3 * ((g >> 1) + 4 * (g & 1)) + ((i) >> 1)) * 128 + ((t ^ ((3 * ((g >> 1) + 4 * (g & 1)) + ((i) >> 1)) & 7) ^ (((i) & 1) << 2)) << 4)))
#define V_OFF(i) ((uint32_t)((6 * t + (i)) * 128 + ((g ^ ((6 * t + (i)) & 7)) << 4)))
template <bool ISV, typename DST>
__device__ __forceinline__ void pack_tile(uint32_t tile, int tau, int nm, uint32_t inv, uint32_t xl, int lane, DST dst) {
    const int g = lane >> 2, t = lane & 3;
    const uint32_t scl = 254u * 0x00800080u - inv;
#pragma unroll 1
    for (int m = 0; m < nm; m++) {
        const int row = ISV ? 6 * t + 2 * m : 3 * ((g >> 1) + 4 * (g & 1)) + m;
        const uint32_t a0 = tile + row * 128 + (((ISV ? g : t) ^ (row & 7)) << 4), a1 = ISV ? (a0 ^ 16) + 128 : a0 ^ 64;
        uint32_t l[8], cw[4], ck = 0, cd = 0;
#pragma unroll
        for (int r = 0; r < 4; r++) {
            uint32_t w0, w1, w2, w3;
            lds128(((r & 1) ? a1 : a0) + (r >> 1) * 3072, w0, w1, w2, w3);
            const uint32_t y0 = bmul2(w0, scl), y1 = bmul2(w1, scl), y2 = bmul2(w2, scl), y3 = bmul2(w3, scl);
            cd |= bdiff2(y0, inv, w0) | bdiff2(y1, inv, w1);
            cd |= bdiff2(y2, inv, w2) | bdiff2(y3, inv, w3);
            const uint32_t ha = prmt(y0, y1, 0x7531), hb = prmt(y2, y3, 0x7531);
            l[2 * r] = prmt(y0, y1, 0x6420); l[2 * r + 1] = prmt(y2, y3, 0x6420);
            asm("lop3.b32 %0, %1, 0x87878787, %2, 0xe2;" : "=r"(cw[r]) : "r"(ha), "r"(__funnelshift_r(hb, hb, 4)));
            ck |= ha | hb;
        }
        const uint32_t bad = __ballot_sync(0xffffffffu, (ck & 0x78787878u) | cd);
        if (bad) {
            const int src = __ffs(bad) - 1;
            const uint32_t b0 = __shfl_sync(0xffffffffu, a0, src), b1 = __shfl_sync(0xffffffffu, a1, src), n0 = lds32(xl);
            const uint32_t ax = ((lane & 8) ? b1 : b0) + (lane >> 4) * 3072 + 2 * (lane & 7), x = lds16(ax), y = bmul2(x, scl);
            const bool out = (y & 0x7800u) | bdiff2(y, inv, x);
            const uint32_t n = n0 + __popc(__ballot_sync(0xffffffffu, out) << (31 - lane)) - 1;
            if (out) {
                asm volatile("st.shared.u16 [%0], %1;" ::"r"(ax), "h"((unsigned short)0) : "memory");
                if (n < XCAP) sts32(xl + 16 + 4 * n, f_(x << 16 | tau << 12 | src << 7 | m << 5 | lane));
            }
            if (lane == 31) sts32(xl, f_(n + 1));
            __syncwarp();
            if (n0 <= XCAP) { m--; continue; }
        }
        uint32_t d[3] = {a0, a1, a0 + 3072};
        dst(m, d);
        sts128(d[0], l[0], l[1], l[2], l[3]);
        sts128(d[1], l[4], l[5], l[6], l[7]);
        sts128(d[2], cw[0], cw[1], cw[2], cw[3]);
    }
}

struct Maps { CUtensorMap k, v, wq, wo, w1, w3, w2, vr; const void* vp; const void* kp; uint32_t zero; };
#define RT_SEL ((wu & 1) ? RT_MASK2 : RT_MASK)
#define PFK 5
#define Q_AT 3
#define WO_T0 32200
#define K5D 370
#define PK_AT 6

__device__ __forceinline__ void load_ffn(const Maps& maps, int b, uint32_t dst, uint32_t bar) {
    const bool gu = b < NG;
    mbar_expect_tx(bar, gu ? 61440 : 49152);
    tma3d(dst, gu ? (b < NG / 2 ? &maps.w1 : &maps.w3) : &maps.w2, gu ? 48 * (b & (NG / 2 - 1)) : 16 * (b - DN0), 0, 0, bar, FFN_POL);
}

__device__ __forceinline__ void load_wo(const Maps& maps, uint32_t dst, int h, int c, uint32_t bar, int nbox) {
#pragma unroll 1
    for (int i = 0; i < nbox; i++) {
        if (!(i & 1)) mbar_expect_tx(bar + 4 * i, i + 1 < nbox ? 20480 : 10240);
        tma3d(dst + i * 10240, &maps.wo, 0, 5 * c, h * DH + 32 * i, bar + 4 * (i & 6), POL_EF);
    }
}

__global__ void __launch_bounds__(NT, 1)
decode_kernel(const __grid_constant__ Maps maps, const __nv_bfloat16* __restrict__ x_in, __nv_bfloat16* __restrict__ out) {
    extern __shared__ __align__(1024) unsigned char smem[];
    const int tid = threadIdx.x, warp = tid >> 5, lane = tid & 31;
    const int wu = __shfl_sync(0xffffffffu, tid >> 5, 0);
    const int b = blockIdx.x, h = b >> 2, c = b & 3;
    const uint32_t sb = smem_u32(smem);
    const uint32_t qbar = sb + SM_BAR + 16 * 8, fbar = qbar + 8, wbar = qbar + 16;
    uint32_t* xs32 = reinterpret_cast<uint32_t*>(smem + SM_XS);
    float* rr = reinterpret_cast<float*>(smem + SM_R);
    float* misc = reinterpret_cast<float*>(smem + SM_MISC);

    PROF_T(0);
    {
        uint2 xv = make_uint2(0u, 0u);
        const uint32_t t_start = now_ns();
        if (elect_one()) {
            const uint32_t rb = sb + SM_BAR + wu * 16, xb = sb + SM_XBAR + wu * 8;
            mbar_init(rb, 1); mbar_init(rb + 8, 1); mbar_init(xb, 1);
            if (wu == 0) mbar_init(qbar, 1);
            asm volatile("fence.mbarrier_init.release.cluster;" ::: "memory");
            const int row = (h * SK + (SK - WIN) + c * 1024 + wu * 128) * 3;
            const uint32_t ring = sb + SM_RING + wu * 2 * TILE;
#pragma unroll
            for (int n = 0; n < 3; n++) {
                const uint32_t bar = ((IN_S1 >> n) & 1) ? rb + 8 : ((IN_S0 >> n) & 1) ? rb : xb;
                mbar_expect_tx(bar, TILE);
                tma2d(((IN_S1 >> n) & 1) ? ring + TILE : ((IN_S0 >> n) & 1) ? ring : sb + SM_B + wu * TILE, &maps.k, 0, row + 48 * n, bar, POL_EF);
                if (n == 0 && wu == 0) {
                    mbar_expect_tx(qbar, 61440);
                    tma3d(sb + SM_Q, &maps.wq, 0, 160 * c, 3 * h, qbar, POL_EF);
                }
            }
            if (wu == 1) {
                mbar_init(fbar, 1);
#pragma unroll
                for (int i = 0; i < 3; i++) mbar_init(wbar + 8 * i, 1);
                asm volatile("fence.mbarrier_init.release.cluster;" ::: "memory");
            }
            if (wu >= 2) {
                const CUtensorMap* mp = wu == 2 ? &maps.v : wu == 3 ? &maps.wo : wu == 4 ? &maps.w1 : wu == 5 ? &maps.w3 : wu == 6 ? &maps.w2 : &maps.vr;
                asm volatile("prefetch.tensormap [%0];" ::"l"(mp) : "memory");
            }
        }
        if (tid < 160) asm volatile("ld.global.nc.v2.u32 {%0,%1}, [%2];" : "=r"(xv.x), "=r"(xv.y) : "l"(x_in + 4 * tid) : "memory");
        if (tid == 96) { misc[2] = 0.f; misc[3] = 0.f; }
        if (lane == 1) *reinterpret_cast<uint2*>(smem + SM_XL + warp * XSTR) = make_uint2(0u, t_start + WO_T0);
        if (tid >= 128 && tid < 148) {
            const uint32_t v = tid < 138 ? ONES : 0u;
            reinterpret_cast<uint4*>(smem + SM_ONE)[tid - 128] = make_uint4(v, v, v, v);
        }
        if (tid < 160) { xs32[xpos(2 * tid)] = xv.x; xs32[xpos(2 * tid + 1)] = xv.y; }
        __syncthreads();
        PROF_T(14);
        if (b == 0 && tid >= 232) asm volatile("st.relaxed.gpu.global.u32 [%0], %1;" ::"l"(g_scr.ticket + tid - 232), "r"(0) : "memory");
        if (tid == 64 || (tid == 65 && b < 216 - NCTA)) st_pkt(&g_scr.acc[1][(b + NCTA * (tid - 64)) * ACC_STR], 0, 0, 0, 0);
    }

    uint32_t kq[NQ][4];
    const float SC = 0.07216878364870322f * 1.4426950408889634f;

#pragma unroll 1
    for (int ph = 0; ph < 3; ph++) {
        const int layer = ph >> 1;
        const uint32_t tag = layer + 1;
        PROF_T(1 + layer * 16);
        if (ph) {
        {
            const int tl = opq(tid), warp = tl >> 5, lane = tl & 31, g = lane >> 2, t = lane & 3, mat = lane >> 3, r8 = lane & 7;
            const int kh = warp >> 2, mg = warp & 3;
            uint32_t aq[3];
#pragma unroll
            for (int i = 0; i < 3; i++) {
                const int ch = 6 * mg + 2 * i + (mat & 1);
                aq[i] = sb + SM_Q + (80 * kh + (mat >> 1) * 8 + r8) * 128 + (ch >> 3) * 20480 + (((ch & 7) ^ r8) << 4);
            }
#define PF_K5 if (layer == 1 && PFK) tile_keep(&maps.k, (h * SK + (SK - WIN) + c * 1024 + wu * 128 + PFK * 16) * 3);
            uint2 xv = make_uint2(0u, 0u);
            mbar_wait(qbar, 0);
            uint32_t pre[6][4];
#pragma unroll
            for (int n = 0; n < 6; n++) ldsm4t(aq[n % 3] + (n / 3) * 2048, pre[n]);
            if (layer == 1) {
                __syncthreads();
                if (elect_one()) {
                    const uint32_t bar = sb + SM_BAR + wu * 16;
                    asm volatile("mbarrier.expect_tx.relaxed.cta.shared::cta.b64 [%0], 1536;" ::"r"(bar) : "memory");
#pragma unroll
                    for (int k = 0; k < 3; k++)
                        tma2d(sb + SM_Q + v1_pos(3 * wu + k), &maps.vr, 0, (h * SK + (SK - WIN) + c * 1024 + wu * 128) / 2 + 8 + 2 * k, bar, POL_EF);
                }
            }
            const uint32_t pm = opq(g == 1 ? sb + SM_ONE : sb + SM_XS + 160 * (2 * c + kh) + 16 * t), pm2 = opq(pm + 128 - (g == 1 ? 0 : 8 * t));
            const uint32_t dq = opq(sb + SM_R + 8 * (kh * 192 + 48 * mg + g)), ds = opq(sb + SM_ST + 8 * warp + (lane < 16 ? 4 : 0));
            const bool wr = t == 0, ws = (lane & 15) == 0, lo = lane < 16;
            if (wu < 5) {
                const int p0 = xpos(2 * tl), p1 = xpos(2 * tl + 1);
                if (layer == 1) {
                    uint4 v;
                    int it = 0;
                    do { v = ld_pkt(&g_scr.ay[tl]); } while (!__all_sync(0xffffffffu, v.w == 1) && ++it < SPIN_CAP);
                    xv = make_uint2(v.x, v.y);
                    xs32[p0] = xv.x; xs32[p1] = xv.y;
                } else xv = make_uint2(xs32[p0], xs32[p1]);
            }
            if (layer) PC(24);
            if (layer) __syncthreads();
            PF_K5
            if (layer) PC(25);
            PROF_T(13 + layer * 16);
            const float e0 = bf_lo(xv.x), e1 = bf_hi(xv.x), e2 = bf_lo(xv.y), e3 = bf_hi(xv.y);
            const float s1 = (e0 + e1) + (e2 + e3), s2 = (e0 * e0 + e1 * e1) + (e2 * e2 + e3 * e3);
            float sv = lo ? s1 : s2, cc[3][4];
            gemv15<2048>(cc, pre, [&](int i) { return aq[i]; }, pm, pm2, sv, lo ? s2 : s1);
            if (wr) {
#pragma unroll
                for (int i = 0; i < 3; i++) { sts64(dq + 128 * i, cc[i][0], cc[i][1]); sts64(dq + 128 * i + 64, cc[i][2], cc[i][3]); }
            }
            if (ws) sts32(ds, sv);
        }
        const uint32_t pa = opq(sb + SM_R + 32 * opq(tid)), st = opq(sb + SM_ST);
        uint4* const pq = opq(&g_scr.hx[b * 48 + opq(tid)]);
        if (layer) PC(26);
        __syncthreads();
        if (layer) PC(27);
        PROF_T(33 + layer * 16);
        if (tid < 48) {
            float mean, inv;
            ln_stats(st, mean, inv);
            const float4 a0 = lds4f(pa), a1 = lds4f(pa + 16), b0 = lds4f(pa + 1536), b1 = lds4f(pa + 1552);
            float q0 = inv * ((a0.x + b0.x) - mean * (a0.y + b0.y)), q1 = inv * ((a0.z + b0.z) - mean * (a0.w + b0.w));
            float q2 = inv * ((a1.x + b1.x) - mean * (a1.y + b1.y)), q3 = inv * ((a1.z + b1.z) - mean * (a1.w + b1.w));
            st_pktf(pq, q0, q1, q2, q3, 1);
        }
        if (layer == 1 && tid >= 192 && tid < 194 && b < 108) st_pkt(&g_scr.acc[0][(2 * b + opq(tid) - 192) * ACC_STR], 0, 0, 0, 0);
        }
        if (layer) PC(28);
        if (layer == 1 && (wu & 2)) {
            idle(K5D);
#pragma unroll 1
            for (int w = wu; w >= (wu > 4 ? wu - 2 : wu); w -= 2)
                tile_load(sb + SM_Q + c_slot(w), &maps.k, (h * SK + (SK - WIN) + c * 1024 + w * 128 + 5 * 16) * 3, sb + SM_XBAR + w * 8, 0, 0);
        }

        float sc0 = -INFINITY, sc1 = -INFINITY, sc2 = 0.f, sc3 = 0.f, mw;
        uint32_t pk0, pk1;
        float acc[3][4];
        {
            const uint32_t ring = sb + SM_RING + wu * 2 * TILE, rb = sb + SM_BAR + wu * 16;
            const uint32_t xtile = sb + SM_Q + c_slot(wu), xb = sb + SM_XBAR + wu * 8;
#define V_SEQ(n) ((int)(SEQ1 >> (4 * (n))) & 7)
#define SLOT1(n) (((IN_S1 >> (n)) & 1) ? ring + TILE : ((IN_S0 >> (n)) & 1) ? ring : sb + SM_B + wu * TILE)
#define BAR1(n) (((IN_S1 >> (n)) & 1) ? rb + 8 : ((IN_S0 >> (n)) & 1) ? rb : xb)
#define PAR1(n) ((PARITY1 >> (n)) & 1)
#define PAR2(n) ((PARITY2 >> (n)) & 1)
            const int row0 = (h * SK + (SK - WIN) + c * 1024 + wu * 128) * 3;
            auto issue1 = [&](int n, uint32_t dep, bool vph = false) {
                const CUtensorMap* mp = n < 8 ? &maps.k : &maps.v;
                const int tl = V_SEQ(n), row = row0 + tl * 48;
                const uint32_t dst = SLOT1(n), bar = BAR1(n);
                if (vph && wu < L1R && tl == 7 - (wu & 1)) {
                    tile_load_l1(dst, maps.vp, row, bar, opq(tid) & 31);
                    return;
                }
                tile_load(dst, mp, row, bar, dep, maps.zero);
                if ((RT_SEL >> (tl + (n & 8))) & 1) {
                    if (n != V0_AT + 1) tile_keep(mp, row);
                    else if ((opq(tid) & 31) < 8)
                        asm volatile("cp.async.bulk.prefetch.L2.global.L2::cache_hint [%0], 256, %1;"
                                     ::"l"(static_cast<const char*>(maps.vp) + (size_t)(row + 4 + 6 * (opq(tid) & 31)) * 128), "l"(POL_EN) : "memory");
                }
            };
            auto refill1 = [&](int s, uint32_t dep, bool vph = false) { issue1(s + (!vph || s < V0_AT ? 3 : 2), dep, vph); };
#define LANE_IDS const int tl = opq(tid), lane = tl & 31, g = lane >> 2, t = lane & 3; (void)tl; (void)lane; (void)g; (void)t;
            const uint32_t xl = sb + SM_XL + wu * XSTR;
            if (layer == 0) {
#pragma unroll 1
                for (int s = ph ? Q_AT : 0; s < (ph ? 5 : Q_AT); s++) {
                    LANE_IDS
                    const uint32_t tile = SLOT1(s);
                    mbar_wait(BAR1(s), PAR1(s));
                    const uint32_t scl = s == 0 ? pack_scale(tile, lane, xl + 8) : lds32(xl + 8);
                    pack_tile<false>(tile, s, 3, scl, xl, lane, [](int, uint32_t (&)[3]) {});
#pragma unroll
                    for (int n = 0; n < 5; n++) {
                        if (s == n) {
#pragma unroll
                            for (int m = 0; m < 3; m++) {
                                const uint32_t a = tile + K_OFF(2 * m);
                                lds128(a, kq[9 * n + 3 * m][0], kq[9 * n + 3 * m][1], kq[9 * n + 3 * m][2], kq[9 * n + 3 * m][3]);
                                lds128(a ^ 64, kq[9 * n + 3 * m + 1][0], kq[9 * n + 3 * m + 1][1], kq[9 * n + 3 * m + 1][2], kq[9 * n + 3 * m + 1][3]);
                                lds128(a + 3072, kq[9 * n + 3 * m + 2][0], kq[9 * n + 3 * m + 2][1], kq[9 * n + 3 * m + 2][2], kq[9 * n + 3 * m + 2][3]);
                            }
                        }
                    }
                    __syncwarp();
                    refill1(s, lds32(tile));
                }
                if (!ph) continue;
            }
            {
                const int tl = opq(tid);
                if (tl < 48) {
                    const int w = 2 * tl;
                    const uint32_t pos = opq(sb + SM_QS + 4 * (((w >> 2) & 3) * 24 + 2 * (w >> 4) + ((w >> 1) & 1)));
                    uint4 v[4];
                    int it = 0;
                    bool ok;
                    do {
#pragma unroll
                        for (int k = 0; k < 4; k++) v[k] = ld_pkt(&g_scr.hx[(h * 4 + k) * 48 + tl]);
                        ok = ~((v[0].w & v[1].w) & (v[2].w & v[3].w)) & 1;
                    } while (ok && ++it < SPIN_CAP);
                    sts32(pos, f_(pack2((f_(v[0].x) + f_(v[1].x)) + (f_(v[2].x) + f_(v[3].x)), (f_(v[0].y) + f_(v[1].y)) + (f_(v[2].y) + f_(v[3].y)))));
                    sts32(pos + 48, f_(pack2((f_(v[0].z) + f_(v[1].z)) + (f_(v[2].z) + f_(v[3].z)), (f_(v[0].w) + f_(v[1].w)) + (f_(v[2].w) + f_(v[3].w)))));
                }
            }
            if (layer) PC(29);
            __syncthreads();
            if (layer) PC(30);
            PROF_T(2 + layer * 16);
#define V1_REST(p) ((p) < 6 ? sb + SM_Q + v1_pos(3 * wu + ((p) >> 1)) + 256 * ((p) & 1) : ((sb + SM_R + wu * 784 + 127) & ~127u) - 1536 + 256 * (p))
#define V1_LOAD(bar) if (elect_one()) tma2d(V1_REST(6), &maps.vr, 0, row0 / 6 + 14, bar, POL_EF);
#define V1_EXPECT(bar) { if ((opq(tid) & 31) == 0) asm volatile("mbarrier.expect_tx.relaxed.cta.shared::cta.b64 [%0], 512;" ::"r"(bar) : "memory"); }
            if (layer == 1 && wu < 2) tile_load(xtile, &maps.k, row0 + 5 * 48, xb, 0, 0);
            if (layer == 1 && wu >= 4) idle(STAG);
            {
                uint32_t qf[12];
                int t;
                {
                    const int lane = opq(tid) & 31;
                    t = lane & 3;
                    const uint32_t qa = sb + SM_QS + (2 * t + ((lane >> 2) & 1)) * 48;
#pragma unroll
                    for (int i = 0; i < 3; i++) lds128(qa + 16 * i, qf[4 * i], qf[4 * i + 1], qf[4 * i + 2], qf[4 * i + 3]);
                }
                const uint32_t sq = lds32(xl + 8) - 64u * 0x00800080u;
#pragma unroll
                for (int i = 0; i < 12; i++) qf[i] = bmul2(qf[i], sq);
#define KR_STEP(tau, m) \
                    _Pragma("unroll") for (int i = 2 * (m); i < 2 * (m) + 2; i++) { \
                        const int q0 = 9 * tau + 3 * (i >> 1), r = i & 1; \
                        uint32_t w[4]; \
                        unpack8(kq[q0][2 * r], kq[q0][2 * r + 1], kq[q0 + 2][r], w); \
                        mma16816(cA, w[0], w[1], w[2], w[3], qf[2 * i], qf[2 * i + 1]); \
                        unpack8(kq[q0 + 1][2 * r], kq[q0 + 1][2 * r + 1], kq[q0 + 2][2 + r], w); \
                        mma16816(cB, w[0], w[1], w[2], w[3], qf[2 * i], qf[2 * i + 1]); \
                    }
#define KR_BEGIN float cA[4] = {0.f, 0.f, 0.f, 0.f}, cB[4] = {0.f, 0.f, 0.f, 0.f};
#define KR_END(tau) \
                    const float sA = (cA[0] + cA[3]) * 18446744073709551616.f, sB = (cB[0] + cB[3]) * 18446744073709551616.f; \
                    if (t == (tau & 3)) { if (tau < 4) { sc0 = sA; sc1 = sB; } else { sc2 = sA; sc3 = sB; } }
#define KR_SCORES(tau) { KR_BEGIN KR_STEP(tau, 0) KR_STEP(tau, 1) KR_STEP(tau, 2) KR_END(tau) }
                uint32_t va[3];
                {
                    const int lane = opq(tid) & 31, g = lane >> 2, t = lane & 3;
#pragma unroll
                    for (int i = 0; i < 3; i++) va[i] = ring + V_OFF(2 * i);
                }
#define V_STG(n) _Pragma("unroll") for (int j = 3 * (n); j < 3 * (n) + 3; j++) { \
                    const int i = (j % 12) >> 1; \
                    lds128p(((i & 1) ? (va[i >> 1] ^ 16) + 128 : va[i >> 1]) + (j / 12) * TILE + (j & 1) * 3072, layer, kq[j][0], kq[j][1], kq[j][2], kq[j][3]); }
                uint32_t dep = 0;
                {
                    KR_BEGIN
                    KR_STEP(0, 0) V_STG(0) KR_STEP(0, 1) V_STG(1) KR_STEP(0, 2) V_STG(2)
                    KR_END(0)
                }
                {
                    KR_BEGIN
                    KR_STEP(1, 0) V_STG(3)
                    __syncwarp();
                    dep = lds32(ring);
                    if (layer == 1) tile_load(ring, &maps.k, row0 + 6 * 48, rb, dep, maps.zero);
                    KR_STEP(1, 1) V_STG(4) KR_STEP(1, 2) V_STG(5)
                    KR_END(1)
                }
                {
                    KR_BEGIN
                    KR_STEP(2, 0) V_STG(6) KR_STEP(2, 1) V_STG(7)
                    __syncwarp();
                    dep = lds32(ring + TILE);
                    KR_STEP(2, 2)
                    if (layer == 1) {
                        V1_EXPECT(rb + 8)
                        tile_load(ring + TILE, &maps.k, row0 + 7 * 48, rb + 8, dep, maps.zero);
                        V1_LOAD(rb + 8)
                    }
                    KR_END(2)
                }
#pragma unroll 1
                for (int s = 5; s < 8; s++) {
                    {
                        LANE_IDS
                        const uint32_t tile = !layer ? SLOT1(s) : s == 5 ? xtile : ring + (s - 6) * TILE, tb = !layer ? BAR1(s) : s == 5 ? xb : rb + (s - 6) * 8;
                        const float ur = f_((318u << 23) - (lds32(xl + 8) << 16));
                        mbar_wait(tb, layer ? PAR2(s - 5) : PAR1(s));
                        if (layer) PROF_T(29 + s);
                        float cA[4] = {0.f, 0.f, 0.f, 0.f}, cB[4] = {0.f, 0.f, 0.f, 0.f};
#pragma unroll
                        for (int i = 0; i < 6; i++) {
                            uint32_t a0, a1, a2, a3;
                            lds128(tile + K_OFF(i), a0, a1, a2, a3);
                            mma16816(cA, a0, a1, a2, a3, qf[2 * i], qf[2 * i + 1]);
                            lds128(tile + K_OFF(i) + 3072, a0, a1, a2, a3);
                            mma16816(cB, a0, a1, a2, a3, qf[2 * i], qf[2 * i + 1]);
                        }
                        __syncwarp();
                        const uint32_t last = lds32(tile);
                        if (layer) tile_load(tile, &maps.v, row0 + (s - 2) * 48, tb, last, maps.zero);
                        else refill1(s, last);
                        if (t == (s & 3)) { sc2 = (cA[0] + cA[3]) * ur; sc3 = (cB[0] + cB[3]) * ur; }
                    }
                    if (s == 5) KR_SCORES(3)
                    if (s == 6) {
                        KR_SCORES(4)
                        const int lane = opq(tid) & 31;
                        const uint32_t nx = min(lds32(xl), (uint32_t)XCAP);
#pragma unroll 1
                        for (uint32_t n = 0; n < nx; n++) {
                            const uint32_t id = lds32(xl + 16 + 4 * n);
                            const uint32_t qo = 96 * ((id >> 7) & 3) + 48 * ((id >> 1) & 1) + 16 * ((id >> 5) & 3) + (id & 12) + 2 * (id & 1);
                            const float cr = bf_hi(id) * f_(lds16(sb + SM_QS + qo) << 16);
                            const int d = (int)(16 * ((id >> 9) & 7) + 4 * ((id >> 12) & 3) + ((id >> 13) & 2) + ((id >> 4) & 1) + ((id >> 8) & 128)) - 4 * lane;
                            if (d == 0) sc0 += cr;
                            if (d == 1) sc1 += cr;
                            if (d == 2) sc2 += cr;
                            if (d == 3) sc3 += cr;
                        }
                    }
                }
#undef KR_SCORES
#undef KR_STEP
#undef KR_BEGIN
#undef KR_END
#undef V_STG
                {
                    LANE_IDS
                    if (lds32(xl) > XCAP || !__all_sync(0xffffffffu, (fabsf(sc0) + fabsf(sc1)) + (fabsf(sc2) + fabsf(sc3)) < INFINITY)) {
                        const uint32_t qa = sb + SM_QS + (2 * t + (g & 1)) * 48;
#pragma unroll
                        for (int i = 0; i < 3; i++) lds128(qa + 16 * i, qf[4 * i], qf[4 * i + 1], qf[4 * i + 2], qf[4 * i + 3]);
                        const uint4* kg = reinterpret_cast<const uint4*>(static_cast<const char*>(maps.kp) + (size_t)row0 * 128) + ((g >> 1) + 4 * (g & 1)) * 24 + t;
#pragma unroll 1
                        for (int s = 0; s < 8; s++) {
                            float cA[4] = {0.f, 0.f, 0.f, 0.f}, cB[4] = {0.f, 0.f, 0.f, 0.f};
#pragma unroll
                            for (int i = 0; i < 6; i++) {
                                uint4 u = ldg128(kg + s * 384 + 4 * i);
                                mma16816v(cA, u.x, u.y, u.z, u.w, qf[2 * i], qf[2 * i + 1]);
                                u = ldg128(kg + s * 384 + 4 * i + 192);
                                mma16816v(cB, u.x, u.y, u.z, u.w, qf[2 * i], qf[2 * i + 1]);
                            }
                            if (t == s) { sc0 = cA[0] + cA[3]; sc1 = cB[0] + cB[3]; }
                            if (t + 4 == s) { sc2 = cA[0] + cA[3]; sc3 = cB[0] + cB[3]; }
                        }
                    }
                }
            }
            mw = warp_max(fmaxf(fmaxf(sc0, sc1), fmaxf(sc2, sc3)));
            pk0 = pack2(ex2((sc0 - mw) * SC), ex2((sc1 - mw) * SC));
            pk1 = pack2(ex2((sc2 - mw) * SC), ex2((sc3 - mw) * SC));
            sc2 = (bf_lo(pk0) + bf_hi(pk0)) + (bf_lo(pk1) + bf_hi(pk1));
            sc2 = (float)__reduce_add_sync(0xffffffffu, __float2uint_rn(sc2 * 16777216.f)) * (1.0f / 16777216.f);
            if ((opq(tid) & 31) == 0) st_pkt2(&g_scr.mx[h * 32 + c * 8 + wu], __float_as_uint(mw), (__float_as_uint(sc2) & ~3u) | tag);
            auto head_factor = [&]() {
                const int lane = opq(tid) & 31;
                int it = 0;
                while (!__all_sync(0xffffffffu, (__float_as_uint(sc1) & 3u) == tag) && ++it < SPIN_CAP) {
                    const uint2 mv = ld_pkt2(&g_scr.mx[h * 32 + lane]); sc0 = f_(mv.x); sc1 = f_(mv.y);
                }
                const float e = ex2((sc0 - warp_max(sc0)) * SC);
                const uint32_t d = __reduce_add_sync(0xffffffffu, __float2uint_rn(sc1 * e * 524288.f));
                sc3 = __shfl_sync(0xffffffffu, e, c * 8 + wu) * 524288.f * rcp((float)d);
            };
#pragma unroll
            for (int s = 0; s < 3; s++) { acc[s][0] = acc[s][1] = acc[s][2] = acc[s][3] = 0.f; }
#define P_CONSTS \
                const uint32_t sel0 = g == 0 ? 0x4410u : (g == 1 ? 0x1044u : 0x4444u); \
                const uint32_t sel1 = g == 2 ? 0x4410u : (g == 3 ? 0x1044u : 0x4444u); \
                const int src00 = 4 * (t < 2 ? 4 * t : 4 * (t - 2) + 1);
#define P_FRAGS(tau) \
                const uint32_t pk = ((tau) & 4) ? pk1 : pk0; \
                const uint32_t w0 = __shfl_sync(0xffffffffu, pk, src00 + ((tau) & 3)); \
                const uint32_t w1 = __shfl_sync(0xffffffffu, pk, src00 + ((tau) & 3) + 8); \
                uint32_t pb[4][2]; \
                _Pragma("unroll") for (int j = 0; j < 4; j++) { \
                    const uint32_t src = ((j & 1) ? w1 : w0) >> ((j >> 1) * 16); \
                    pb[j][0] = __byte_perm(src, 0, sel0); pb[j][1] = __byte_perm(src, 0, sel1); \
                }
            if (layer == 0) {
#pragma unroll 1
                for (int s = 8; s < 16; s++) {
                    LANE_IDS
                    P_CONSTS
                    if (s == 13) { const uint2 mv = ld_pkt2(&g_scr.mx[h * 32 + lane]); sc0 = f_(mv.x); sc1 = f_(mv.y); }
                    P_FRAGS(V_SEQ(s))
                    mbar_wait(BAR1(s), PAR1(s));
                    const uint32_t tile = SLOT1(s);
#pragma unroll
                    for (int j = 0; j < 4; j++) {
#pragma unroll
                        for (int u = 0; u < 3; u++) {
                            uint32_t a0, a1, a2, a3;
                            lds128(tile + (j >> 1) * 3072 + V_OFF(3 * (j & 1) + u), a0, a1, a2, a3);
                            mma16816(acc[u], a0, a1, a2, a3, pb[j][0], pb[j][1]);

                        }
                    }
                    __syncwarp();
                    if (s < V0_AT || (s > V0_AT + 1 && s < 14)) refill1(s, lds32(tile), true);
                    if (s == V0_AT || s == V0_AT + 1) {
                        {
                            const uint32_t ar = sb + SM_R + wu * 784 + 32 * g + 16 * t;
                            if (t < 2) {
#pragma unroll
                                for (int u = 0; u < 3; u++) sts128(ar + 256 * u, __float_as_uint(acc[u][0]), __float_as_uint(acc[u][1]), __float_as_uint(acc[u][2]), __float_as_uint(acc[u][3]));
                            }
                        }
                        const uint32_t scl = s == V0_AT ? pack_scale(tile, lane, xl + 12) : lds32(xl + 12);
                        pack_tile<true>(tile, s + 8 - V0_AT, V0_AT + 3 - s, scl, xl, lane, [&](int m, uint32_t (&d)[3]) {
                            if (s != V0_AT && m == 0) {
#pragma unroll
                                for (int k = 0; k < 3; k++) d[k] = ring + 3072 + V_OFF(2 * k + 1);
                            }
                        });
                        if (s != V0_AT) {
                            lds128(tile + V_OFF(2), kq[45][0], kq[45][1], kq[45][2], kq[45][3]);
                            lds128(tile + V_OFF(3), kq[46][0], kq[46][1], kq[46][2], kq[46][3]);
                            lds128(tile + V_OFF(2) + 3072, kq[47][0], kq[47][1], kq[47][2], kq[47][3]);
                            __syncwarp();
                            issue1(V0_AT + 3, lds32(tile));
                        }
                        const int ln = opq(tid) & 31;
                        const uint32_t ar = sb + SM_R + wu * 784 + 8 * (ln & 28) + 16 * (ln & 1);
#pragma unroll
                        for (int u = 0; u < 3; u++) {
                            uint32_t a0, a1, a2, a3;
                            lds128(ar + 256 * u, a0, a1, a2, a3);
                            acc[u][0] = f_(a0); acc[u][1] = f_(a1); acc[u][2] = f_(a2); acc[u][3] = f_(a3);
                        }
                    }
                    if (s == 13) head_factor();
                    if (s >= 14 && elect_one()) {
                        if (atomicAdd(reinterpret_cast<unsigned*>(misc + 3), 1u) == 14u && (int)(now_ns() - lds32(xl + 4)) >= 0) {
                            PROF_X(47);
                            load_wo(maps, sb + SM_B, h, c, wbar, 6);
                            atomicAdd(reinterpret_cast<unsigned*>(misc + 3), 256u);
                        }
                    }
                }
            } else {
                LANE_IDS
                P_CONSTS
#pragma unroll
                for (int k = 0; k < 4; k++) lds128(V1_REST(t + 4 * (k >> 1)) + 16 * g + 128 * (k & 1), kq[36 + k][0], kq[36 + k][1], kq[36 + k][2], kq[36 + k][3]);
#pragma unroll 1
                for (int i = 3; i < 8; i++) {
                    const uint32_t tile = i > 3 ? ring + (i & 1) * TILE : xtile, tb = i > 3 ? rb + (i & 1) * 8 : xb;
                    if (i == 6) { const uint2 mv = ld_pkt2(&g_scr.mx[h * 32 + lane]); sc0 = f_(mv.x); sc1 = f_(mv.y); }
                    if (i == 7) head_factor();
                    if (i == PK_AT) {
                uint32_t nx, nk, ik, iv;
                lds128(xl, nx, nk, ik, iv);
                if (nx <= XCAP) {
                    const uint32_t pks = bmul2(pk0, iv);
#pragma unroll
                    for (int s = 0; s < 2; s++) {
                        const uint32_t pk1 = 0, pk0 = pks;
                        P_FRAGS(s)
#pragma unroll
                        for (int j = 0; j < 4; j++) {
#pragma unroll
                            for (int u = 0; u < 3; u++) {
                                const int i = 3 * (j & 1) + u, m = i >> 1, r = i & 1, hf = j >> 1;
                                if (s == 1 && m == 2) continue;
                                const int ql = s == 0 ? 4 * m + 2 * hf : m == 0 ? 3 + 4 * hf : 45 + hf, qc = s == 0 ? 4 * m + 1 : m == 0 ? 11 : 47;
                                uint32_t w[4];
                                unpack8(kq[ql][2 * r], kq[ql][2 * r + 1], kq[qc][2 * hf + r], w);
                                mma16816(acc[u], w[0], w[1], w[2], w[3], pb[j][0], pb[j][1]);
                            }
                        }
                    }
#pragma unroll 1
                    for (uint32_t n = 0; n < nx; n++) {
                        const uint32_t id = lds32(xl + 16 + 4 * n);
                        const int i = ((id >> 4) & 6) + ((id >> 3) & 1), key = ((id >> 6) & 6) + (i >= 3);
                        const uint32_t pw = __shfl_sync(0xffffffffu, pk0, 8 * (key & 3) + (key & 4) + ((id >> 12) & 3));
                        const float cr = bf_hi(id) * ((id & 16) ? bf_hi(pw) : bf_lo(pw));
                        const int d = (int)(64 * ((id >> 9) & 7) + 4 * (id & 4) + 4 * (i >= 3 ? i - 3 : i) + (id & 3) + ((~id >> 5) & 1024)) - 16 * lane;
#pragma unroll
                        for (int k = 0; k < 12; k++) if (d == k) acc[k >> 2][k & 3] += cr;
                    }
                } else {
                    const uint4* vg = reinterpret_cast<const uint4*>(static_cast<const char*>(maps.vp) + (size_t)row0 * 128) + 48 * t + g;
#pragma unroll 1
                    for (int s = 0; s < 2; s++) {
                        P_FRAGS(s)
#pragma unroll
                        for (int j = 0; j < 4; j++) {
#pragma unroll
                            for (int u = 0; u < 3; u++) {
                                if (s == 1 && (j & 1) && u) continue;
                                const uint4 w = ldg128(vg + 384 * s + 192 * (j >> 1) + 24 * (j & 1) + 8 * u);
                                mma16816v(acc[u], w.x, w.y, w.z, w.w, pb[j][0], pb[j][1]);
                            }
                        }
                    }
                }
#pragma unroll
                for (int s = 2; s > 0; s--) {
                    P_FRAGS(s)
#pragma unroll
                    for (int j = 0; j < 4; j++) {
#pragma unroll
                        for (int u = 0; u < 3; u++) {
                            if (s == 1 && !((j & 1) && u)) continue;
                            const int k = s == 2 ? 12 + 2 * (3 * (j & 1) + u) + (j >> 1) : 35 + (j >> 1) * 2 + u;
                            mma16816(acc[u], kq[k][0], kq[k][1], kq[k][2], kq[k][3], pb[j][0], pb[j][1]);
                        }
                    }
                }
                    }
                    P_FRAGS(i)
                    mbar_wait(tb, PAR2(i));
                    PROF_T(34 + i);
#pragma unroll
                    for (int k = 0; k < 6; k++) {
                        const uint32_t a = tile + V_OFF(k);
                        lds128(a, kq[24 + k][0], kq[24 + k][1], kq[24 + k][2], kq[24 + k][3]);
                        lds128(a + 3072, kq[30 + k][0], kq[30 + k][1], kq[30 + k][2], kq[30 + k][3]);
                    }
#pragma unroll
                    for (int j = 0; j < 4; j++) {
#pragma unroll
                        for (int u = 0; u < 3; u++) {
                            const int k = 24 + 6 * (j >> 1) + 3 * (j & 1) + u;
                            mma16816(acc[u], kq[k][0], kq[k][1], kq[k][2], kq[k][3], pb[j][0], pb[j][1]);
                        }
                    }
                    __syncwarp();
                    if (wu < L1R && i == 5 - (wu & 1)) tile_load_l1(tile, maps.vp, row0 + (i + 2) * 48, tb, lane);
                    else if (i == 4 || i == 5) tile_load(tile, &maps.v, row0 + (i + 2) * 48, tb, lds32(tile), maps.zero);
                    if (i == WO_AT1 && HAS_FFN && elect_one()) {
                        if (atomicAdd(reinterpret_cast<unsigned*>(misc + 2), 1u) == 7u) {
                            PROF_X(63);
                            load_wo(maps, sb + SM_Q, h, c, wbar, KEEP4 && __float_as_uint(misc[1]) >= DN0 ? 5 : 6);
                        }
                    }
                }
            }
#undef P_FRAGS
#undef P_CONSTS
#undef LANE_IDS
        }
        PROF_T(3 + layer * 16);
        PC(layer * 32 + 1);

        {
            const int tl = opq(tid), warp = tl >> 5, lane = tl & 31, g = lane >> 2, t = lane & 3;
            if (t < 2) {
#pragma unroll
                for (int u = 0; u < 3; u++)
                    *reinterpret_cast<float4*>(rr + warp * 196 + 64 * u + 8 * g + 4 * t) = make_float4(acc[u][0] * sc3, acc[u][1] * sc3, acc[u][2] * sc3, acc[u][3] * sc3);
            }
        }
        const uint32_t role1 = layer ? lds32(sb + SM_MISC + 4) : DN0 + NDN;
        const uint32_t pc = opq(sb + SM_R + 16 * opq(tid));
        uint4* const px0 = opq(&g_scr.hx[b * 48 + opq(tid)]);
        __syncthreads();
        PROF_T(4 + layer * 16);
        PC(layer * 32 + 2);
        uint32_t ticket = 0;
        if (layer == 0 && tid == 224)
            asm volatile("atom.relaxed.gpu.global.inc.u32 %0, [%1], 0x7fffffff;" : "=r"(ticket) : "l"(g_scr.ticket + 8 + (b >> 3)) : "memory");
        if (layer == 0 && tid == 224 && lds32(sb + SM_MISC + 12) < 256u) {
            int it = 0;
            while ((int)(now_ns() - lds32(sb + SM_XL + 4)) < 0 && ++it < SPIN_CAP) {}
            PROF_X(47);
            load_wo(maps, sb + SM_B, h, c, wbar, 6);
        }
        uint32_t pr;
        uint4* pacc;
        {
            const int tid = opq(threadIdx.x), warp = tid >> 5, lane = tid & 31, g = lane >> 2, t = lane & 3, mat = lane >> 3, r8 = lane & 7;
            const int kg = warp >> 1, mg = warp & 1;
            const bool wo2 = role1 < DN0 + NDN;
            const uint32_t aw2 = 40960 + (wo2 && KEEP4 && role1 >= DN0 && kg >= 2 ? SM_B - SM_Q : 0);
            uint32_t aw[5];
#pragma unroll
            for (int i = 0; i < 5; i++) {
                const uint32_t lin = ((mat >> 1) * 8 + r8) * 320 + 64 * i + 32 * mg + 16 * (mat & 1);
                aw[i] = sb + (wo2 ? SM_Q : SM_B) + 5120 * kg + (lin ^ ((lin >> 3) & 48));
            }
            float4 o = make_float4(0.f, 0.f, 0.f, 0.f);
            if (threadIdx.x < 48) {
                float4 v[8];
#pragma unroll
                for (int w = 0; w < 8; w++) v[w] = lds4f(pc + w * 784);
                o.x = ((v[0].x + v[1].x) + (v[2].x + v[3].x)) + ((v[4].x + v[5].x) + (v[6].x + v[7].x));
                o.y = ((v[0].y + v[1].y) + (v[2].y + v[3].y)) + ((v[4].y + v[5].y) + (v[6].y + v[7].y));
                o.z = ((v[0].z + v[1].z) + (v[2].z + v[3].z)) + ((v[4].z + v[5].z) + (v[6].z + v[7].z));
                o.w = ((v[0].w + v[1].w) + (v[2].w + v[3].w)) + ((v[4].w + v[5].w) + (v[6].w + v[7].w));
                st_pktf(px0, o.x, o.y, o.z, o.w, 0);
            }
#define CXE 1
            const uint32_t ao = pin(sb + SM_OS + 96 * kg + 16 * t), dw = pin(sb + SM_R + 16 * (16 * mg + g) + 4 * kg);
            pr = pin(sb + SM_R + 48 * tid); pacc = pin(&g_scr.acc[layer][(54 * c + tid) * ACC_STR]);
            const int w = 2 * tid;
            const uint32_t d0 = pin(sb + SM_OS + 4 * (24 * ((w >> 3) & 3) + ((w >> 2) & 1) + (w < 64 ? 4 * (w & 3) + 2 * (w >> 5) : 16 + 2 * (w & 3))));
            const uint32_t d1 = pin(d0 + (w < 64 ? 16 : 8));
            const uint4* pp[3];
#pragma unroll
            for (int k = 0; k < 3; k++) pp[k] = pin(&g_scr.hx[(h * 4 + ((c + 1 + k) & 3)) * 48 + min(tid, 47)]);
            bool ok = true;
            if ((PRE1 & 8) && layer) {
#pragma unroll
                for (int ks = 0; ks < 3; ks++) {
                    mbar_wait(wbar + 8 * ks, wo2);
#pragma unroll
                    for (int i = 0; i < 5; i++) ldsm4t(aw[i] + (ks == 2 ? aw2 : 20480 * ks), kq[3 * i + ks]);
                    if (ks == CXE && threadIdx.x < 48) {
#pragma unroll
                        for (int k = 0; k < 3; k++) { const uint4 v = ld_pkt(pp[k]); kq[20 + k][0] = v.x; kq[20 + k][1] = v.y; kq[20 + k][2] = v.z; kq[20 + k][3] = v.w; }
                    }
                }
                PROF_T(50);
                if (CXE < 3 && threadIdx.x < 48) {
                    ok = (kq[20][3] | kq[21][3] | kq[22][3]) & 1;
                    if (!ok) {
#pragma unroll
                        for (int k = 0; k < 3; k++) { o.x += f_(kq[20 + k][0]); o.y += f_(kq[20 + k][1]); o.z += f_(kq[20 + k][2]); o.w += f_(kq[20 + k][3]); }
                    }
                }
            }
            if (tid < 48) {
                if (ok) {
                    uint4 v3[3];
                    int it = 0;
                    do {
#pragma unroll
                        for (int k = 0; k < 3; k++) v3[k] = ld_pkt(pp[k]);
                        ok = (v3[0].w | v3[1].w | v3[2].w) & 1;
                    } while (ok && ++it < SPIN_CAP);
#pragma unroll
                    for (int k = 0; k < 3; k++) { o.x += f_(v3[k].x); o.y += f_(v3[k].y); o.z += f_(v3[k].z); o.w += f_(v3[k].w); }
                }
                sts32(d0, f_(pack2(o.x, o.y)));
                sts32(d1, f_(pack2(o.z, o.w)));
            }
            PC(layer * 32 + 3);
            __syncthreads();
            PROF_T(5 + layer * 16);
            PC(layer * 32 + 5);
            if (tid == 224 && layer == 0) {
                if (ticket >= 6 + ((b >> 3) & 1)) ticket = DN0 + NDN;
                else asm volatile("atom.relaxed.gpu.global.inc.u32 %0, [%1], 0x7fffffff;" : "=r"(ticket) : "l"(g_scr.ticket) : "memory");
            }
            uint32_t ob[6];
            lds128(ao, ob[0], ob[1], ob[2], ob[3]);
            lds64(ao + 64 - 8 * t, ob[4], ob[5]);
            float cc[5][4];
#pragma unroll
            for (int i = 0; i < 5; i++) cc[i][0] = cc[i][1] = cc[i][2] = cc[i][3] = 0.f;
            if ((PRE1 & 8) && layer) {
#pragma unroll
                for (int ks = 0; ks < 3; ks++) {
#pragma unroll
                    for (int i = 0; i < 5; i++) mma16816(cc[i], kq[3 * i + ks][0], kq[3 * i + ks][1], kq[3 * i + ks][2], kq[3 * i + ks][3], ob[2 * ks], ob[2 * ks + 1]);
                }
            } else {
#pragma unroll
                for (int ks = 0; ks < 3; ks++) {
                    mbar_wait(wbar + 8 * ks, wo2);
                    if (ks == 2) { PC(layer * 32 + 4); PROF_T(48 + layer * 2); }
                    uint32_t a[5][4];
#pragma unroll
                    for (int i = 0; i < 5; i++) ldsm4t(aw[i] + (ks == 2 ? aw2 : 20480 * ks), a[i]);
#pragma unroll
                    for (int i = 0; i < 5; i++) mma16816(cc[i], a[i][0], a[i][1], a[i][2], a[i][3], ob[2 * ks], ob[2 * ks + 1]);
                }
            }
            if (t == 0) {
#pragma unroll
                for (int i = 0; i < 5; i++) { sts32(dw + 512 * i, cc[i][0]); sts32(dw + 512 * i + 128, cc[i][2]); }
            }
        }
        PC(layer * 32 + 6);
        __syncthreads();
        PROF_T(6 + layer * 16);
        PC(layer * 32 + 7);
        if (tid < 54) {
            const float4 v0 = lds4f(pr), v1 = lds4f(pr + 16), v2 = lds4f(pr + 32);
            const float y0 = (v0.x + v0.y) + (v0.z + v0.w), y1 = (v1.x + v1.y) + (v1.z + v1.w), y2 = (v2.x + v2.y) + (v2.z + v2.w);
            red_pkt(pacc, y0, tid == 53 ? 0.f : y1, tid == 53 ? 0.f : y2);
        }
        if (tid == 224 && layer == 0) {
            misc[1] = __uint_as_float(ticket);
            if (ticket < DN0 + NDN && (ticket < NG || !DNTH)) load_ffn(maps, ticket, sb + SM_B, fbar);
        }
        PROF_T(7 + layer * 16);
        PC(layer * 32 + 8);
        __syncthreads();
        const int role = (int)__float_as_uint(misc[1]);
        PC(layer * 32 + 9);
        const uint32_t fbase = sb + SM_B;
        const uint32_t DONE32 = 0x42000000u;
        if (role < NG) {
            const int tid = opq(threadIdx.x), warp = tid >> 5, lane = tid & 31, g = lane >> 2, t = lane & 3, mat = lane >> 3, r8 = lane & 7;
            const uint32_t ag = fbase + (80 * warp + (mat >> 1) * 8 + r8) * 96 + (((mat & 1) ^ (r8 >> 2)) << 4);
            constexpr int GI = 32, GK = 16 * 96;
            const bool on = (g & 1) == (t >> 1), isx = on && g < 2;
            const uint32_t pm = opq(isx ? sb + SM_XS + 160 * warp + 16 * t : sb + (on ? SM_ONE : SM_ZERO)), pm2 = opq(pm + 128 - (isx ? 8 * t : 0));
            const uint32_t dg = opq(sb + SM_R + 4 * (2 * (warp * 48 + g) + t)), ds = opq(sb + SM_ST + 8 * warp + (lane < 16 ? 4 : 0));
            const bool wr = t < 2, ws = (lane & 15) == 0, lo = lane < 16;
            uint32_t pre[6][4];
            float s1 = 0.f, s2 = 0.f;
            {
                bool hx = wu == 7;
                int it = 0;
                const uint4* px = &g_scr.acc[layer][min(tid, 215) * ACC_STR];
                const int cq = tid / 54, r = tid - 54 * cq, k0 = min(160 * cq + 3 * r, DM - 1);
                const uint32_t w0 = sb + SM_XS + 4 * xpos(k0 >> 1), w1 = sb + SM_XS + 4 * xpos(min((k0 >> 1) + 1, DM / 2 - 1));
                const uint32_t e0 = w0 + 2 * (k0 & 1), e1 = (k0 & 1) ? w1 : w0 + 2, e2 = w1 + 2 * (k0 & 1);
                                auto sts16 = [](uint32_t a, uint32_t x, bool on) {
                    asm volatile("{\n.reg .pred p;\nsetp.ne.u32 p, %2, 0;\n@p st.shared.u16 [%0], %1;\n}" ::"r"(a), "h"((unsigned short)x), "r"((uint32_t)on) : "memory");
                };
                const bool on0 = tid < 216, on1 = on0 && r != 53;
                const float x0 = on0 ? f_(lds16(e0) << 16) : 0.f, x1 = on1 ? f_(lds16(e1) << 16) : 0.f, x2 = on1 ? f_(lds16(e2) << 16) : 0.f;
                auto take_x = [&](const uint4 v) {
                    if (__all_sync(0xffffffffu, v.w == DONE32)) {
                        hx = true;
                        const uint32_t a = pack2(f_(v.x), f_(v.y)), p = pack2(x0 + bf_lo(a), x1 + bf_hi(a)), q = pack2(x2 + bfr(f_(v.z)), 0.f);
                        sts16(e0, p, on0); sts16(e1, p >> 16, on1); sts16(e2, q, on1);
                        const float y0 = on0 ? bf_lo(p) : 0.f, y1 = on0 ? bf_hi(p) : 0.f, y2 = on0 ? bf_lo(q) : 0.f;
                        s1 = y0 + (y1 + y2); s2 = y0 * y0 + (y1 * y1 + y2 * y2);
                    }
                };
                auto try_x = [&]() { take_x(ld_pkt(px)); };
                while (!mbar_test(fbar, 0) && ++it < SPIN_CAP) { if (!hx) try_x(); }
                uint4 v0 = make_uint4(0u, 0u, 0u, 0u);
                if ((PRE1 & 4) && !hx) v0 = ld_pkt(px);
#pragma unroll
                for (int n = 0; n < 6; n++) ldsm4t(ag + (n % 3) * GI + (n / 3) * GK, pre[n]);
                if ((PRE1 & 1) && layer) {
#pragma unroll
                    for (int n = 6; n < 15; n++) ldsm4t(ag + (n % 3) * GI + (n / 3) * GK, kq[n - 6]);
                }
                if ((PRE1 & 4) && !hx) take_x(v0);
                PC(layer * 32 + 10);
                while (!hx && ++it < SPIN_CAP) try_x();
                PC(layer * 32 + 11);
            __syncthreads();
            PC(layer * 32 + 12);
            PROF_T(9 + layer * 16);
            float sv = lo ? s1 : s2, cc[3][4];
            if ((PRE1 & 1) && layer) gemv15r(cc, pre, kq, pm, pm2, sv, lo ? s2 : s1);
            else gemv15<GK>(cc, pre, [&](int i) { return ag + i * GI; }, pm, pm2, sv, lo ? s2 : s1);
            if (wr) {
#pragma unroll
                for (int i = 0; i < 3; i++) { sts32(dg + 128 * i, cc[i][0] + cc[i][3]); sts32(dg + 128 * i + 64, cc[i][1] + cc[i][2]); }
            }
            if (ws) sts32(ds, sv);
            const uint32_t pg = opq(sb + SM_R + 8 * (24 * warp + (lane < 24 ? lane : 0))), st = opq(sb + SM_ST);
            uint4* const ph = opq(lane < 24 && lane % 6 == 0 ? &g_scr.ah[role * 8 + 4 * warp + lane / 6] : nullptr);
            PC(layer * 32 + 13);
            __syncthreads();
            PC(layer * 32 + 14);
            PROF_T(43 + layer * 16);
            if (wu < 2) {
                float mean, inv;
                ln_stats(st, mean, inv);
                float2 v[8];
#pragma unroll
                for (int w = 0; w < 8; w++) v[w] = lds2f(pg + w * 384);
                const float gx = ((v[0].x + v[1].x) + (v[2].x + v[3].x)) + ((v[4].x + v[5].x) + (v[6].x + v[7].x));
                const float gs = ((v[0].y + v[1].y) + (v[2].y + v[3].y)) + ((v[4].y + v[5].y) + (v[6].y + v[7].y));
                float ga = inv * (gx - mean * gs);
                if (role < NG / 2) { ga = bfr(ga); ga *= rcp(1.0f + ex2(-1.4426950408889634f * ga)); }
                const uint32_t wd = pack2(ga, __shfl_down_sync(0xffffffffu, ga, 1));
                const uint32_t wa = __shfl_down_sync(0xffffffffu, wd, 2), wb = __shfl_down_sync(0xffffffffu, wd, 4);
                if (ph) st_pkt(ph, wd, wa, wb, tag);
            }
            if (HOLD & 2) __syncthreads();
            }
            PROF_T(10 + layer * 16);
            PC(layer * 32 + 15);
        } else if (role < DN0 + NDN) {
            const int j = role - DN0;
            const int tid = opq(threadIdx.x), warp = tid >> 5, lane = tid & 31, g = lane >> 2, t = lane & 3, mat = lane >> 3, r8 = lane & 7;
            float xres = 0.f;
            uint32_t xr0 = 0, xr1 = 0;
            if (wu == 0) {
                const int col = 16 * j + (lane & 15), cc = col / 160, r = col - 160 * cc, e = r % 3;
                const uint4* px = &g_scr.acc[layer][(54 * cc + r / 3) * ACC_STR];
                const float x0 = __bfloat162float(reinterpret_cast<const __nv_bfloat16*>(xs32)[2 * xpos(col >> 1) + (col & 1)]);
                uint4 v;
                int it = 0;
                bool ld = DNTH && layer == 0;
                do {
                    v = ld_pkt(px);
                    if (ld && f_(__shfl_sync(0xffffffffu, v.w, 0)) >= (float)DNTH) { ld = false; if (lane == 0) load_ffn(maps, role, sb + SM_B, fbar); }
                } while (!__all_sync(0xffffffffu, v.w == DONE32) && ++it < SPIN_CAP);
                if (ld && lane == 0) load_ffn(maps, role, sb + SM_B, fbar);
                xres = x0 + bfr(f_(e == 0 ? v.x : (e == 1 ? v.y : v.z)));
                const int p4 = 4 * (lane & 3);
                xr0 = pack2(__shfl_sync(0xffffffffu, xres, p4), __shfl_sync(0xffffffffu, xres, p4 + 1));
                xr1 = pack2(__shfl_sync(0xffffffffu, xres, p4 + 2), __shfl_sync(0xffffffffu, xres, p4 + 3));
            }
            PC(layer * 32 + 17);
            PROF_T(9 + layer * 16);
            const uint32_t ad = fbase + (192 * warp + (mat >> 1) * 8 + r8) * 32 + (((mat & 1) ^ (r8 >> 2)) << 4);
            uint32_t* hs = reinterpret_cast<uint32_t*>(rr) + warp * 96;
            uint32_t pre[NPRE][4];
            {
                uint32_t pos[3];
#pragma unroll
                for (int i = 0; i < 3; i++) { const int w = 3 * lane + i; pos[i] = pin(sb + SM_R + 384 * warp + 4 * ((w & ~15) + 4 * (w & 3) + ((w >> 2) & 1) + ((w >> 2) & 2))); }
                uint4 v = make_uint4(0u, 0u, 0u, 0u), u = v;
                if (layer == 0) { v = ld_pkt(&g_scr.ah[tid]); u = ld_pkt(&g_scr.ah[256 + tid]); }
                mbar_wait(fbar, 0);
#pragma unroll
                for (int n = 0; n < NPRE; n++) ldsm4t(ad + n * 512, pre[n]);
                if ((PRE1 & 2) && layer) {
#pragma unroll
                    for (int n = NPRE; n < 12; n++) ldsm4t(ad + n * 512, kq[12 + n]);
                }
                PC(layer * 32 + 18);
                int it = 0;
                while (!__all_sync(0xffffffffu, v.w == tag && u.w == tag) && ++it < SPIN_CAP) { v = ld_pkt(&g_scr.ah[tid]); u = ld_pkt(&g_scr.ah[256 + tid]); }
                PC(layer * 32 + 19);
                sts32(pos[0], f_(bmul2(v.x, u.x))); sts32(pos[1], f_(bmul2(v.y, u.y))); sts32(pos[2], f_(bmul2(v.z, u.z)));
            __syncwarp();
            PROF_T(11 + layer * 16);
            PC(layer * 32 + 20);
            float ca[4] = {0.f, 0.f, 0.f, 0.f}, cb[4] = {0.f, 0.f, 0.f, 0.f};
            if ((PRE1 & 2) && layer) {
                float cc[4] = {0.f, 0.f, 0.f, 0.f}, cd[4] = {0.f, 0.f, 0.f, 0.f};
#pragma unroll
                for (int jj = 0; jj < 6; jj++) {
                    const uint4 hv = *reinterpret_cast<const uint4*>(hs + 16 * jj + 4 * t);
                    const uint32_t (&f0)[4] = 2 * jj < NPRE ? pre[2 * jj < NPRE ? 2 * jj : 0] : kq[12 + 2 * jj];
                    const uint32_t (&f1)[4] = 2 * jj + 1 < NPRE ? pre[2 * jj + 1 < NPRE ? 2 * jj + 1 : 0] : kq[13 + 2 * jj];
                    if (jj & 1) { mma16816(cc, f0[0], f0[1], f0[2], f0[3], hv.x, hv.y); mma16816(cd, f1[0], f1[1], f1[2], f1[3], hv.z, hv.w); }
                    else { mma16816(ca, f0[0], f0[1], f0[2], f0[3], hv.x, hv.y); mma16816(cb, f1[0], f1[1], f1[2], f1[3], hv.z, hv.w); }
                }
#pragma unroll
                for (int e = 0; e < 4; e++) { ca[e] += cc[e]; cb[e] += cd[e]; }
            } else {
#pragma unroll
                for (int jj = 0; jj < 6; jj++) {
                    const uint4 hv = *reinterpret_cast<const uint4*>(hs + 16 * jj + 4 * t);
                    uint32_t a[4];
                    if (2 * jj < NPRE) { a[0] = pre[2 * jj][0]; a[1] = pre[2 * jj][1]; a[2] = pre[2 * jj][2]; a[3] = pre[2 * jj][3]; }
                    else ldsm4t(ad + 2 * jj * 512, a);
                    mma16816(ca, a[0], a[1], a[2], a[3], hv.x, hv.y);
                    if (2 * jj + 1 < NPRE) { a[0] = pre[2 * jj + 1][0]; a[1] = pre[2 * jj + 1][1]; a[2] = pre[2 * jj + 1][2]; a[3] = pre[2 * jj + 1][3]; }
                    else ldsm4t(ad + (2 * jj + 1) * 512, a);
                    mma16816(cb, a[0], a[1], a[2], a[3], hv.z, hv.w);
                }
            }
            if (t == 0) { rr[768 + warp * 16 + g] = ca[0] + cb[0]; rr[768 + warp * 16 + 8 + g] = ca[2] + cb[2]; }
            const uint32_t pd = opq(sb + SM_R + 3072 + 16 * (lane & 3));
            uint4* const py = opq(&g_scr.ay[j * 4 + lane]);
            uint2* const po = opq(reinterpret_cast<uint2*>(out + 16 * j) + lane);
            PC(layer * 32 + 21);
            __syncthreads();
            PC(layer * 32 + 22);
            if (tid < 4) {
                float4 p[8];
#pragma unroll
                for (int w = 0; w < 8; w++) p[w] = lds4f(pd + 64 * w);
                const uint32_t y0 = pack2(((p[0].x + p[1].x) + (p[2].x + p[3].x)) + ((p[4].x + p[5].x) + (p[6].x + p[7].x)),
                                          ((p[0].y + p[1].y) + (p[2].y + p[3].y)) + ((p[4].y + p[5].y) + (p[6].y + p[7].y)));
                const uint32_t y1 = pack2(((p[0].z + p[1].z) + (p[2].z + p[3].z)) + ((p[4].z + p[5].z) + (p[6].z + p[7].z)),
                                          ((p[0].w + p[1].w) + (p[2].w + p[3].w)) + ((p[4].w + p[5].w) + (p[6].w + p[7].w)));
                uint32_t wd, wn;
                asm("add.rn.bf16x2 %0, %1, %2;" : "=r"(wd) : "r"(xr0), "r"(y0));
                asm("add.rn.bf16x2 %0, %1, %2;" : "=r"(wn) : "r"(xr1), "r"(y1));
                if (layer) asm volatile("st.global.v2.u32 [%0], {%1,%2};" ::"l"(po), "r"(wd), "r"(wn) : "memory");
                st_pkt(py, wd, wn, 0, tag);
            }
            if (HOLD & 1) __syncthreads();
            }
            PROF_T(12 + layer * 16);
            PC(layer * 32 + 23);
        }
    }
}

typedef CUresult (*EncodeFn)(CUtensorMap*, CUtensorMapDataType, cuuint32_t, void*, const cuuint64_t*, const cuuint64_t*, const cuuint32_t*,
                             const cuuint32_t*, CUtensorMapInterleave, CUtensorMapSwizzle, CUtensorMapL2promotion, CUtensorMapFloatOOBfill);

void make_map(EncodeFn enc, CUtensorMap* m, const void* base, int rank, uint64_t d0, uint64_t d1, uint64_t d2, uint64_t s1, uint64_t s2,
              uint32_t b0, uint32_t b1, uint32_t b2, CUtensorMapSwizzle sw, CUtensorMapL2promotion pr = CU_TENSOR_MAP_L2_PROMOTION_NONE) {
    cuuint64_t dims[3] = {d0, d1, d2};
    cuuint64_t strides[2] = {s1, s2};
    cuuint32_t box[3] = {b0, b1, b2};
    cuuint32_t es[3] = {1, 1, 1};
    enc(m, CU_TENSOR_MAP_DATA_TYPE_BFLOAT16, rank, const_cast<void*>(base), dims, strides, box, es, CU_TENSOR_MAP_INTERLEAVE_NONE, sw,
        pr, CU_TENSOR_MAP_FLOAT_OOB_FILL_NONE);
}

}

extern "C" void kernel_launch(void* const* d_in, const int* in_sizes, int n_in, void* d_out, int out_size) {
    (void)in_sizes; (void)n_in; (void)out_size;
    static EncodeFn enc = nullptr;
    if (!enc) {
        void* fn = nullptr;
        cudaDriverEntryPointQueryResult qr;
        cudaGetDriverEntryPoint("cuTensorMapEncodeTiled", &fn, cudaEnableDefault, &qr);
        enc = reinterpret_cast<EncodeFn>(fn);
        cudaFuncSetAttribute(decode_kernel, cudaFuncAttributeMaxDynamicSharedMemorySize, SM_TOTAL);
    }
    Maps maps;
    make_map(enc, &maps.k, d_in[1], 2, 64, (uint64_t)NH * SK * 3, 1, 128, 0, 64, 48, 1, CU_TENSOR_MAP_SWIZZLE_128B);
    make_map(enc, &maps.v, d_in[2], 2, 64, (uint64_t)NH * SK * 3, 1, 128, 0, 64, 48, 1, CU_TENSOR_MAP_SWIZZLE_128B);
    make_map(enc, &maps.wq, d_in[3], 3, 64, DM, NH * DH / 64, NH * DH * 2, 128, 64, 160, 3, CU_TENSOR_MAP_SWIZZLE_128B);
    make_map(enc, &maps.wo, d_in[4], 3, 32, DM / 32, NH * DH, 64, DM * 2, 32, 5, 32, CU_TENSOR_MAP_SWIZZLE_64B);
    make_map(enc, &maps.vr, (const char*)d_in[2] + 512, 2, 128, (uint64_t)NH * SK / 2, 1, 768, 0, 128, 2, 1, CU_TENSOR_MAP_SWIZZLE_NONE);
    constexpr int GW = 48;
    make_map(enc, &maps.w1, d_in[6], 3, FF, 160, 4, FF * 2, 160 * FF * 2, GW, 160, 4, CU_TENSOR_MAP_SWIZZLE_NONE, FFN_PROMO);
    make_map(enc, &maps.w3, d_in[7], 3, FF, 160, 4, FF * 2, 160 * FF * 2, GW, 160, 4, CU_TENSOR_MAP_SWIZZLE_NONE, FFN_PROMO);
    make_map(enc, &maps.w2, d_in[8], 3, DM, 256, 6, DM * 2, 256 * DM * 2, 16, 256, 6, CU_TENSOR_MAP_SWIZZLE_32B, FFN_PROMO);
    maps.vp = d_in[2];
    maps.kp = d_in[1];
    maps.zero = 0;
    decode_kernel<<<NCTA, NT, SM_TOTAL, cudaStreamPerThread>>>(maps, (const __nv_bfloat16*)d_in[0], (__nv_bfloat16*)d_out);
}
```

```cpp
#include <cuda_runtime.h>
#include <cuda_bf16.h>
#include <cuda.h>
#include <stdint.h>
#include <math.h>

namespace {

constexpr int DM = 640;
constexpr int NH = 32;
constexpr int DH = 192;
constexpr int SK = 32768;
constexpr int WIN = 4096;
constexpr int FF = 1536;
constexpr int NCTA = 128;
constexpr int NT = 256;
constexpr int TILE = 6144;
constexpr int NG = 64;
constexpr int DN0 = 64;
constexpr int NDN = 40;

constexpr int SM_RING = 0;
constexpr int SM_B = 8 * 2 * TILE;
constexpr int SM_Q = SM_B + 61440;
__host__ __device__ constexpr int c_slot(int w) { return w < 2 ? 4096 + 10240 * w : 12288 + 6144 * w; }
__host__ __device__ constexpr int v1_pos(int n) { return 10240 * (n >> 3) + 512 * (n & 7); }
constexpr int SM_XS = SM_Q + 61440;
constexpr int SM_R = SM_XS + 1280;
constexpr int SM_ST = SM_R + 4096;
constexpr int SM_QS = SM_R + 6272;
constexpr int SM_OS = SM_QS + 384;
constexpr int SM_BAR = SM_OS + 384;
constexpr int SM_XBAR = SM_BAR + 24 * 8;
constexpr int SM_MISC = SM_XBAR + 8 * 8;
constexpr int SM_ONE = SM_MISC + 16;
constexpr int SM_ZERO = SM_ONE + 160;
constexpr int XCAP = 48;
constexpr int XSTR = 16 + 4 * XCAP;
constexpr int SM_XL = SM_ZERO + 160;
constexpr int SM_TOTAL = SM_XL + 8 * XSTR;
static_assert(SM_TOTAL <= 232448, "shared memory");

constexpr unsigned long long POL_EF = 0x12F0000000000000ull;
constexpr unsigned long long POL_EN = 0x16F0000000000000ull;

#define RT_MASK 0xF2E0u
#define RT_MASK2 0xEAE0u
#define WO_AT1 5
#define FFN_PROMO CU_TENSOR_MAP_L2_PROMOTION_NONE
#define FFN_POL POL_EF
#define HAS_FFN (__float_as_uint(misc[1]) < DN0 + NDN)
#define ACC_STR 1
#define NPRE 6

#define STAG 200
#define L1R 3
#define PRE1 13
#define HOLD 2
#define DNTH 23
constexpr int V0_AT = 8;
constexpr unsigned long long SEQ1 = 0x2765431076543210ull;
constexpr uint32_t IN_S1 = 0xAA49, IN_S0 = 0x124, PARITY1 = 0x6638, PARITY2 = 0xCE;
#define KEEP4 1
constexpr int NQ = 48;
constexpr int SPIN_CAP = 1 << 19;
constexpr uint32_t ONES = 0x3F803F80u;

struct alignas(1024) Scratch {
    uint4 hx[NCTA * 48];
    uint4 pad0[32 * 5 * 32 + 160];
    uint4 acc[2][216 * 8];
    uint4 ay[160];
    uint4 ah[NG * 8];
    uint2 mx[NH * 32];
    uint32_t ticket[32];
    uint32_t pad1[32];
};
__device__ Scratch g_scr;
#define PROF_T(i)
#define PROF_X(i)
#define PC(i)

__device__ __forceinline__ uint32_t smem_u32(const void* p) { return (uint32_t)__cvta_generic_to_shared(p); }
__device__ __forceinline__ void mbar_init(uint32_t bar, uint32_t cnt) {
    asm volatile("mbarrier.init.shared::cta.b64 [%0], %1;" ::"r"(bar), "r"(cnt) : "memory");
}
__device__ __forceinline__ void mbar_expect_tx(uint32_t bar, uint32_t bytes) {
    asm volatile("mbarrier.arrive.expect_tx.shared::cta.b64 _, [%0], %1;" ::"r"(bar), "r"(bytes) : "memory");
}
__device__ __forceinline__ bool mbar_test(uint32_t bar, uint32_t parity) {
    uint32_t done;
    asm volatile("{\n.reg .pred p;\nmbarrier.try_wait.parity.shared::cta.b64 p, [%1], %2;\nselp.u32 %0, 1, 0, p;\n}"
                 : "=r"(done) : "r"(bar), "r"(parity) : "memory");
    return done;
}
__device__ __forceinline__ void mbar_wait(uint32_t bar, uint32_t parity) {
    int it = 0;
    while (!mbar_test(bar, parity) && ++it < SPIN_CAP) {}
}
__device__ __forceinline__ void tma2d(uint32_t dst, const CUtensorMap* map, int c0, int c1, uint32_t bar, unsigned long long pol) {
    asm volatile("cp.async.bulk.tensor.2d.shared::cluster.global.mbarrier::complete_tx::bytes.L2::cache_hint [%0], [%1, {%3, %4}], [%2], %5;"
                 ::"r"(dst), "l"(map), "r"(bar), "r"(c0), "r"(c1), "l"(pol) : "memory");
}
__device__ __forceinline__ void tma3d(uint32_t dst, const CUtensorMap* map, int c0, int c1, int c2, uint32_t bar, unsigned long long pol) {
    asm volatile("cp.async.bulk.tensor.3d.shared::cluster.global.mbarrier::complete_tx::bytes.L2::cache_hint [%0], [%1, {%3, %4, %5}], [%2], %6;"
                 ::"r"(dst), "l"(map), "r"(bar), "r"(c0), "r"(c1), "r"(c2), "l"(pol) : "memory");
}
__device__ __forceinline__ void tile_load(uint32_t dst, const CUtensorMap* map, int row, uint32_t bar, uint32_t dep, uint32_t zero) {
    asm volatile("{\n.reg .pred p;\n.reg .b32 n;\nmad.lo.u32 n, %5, %6, 6144;\nelect.sync _|p, 0xffffffff;\n"
                 "@p mbarrier.arrive.expect_tx.shared::cta.b64 _, [%2], n;\n"
                 "@p cp.async.bulk.tensor.2d.shared::cluster.global.mbarrier::complete_tx::bytes.L2::cache_hint [%0], [%1, {0, %3}], [%2], %4;\n}"
                 ::"r"(dst), "l"(map), "r"(bar), "r"(row), "l"(POL_EF), "r"(dep), "r"(zero) : "memory");
}
__device__ __forceinline__ void tile_keep(const CUtensorMap* map, int row) {
    asm volatile("{\n.reg .pred p;\nelect.sync _|p, 0xffffffff;\n"
                 "@p cp.async.bulk.prefetch.tensor.2d.L2.global.L2::cache_hint [%0, {0, %1}], %2;\n}"
                 ::"l"(map), "r"(row), "l"(POL_EN) : "memory");
}
__device__ __forceinline__ void tile_load_l1(uint32_t dst, const void* base, int row, uint32_t bar, int lane) {
    const char* g = static_cast<const char*>(base) + (size_t)row * 128 + lane * 16;
    const uint32_t s0 = dst + (lane >> 3) * 128 + (((lane & 7) ^ (lane >> 3)) << 4), s1 = s0 ^ 64;
#pragma unroll
    for (int k = 0; k < 12; k++)
        asm volatile("cp.async.ca.shared.global.L2::cache_hint [%0], [%1], 16, %2;" ::"r"(((k & 1) ? s1 : s0) + k * 512), "l"(g + k * 512), "l"(POL_EF) : "memory");
    asm volatile("cp.async.mbarrier.arrive.shared::cta.b64 [%0];" ::"r"(bar) : "memory");
    __syncwarp();
    if (lane == 0) asm volatile("mbarrier.arrive.shared::cta.b64 _, [%0];" ::"r"(bar) : "memory");
}
__device__ __forceinline__ bool elect_one() {
    uint32_t p;
    asm volatile("{\n.reg .pred p;\nelect.sync _|p, 0xffffffff;\nselp.u32 %0, 1, 0, p;\n}" : "=r"(p));
    return p;
}
__device__ __forceinline__ void lds128(uint32_t addr, uint32_t& a, uint32_t& b, uint32_t& c, uint32_t& d) {
    asm volatile("ld.shared.v4.u32 {%0,%1,%2,%3}, [%4];" : "=r"(a), "=r"(b), "=r"(c), "=r"(d) : "r"(addr) : "memory");
}
__device__ __forceinline__ void lds128p(uint32_t addr, uint32_t on, uint32_t& a, uint32_t& b, uint32_t& c, uint32_t& d) {
    asm volatile("{\n.reg .pred p;\nsetp.ne.u32 p, %5, 0;\n@p ld.shared.v4.u32 {%0,%1,%2,%3}, [%4];\n}" : "+r"(a), "+r"(b), "+r"(c), "+r"(d) : "r"(addr), "r"(on) : "memory");
}
__device__ __forceinline__ void lds64(uint32_t addr, uint32_t& a, uint32_t& b) {
    asm volatile("ld.shared.v2.u32 {%0,%1}, [%2];" : "=r"(a), "=r"(b) : "r"(addr) : "memory");
}
__device__ __forceinline__ void ldsm4t(uint32_t addr, uint32_t (&a)[4]) {
    asm volatile("ldmatrix.sync.aligned.m8n8.x4.trans.shared.b16 {%0,%1,%2,%3}, [%4];" : "=r"(a[0]), "=r"(a[1]), "=r"(a[2]), "=r"(a[3]) : "r"(addr) : "memory");
}
__device__ __forceinline__ void mma16816(float (&c)[4], uint32_t a0, uint32_t a1, uint32_t a2, uint32_t a3, uint32_t b0, uint32_t b1) {
    asm("mma.sync.aligned.m16n8k16.row.col.f32.bf16.bf16.f32 {%0,%1,%2,%3}, {%4,%5,%6,%7}, {%8,%9}, {%0,%1,%2,%3};"
        : "+f"(c[0]), "+f"(c[1]), "+f"(c[2]), "+f"(c[3]) : "r"(a0), "r"(a1), "r"(a2), "r"(a3), "r"(b0), "r"(b1));
}
__device__ __forceinline__ void mma16816v(float (&c)[4], uint32_t a0, uint32_t a1, uint32_t a2, uint32_t a3, uint32_t b0, uint32_t b1) {
    asm volatile("mma.sync.aligned.m16n8k16.row.col.f32.bf16.bf16.f32 {%0,%1,%2,%3}, {%4,%5,%6,%7}, {%8,%9}, {%0,%1,%2,%3};"
        : "+f"(c[0]), "+f"(c[1]), "+f"(c[2]), "+f"(c[3]) : "r"(a0), "r"(a1), "r"(a2), "r"(a3), "r"(b0), "r"(b1));
}
__device__ __forceinline__ int xpos(int w) {
    const int seg = w / 40, r = w - 40 * seg;
    return 40 * seg + (r < 32 ? (r & 16) + 4 * (r & 3) + ((r >> 2) & 3) : 32 + 2 * (r & 3) + ((r >> 2) & 1));
}
#define NA_LD ""
#define NA_ST ""
__device__ __forceinline__ void st_pkt(uint4* p, uint32_t a, uint32_t b, uint32_t c, uint32_t d) {
    asm volatile("{\n.reg .b128 t;\n.reg .b64 lo, hi;\nmov.b64 lo, {%1,%2};\nmov.b64 hi, {%3,%4};\nmov.b128 t, {lo,hi};\nst.relaxed.gpu.global" NA_ST ".b128 [%0], t;\n}"
                 ::"l"(p), "r"(a), "r"(b), "r"(c), "r"(d) : "memory");
}
__device__ __forceinline__ void st_pktf(uint4* p, float a, float b, float c, float d, uint32_t bit) {
    st_pkt(p, __float_as_uint(a), __float_as_uint(b), __float_as_uint(c), (__float_as_uint(d) & ~1u) | bit);
}
__device__ __forceinline__ void red_pkt(uint4* p, float a, float b, float c) {
    asm volatile("red.relaxed.gpu.global.add.v4.f32 [%0], {%1,%2,%3,%4};" ::"l"(p), "f"(a), "f"(b), "f"(c), "f"(1.0f) : "memory");
}
__device__ __forceinline__ void st_pktp(uint4* p, uint32_t a, uint32_t b, uint32_t c, uint32_t d, bool on) {
    asm volatile("{\n.reg .pred p;\n.reg .b128 t;\n.reg .b64 lo, hi;\nsetp.ne.u32 p, %5, 0;\nmov.b64 lo, {%1,%2};\nmov.b64 hi, {%3,%4};\nmov.b128 t, {lo,hi};\n"
                 "@p st.relaxed.gpu.global.b128 [%0], t;\n}" ::"l"(p), "r"(a), "r"(b), "r"(c), "r"(d), "r"((uint32_t)on) : "memory");
}
__device__ __forceinline__ void st_pktfp(uint4* p, float a, float b, float c, float d, uint32_t bit, bool on) {
    st_pktp(p, __float_as_uint(a), __float_as_uint(b), __float_as_uint(c), (__float_as_uint(d) & ~1u) | bit, on);
}
__device__ __forceinline__ uint4 ld_pkt(const uint4* p) {
    uint4 v;
    asm volatile("{\n.reg .b128 t;\n.reg .b64 lo, hi;\nld.relaxed.gpu.global" NA_LD ".b128 t, [%4];\nmov.b128 {lo,hi}, t;\nmov.b64 {%0,%1}, lo;\nmov.b64 {%2,%3}, hi;\n}"
                 : "=r"(v.x), "=r"(v.y), "=r"(v.z), "=r"(v.w) : "l"(p) : "memory");
    return v;
}
__device__ __forceinline__ uint2 ld_pkt2(const uint2* p) {
    unsigned long long v;
    asm volatile("ld.relaxed.gpu.global" NA_LD ".b64 %0, [%1];" : "=l"(v) : "l"(p) : "memory");
    return make_uint2((uint32_t)v, (uint32_t)(v >> 32));
}
__device__ __forceinline__ void st_pkt2(uint2* p, uint32_t a, uint32_t b) {
    asm volatile("st.relaxed.gpu.global" NA_ST ".b64 [%0], %1;" ::"l"(p), "l"((unsigned long long)a | ((unsigned long long)b << 32)) : "memory");
}
__device__ __forceinline__ float ex2(float x) { float y; asm("ex2.approx.ftz.f32 %0, %1;" : "=f"(y) : "f"(x)); return y; }
__device__ __forceinline__ float rcp(float x) { float y; asm("rcp.approx.ftz.f32 %0, %1;" : "=f"(y) : "f"(x)); return y; }
__device__ __forceinline__ uint32_t pack2(float lo, float hi) {
    uint32_t r; asm("cvt.rn.bf16x2.f32 %0, %1, %2;" : "=r"(r) : "f"(hi), "f"(lo)); return r;
}
__device__ __forceinline__ float bf_lo(uint32_t w) { return __uint_as_float(w << 16); }
__device__ __forceinline__ float bf_hi(uint32_t w) { return __uint_as_float(w & 0xffff0000u); }
__device__ __forceinline__ float bfr(float x) { return bf_lo(pack2(x, 0.f)); }
__device__ __forceinline__ float f_(uint32_t u) { return __uint_as_float(u); }

template <int SK, typename AddrF>
__device__ __forceinline__ void gemv15(float (&cc)[3][4], uint32_t (&pre)[6][4], AddrF ad, uint32_t px, uint32_t px2, float& sv, float so) {
    uint32_t x0[4], x1[4], a[3][4];
    asm volatile("ld.shared.v4.u32 {%0,%1,%2,%3}, [%20];\nld.shared.v4.u32 {%4,%5,%6,%7}, [%20+64];\n"
                 "ldmatrix.sync.aligned.m8n8.x4.trans.shared.b16 {%8,%9,%10,%11}, [%21];\n"
                 "ldmatrix.sync.aligned.m8n8.x4.trans.shared.b16 {%12,%13,%14,%15}, [%22];\n"
                 "ldmatrix.sync.aligned.m8n8.x4.trans.shared.b16 {%16,%17,%18,%19}, [%23];\nbar.warp.sync 0xffffffff;"
                 : "=r"(x0[0]), "=r"(x0[1]), "=r"(x0[2]), "=r"(x0[3]), "=r"(x1[0]), "=r"(x1[1]), "=r"(x1[2]), "=r"(x1[3]),
                   "=r"(a[0][0]), "=r"(a[0][1]), "=r"(a[0][2]), "=r"(a[0][3]), "=r"(a[1][0]), "=r"(a[1][1]), "=r"(a[1][2]), "=r"(a[1][3]),
                   "=r"(a[2][0]), "=r"(a[2][1]), "=r"(a[2][2]), "=r"(a[2][3])
                 : "r"(px), "r"(ad(0) + 2 * SK), "r"(ad(1) + 2 * SK), "r"(ad(2) + 2 * SK) : "memory");
    __syncwarp();
    sv += __shfl_xor_sync(0xffffffffu, so, 16);
#pragma unroll
    for (int i = 0; i < 3; i++) {
        cc[i][0] = cc[i][1] = cc[i][2] = cc[i][3] = 0.f;
        mma16816v(cc[i], pre[i][0], pre[i][1], pre[i][2], pre[i][3], x0[0], x0[1]);
    }
    sv += __shfl_xor_sync(0xffffffffu, sv, 8);
#pragma unroll
    for (int i = 0; i < 3; i++) {
        mma16816v(cc[i], pre[3 + i][0], pre[3 + i][1], pre[3 + i][2], pre[3 + i][3], x0[2], x0[3]);
        ldsm4t(ad(i) + 3 * SK, pre[i]);
    }
    lds64(px2, x0[0], x0[1]);
    __syncwarp();
    sv += __shfl_xor_sync(0xffffffffu, sv, 4);
#pragma unroll
    for (int i = 0; i < 3; i++) {
        mma16816v(cc[i], a[i][0], a[i][1], a[i][2], a[i][3], x1[0], x1[1]);
        ldsm4t(ad(i) + 4 * SK, pre[3 + i]);
    }
    __syncwarp();
    sv += __shfl_xor_sync(0xffffffffu, sv, 2);
#pragma unroll
    for (int i = 0; i < 3; i++) mma16816v(cc[i], pre[i][0], pre[i][1], pre[i][2], pre[i][3], x1[2], x1[3]);
    sv += __shfl_xor_sync(0xffffffffu, sv, 1);
#pragma unroll
    for (int i = 0; i < 3; i++) mma16816v(cc[i], pre[3 + i][0], pre[3 + i][1], pre[3 + i][2], pre[3 + i][3], x0[0], x0[1]);
}
__device__ __forceinline__ void gemv15r(float (&cc)[3][4], const uint32_t (&pre)[6][4], const uint32_t (&ext)[NQ][4], uint32_t px, uint32_t px2, float& sv, float so) {
    uint32_t x0[4], x1[4], x2[2];
    float cd[3][4];
    lds128(px, x0[0], x0[1], x0[2], x0[3]);
    lds128(px + 64, x1[0], x1[1], x1[2], x1[3]);
    lds64(px2, x2[0], x2[1]);
    sv += __shfl_xor_sync(0xffffffffu, so, 16);
#pragma unroll
    for (int i = 0; i < 3; i++) {
        cc[i][0] = cc[i][1] = cc[i][2] = cc[i][3] = cd[i][0] = cd[i][1] = cd[i][2] = cd[i][3] = 0.f;
        mma16816v(cc[i], pre[i][0], pre[i][1], pre[i][2], pre[i][3], x0[0], x0[1]);
        mma16816v(cd[i], pre[3 + i][0], pre[3 + i][1], pre[3 + i][2], pre[3 + i][3], x0[2], x0[3]);
    }
    sv += __shfl_xor_sync(0xffffffffu, sv, 8);
#pragma unroll
    for (int i = 0; i < 3; i++) {
        mma16816v(cc[i], ext[i][0], ext[i][1], ext[i][2], ext[i][3], x1[0], x1[1]);
        mma16816v(cd[i], ext[3 + i][0], ext[3 + i][1], ext[3 + i][2], ext[3 + i][3], x1[2], x1[3]);
    }
    sv += __shfl_xor_sync(0xffffffffu, sv, 4);
#pragma unroll
    for (int i = 0; i < 3; i++) mma16816v(cc[i], ext[6 + i][0], ext[6 + i][1], ext[6 + i][2], ext[6 + i][3], x2[0], x2[1]);
    sv += __shfl_xor_sync(0xffffffffu, sv, 2);
    sv += __shfl_xor_sync(0xffffffffu, sv, 1);
#pragma unroll
    for (int i = 0; i < 3; i++) { cc[i][0] += cd[i][0]; cc[i][1] += cd[i][1]; cc[i][2] += cd[i][2]; cc[i][3] += cd[i][3]; }
}

__device__ __forceinline__ float warp_max(float x) {
    int i = __float_as_int(x);
    i = __reduce_max_sync(0xffffffffu, i ^ ((i >> 31) & 0x7fffffff));
    return __int_as_float(i ^ ((i >> 31) & 0x7fffffff));
}
__device__ __forceinline__ void idle(uint32_t clk) {
    uint32_t t0, t;
    asm volatile("mov.u32 %0, %%clock;" : "=r"(t0) :: "memory");
    do asm volatile("mov.u32 %0, %%clock;" : "=r"(t) :: "memory"); while (t - t0 < clk);
}
__device__ __forceinline__ uint32_t now_ns() { uint32_t t; asm volatile("mov.u32 %0, %%globaltimer_lo;" : "=r"(t)); return t; }
__device__ __forceinline__ int opq(int x) { asm volatile("" : "+r"(x)); return x; }
__device__ __forceinline__ uint32_t opq(uint32_t x) { asm volatile("" : "+r"(x)); return x; }
__device__ __forceinline__ uint32_t pin(uint32_t x) { return __shfl_sync(0xffffffffu, x, threadIdx.x & 31); }
template <typename T> __device__ __forceinline__ T* pin(T* p) {
    const unsigned long long v = (unsigned long long)p;
    return (T*)((unsigned long long)pin((uint32_t)v) | (unsigned long long)pin((uint32_t)(v >> 32)) << 32);
}
template <typename T> __device__ __forceinline__ T* opq(T* p) { asm volatile("" : "+l"(p)); return p; }
__device__ __forceinline__ float4 lds4f(uint32_t a) { float4 v; asm volatile("ld.shared.v4.f32 {%0,%1,%2,%3}, [%4];" : "=f"(v.x), "=f"(v.y), "=f"(v.z), "=f"(v.w) : "r"(a) : "memory"); return v; }
__device__ __forceinline__ float2 lds2f(uint32_t a) { float2 v; asm volatile("ld.shared.v2.f32 {%0,%1}, [%2];" : "=f"(v.x), "=f"(v.y) : "r"(a) : "memory"); return v; }
__device__ __forceinline__ void ln_stats(uint32_t st, float& mean, float& inv) {
    const float4 a = lds4f(st), b = lds4f(st + 16), c = lds4f(st + 32), d = lds4f(st + 48);
    const float s2 = ((a.x + a.z) + (b.x + b.z)) + ((c.x + c.z) + (d.x + d.z));
    const float md = (((a.y + a.w) + (b.y + b.w)) + ((c.y + c.w) + (d.y + d.w))) * (1.0f / DM);
    const float var = fmaxf(s2 * (1.0f / DM) - md * md, 0.f);
    mean = bfr(md);
    asm("rsqrt.approx.ftz.f32 %0, %1;" : "=f"(inv) : "f"(var + 1e-5f));
}
__device__ __forceinline__ void sts32(uint32_t a, float v) { asm volatile("st.shared.f32 [%0], %1;" ::"r"(a), "f"(v) : "memory"); }
__device__ __forceinline__ void sts32p(uint32_t a, float v, uint32_t off) {
    asm volatile("{\n.reg .pred p;\nsetp.eq.u32 p, %2, 0;\n@p st.shared.f32 [%0], %1;\n}" ::"r"(a), "f"(v), "r"(off) : "memory");
}
__device__ __forceinline__ void sts128p(uint32_t a, float x, float y, float z, float w, uint32_t off) {
    asm volatile("{\n.reg .pred p;\nsetp.eq.u32 p, %5, 0;\n@p st.shared.v4.f32 [%0], {%1,%2,%3,%4};\n}" ::"r"(a), "f"(x), "f"(y), "f"(z), "f"(w), "r"(off) : "memory");
}
__device__ __forceinline__ void sts64(uint32_t a, float v, float w) { asm volatile("st.shared.v2.f32 [%0], {%1,%2};" ::"r"(a), "f"(v), "f"(w) : "memory"); }

__device__ __forceinline__ uint32_t prmt(uint32_t a, uint32_t b, uint32_t s) { uint32_t r; asm("prmt.b32 %0, %1, %2, %3;" : "=r"(r) : "r"(a), "r"(b), "r"(s)); return r; }
__device__ __forceinline__ uint32_t bmul2(uint32_t a, uint32_t b) { uint32_t r; asm("mul.rn.bf16x2 %0, %1, %2;" : "=r"(r) : "r"(a), "r"(b)); return r; }
__device__ __forceinline__ void sts128(uint32_t addr, uint32_t a, uint32_t b, uint32_t c, uint32_t d) {
    asm volatile("st.shared.v4.u32 [%0], {%1,%2,%3,%4};" ::"r"(addr), "r"(a), "r"(b), "r"(c), "r"(d) : "memory");
}
__device__ __forceinline__ uint4 ldg128(const uint4* p) {
    uint4 v;
    asm volatile("ld.volatile.global.v4.u32 {%0,%1,%2,%3}, [%4];" : "=r"(v.x), "=r"(v.y), "=r"(v.z), "=r"(v.w) : "l"(p) : "memory");
    return v;
}
__device__ __forceinline__ uint32_t lds32(uint32_t a) { uint32_t v; asm volatile("ld.shared.u32 %0, [%1];" : "=r"(v) : "r"(a) : "memory"); return v; }
__device__ __forceinline__ uint32_t lds16(uint32_t a) { unsigned short v; asm volatile("ld.shared.u16 %0, [%1];" : "=h"(v) : "r"(a) : "memory"); return v; }
__device__ __forceinline__ void unpack8(uint32_t la, uint32_t lb, uint32_t c, uint32_t (&w)[4]) {
    const uint32_t ha = c & 0x87878787u, hb = __funnelshift_l(c, c, 4) & 0x87878787u;
    w[0] = prmt(la, ha, 0x5140); w[1] = prmt(la, ha, 0x7362); w[2] = prmt(lb, hb, 0x5140); w[3] = prmt(lb, hb, 0x7362);
}
__device__ __forceinline__ uint32_t bdiff2(uint32_t y, uint32_t inv, uint32_t x) {
    uint32_t r;
    asm("{\n.reg .b32 n;\nneg.bf16x2 n, %3;\nfma.rn.bf16x2 %0, %1, %2, n;\n}" : "=r"(r) : "r"(y), "r"(inv), "r"(x));
    return r;
}
__device__ __forceinline__ uint32_t pack_scale(uint32_t tile, int lane, uint32_t inv_addr) {
    uint32_t m = 0;
#pragma unroll 1
    for (int k = 0; k < 12; k++) {
        uint32_t a, b, c, d;
        lds128(tile + k * 512 + lane * 16, a, b, c, d);
        asm("max.xorsign.abs.bf16x2 %0, %0, %1;" : "+r"(a) : "r"(b));
        asm("max.xorsign.abs.bf16x2 %0, %0, %1;" : "+r"(c) : "r"(d));
        asm("max.xorsign.abs.bf16x2 %0, %0, %1;" : "+r"(a) : "r"(c));
        asm("max.xorsign.abs.bf16x2 %0, %0, %1;" : "+r"(m) : "r"(a));
    }
    m = __reduce_max_sync(0xffffffffu, max(m & 0x7fffu, (m >> 16) & 0x7fffu));
    const uint32_t inv = (112u + min((m + 0x28u) >> 7, 141u)) * 0x00800080u;
    if (lane == 0) asm volatile("st.shared.u32 [%0], %1;" ::"r"(inv_addr), "r"(inv) : "memory");
    return inv;
}

#define K_OFF(i) ((uint32_t)((3 * ((g >> 1) + 4 * (g & 1)) + ((i) >> 1)) * 128 + ((t ^ ((3 * ((g >> 1) + 4 * (g & 1)) + ((i) >> 1)) & 7) ^ (((i) & 1) << 2)) << 4)))
#define V_OFF(i) ((uint32_t)((6 * t + (i)) * 128 + ((g ^ ((6 * t + (i)) & 7)) << 4)))
template <bool ISV, typename DST>
__device__ __forceinline__ void pack_tile(uint32_t tile, int tau, int nm, uint32_t inv, uint32_t xl, int lane, DST dst) {
    const int g = lane >> 2, t = lane & 3;
    const uint32_t scl = 254u * 0x00800080u - inv;
#pragma unroll 1
    for (int m = 0; m < nm; m++) {
        const int row = ISV ? 6 * t + 2 * m : 3 * ((g >> 1) + 4 * (g & 1)) + m;
        const uint32_t a0 = tile + row * 128 + (((ISV ? g : t) ^ (row & 7)) << 4), a1 = ISV ? (a0 ^ 16) + 128 : a0 ^ 64;
        uint32_t l[8], cw[4], ck = 0, cd = 0;
#pragma unroll
        for (int r = 0; r < 4; r++) {
            uint32_t w0, w1, w2, w3;
            lds128(((r & 1) ? a1 : a0) + (r >> 1) * 3072, w0, w1, w2, w3);
            const uint32_t y0 = bmul2(w0, scl), y1 = bmul2(w1, scl), y2 = bmul2(w2, scl), y3 = bmul2(w3, scl);
            cd |= bdiff2(y0, inv, w0) | bdiff2(y1, inv, w1);
            cd |= bdiff2(y2, inv, w2) | bdiff2(y3, inv, w3);
            const uint32_t ha = prmt(y0, y1, 0x7531), hb = prmt(y2, y3, 0x7531);
            l[2 * r] = prmt(y0, y1, 0x6420); l[2 * r + 1] = prmt(y2, y3, 0x6420);
            asm("lop3.b32 %0, %1, 0x87878787, %2, 0xe2;" : "=r"(cw[r]) : "r"(ha), "r"(__funnelshift_r(hb, hb, 4)));
            ck |= ha | hb;
        }
        const uint32_t bad = __ballot_sync(0xffffffffu, (ck & 0x78787878u) | cd);
        if (bad) {
            const int src = __ffs(bad) - 1;
            const uint32_t b0 = __shfl_sync(0xffffffffu, a0, src), b1 = __shfl_sync(0xffffffffu, a1, src), n0 = lds32(xl);
            const uint32_t ax = ((lane & 8) ? b1 : b0) + (lane >> 4) * 3072 + 2 * (lane & 7), x = lds16(ax), y = bmul2(x, scl);
            const bool out = (y & 0x7800u) | bdiff2(y, inv, x);
            const uint32_t n = n0 + __popc(__ballot_sync(0xffffffffu, out) << (31 - lane)) - 1;
            if (out) {
                asm volatile("st.shared.u16 [%0], %1;" ::"r"(ax), "h"((unsigned short)0) : "memory");
                if (n < XCAP) sts32(xl + 16 + 4 * n, f_(x << 16 | tau << 12 | src << 7 | m << 5 | lane));
            }
            if (lane == 31) sts32(xl, f_(n + 1));
            __syncwarp();
            if (n0 <= XCAP) { m--; continue; }
        }
        uint32_t d[3] = {a0, a1, a0 + 3072};
        dst(m, d);
        sts128(d[0], l[0], l[1], l[2], l[3]);
        sts128(d[1], l[4], l[5], l[6], l[7]);
        sts128(d[2], cw[0], cw[1], cw[2], cw[3]);
    }
}

struct Maps { CUtensorMap k, v, wq, wo, w1, w3, w2, vr; const void* vp; const void* kp; uint32_t zero; };
#define RT_SEL ((wu & 1) ? RT_MASK2 : RT_MASK)
#define PFK 5
#define Q_AT 3
#define WO_T0 32200
#define K5D 370
#define PK_AT 6

__device__ __forceinline__ void load_ffn(const Maps& maps, int b, uint32_t dst, uint32_t bar) {
    const bool gu = b < NG;
    mbar_expect_tx(bar, gu ? 61440 : 49152);
    tma3d(dst, gu ? (b < NG / 2 ? &maps.w1 : &maps.w3) : &maps.w2, gu ? 48 * (b & (NG / 2 - 1)) : 16 * (b - DN0), 0, 0, bar, FFN_POL);
}

__device__ __forceinline__ void load_wo(const Maps& maps, uint32_t dst, int h, int c, uint32_t bar, int nbox) {
#pragma unroll 1
    for (int i = 0; i < nbox; i++) {
        if (!(i & 1)) mbar_expect_tx(bar + 4 * i, i + 1 < nbox ? 20480 : 10240);
        tma3d(dst + i * 10240, &maps.wo, 0, 5 * c, h * DH + 32 * i, bar + 4 * (i & 6), POL_EF);
    }
}

__global__ void __launch_bounds__(NT, 1)
decode_kernel(const __grid_constant__ Maps maps, const __nv_bfloat16* __restrict__ x_in, __nv_bfloat16* __restrict__ out) {
    extern __shared__ __align__(1024) unsigned char smem[];
    const int tid = threadIdx.x, warp = tid >> 5, lane = tid & 31;
    const int wu = __shfl_sync(0xffffffffu, tid >> 5, 0);
    const int b = blockIdx.x, h = b >> 2, c = b & 3;
    const uint32_t sb = smem_u32(smem);
    const uint32_t qbar = sb + SM_BAR + 16 * 8, fbar = qbar + 8, wbar = qbar + 16;
    uint32_t* xs32 = reinterpret_cast<uint32_t*>(smem + SM_XS);
    float* rr = reinterpret_cast<float*>(smem + SM_R);
    float* misc = reinterpret_cast<float*>(smem + SM_MISC);

    PROF_T(0);
    {
        uint2 xv = make_uint2(0u, 0u);
        const uint32_t t_start = now_ns();
        if (elect_one()) {
            const uint32_t rb = sb + SM_BAR + wu * 16, xb = sb + SM_XBAR + wu * 8;
            mbar_init(rb, 1); mbar_init(rb + 8, 1); mbar_init(xb, 1);
            if (wu == 0) mbar_init(qbar, 1);
            asm volatile("fence.mbarrier_init.release.cluster;" ::: "memory");
            const int row = (h * SK + (SK - WIN) + c * 1024 + wu * 128) * 3;
            const uint32_t ring = sb + SM_RING + wu * 2 * TILE;
#pragma unroll
            for (int n = 0; n < 3; n++) {
                const uint32_t bar = ((IN_S1 >> n) & 1) ? rb + 8 : ((IN_S0 >> n) & 1) ? rb : xb;
                mbar_expect_tx(bar, TILE);
                tma2d(((IN_S1 >> n) & 1) ? ring + TILE : ((IN_S0 >> n) & 1) ? ring : sb + SM_B + wu * TILE, &maps.k, 0, row + 48 * n, bar, POL_EF);
                if (n == 0 && wu == 0) {
                    mbar_expect_tx(qbar, 61440);
                    tma3d(sb + SM_Q, &maps.wq, 0, 160 * c, 3 * h, qbar, POL_EF);
                }
            }
            if (wu == 1) {
                mbar_init(fbar, 1);
#pragma unroll
                for (int i = 0; i < 3; i++) mbar_init(wbar + 8 * i, 1);
                asm volatile("fence.mbarrier_init.release.cluster;" ::: "memory");
            }
            if (wu >= 2) {
                const CUtensorMap* mp = wu == 2 ? &maps.v : wu == 3 ? &maps.wo : wu == 4 ? &maps.w1 : wu == 5 ? &maps.w3 : wu == 6 ? &maps.w2 : &maps.vr;
                asm volatile("prefetch.tensormap [%0];" ::"l"(mp) : "memory");
            }
        }
        if (tid < 160) asm volatile("ld.global.nc.v2.u32 {%0,%1}, [%2];" : "=r"(xv.x), "=r"(xv.y) : "l"(x_in + 4 * tid) : "memory");
        if (tid == 96) { misc[2] = 0.f; misc[3] = 0.f; }
        if (lane == 1) *reinterpret_cast<uint2*>(smem + SM_XL + warp * XSTR) = make_uint2(0u, t_start + WO_T0);
        if (tid >= 128 && tid < 148) {
            const uint32_t v = tid < 138 ? ONES : 0u;
            reinterpret_cast<uint4*>(smem + SM_ONE)[tid - 128] = make_uint4(v, v, v, v);
        }
        if (tid < 160) { xs32[xpos(2 * tid)] = xv.x; xs32[xpos(2 * tid + 1)] = xv.y; }
        __syncthreads();
        PROF_T(14);
        if (b == 0 && tid >= 232) asm volatile("st.relaxed.gpu.global.u32 [%0], %1;" ::"l"(g_scr.ticket + tid - 232), "r"(0) : "memory");
        if (tid == 64 || (tid == 65 && b < 216 - NCTA)) st_pkt(&g_scr.acc[1][(b + NCTA * (tid - 64)) * ACC_STR], 0, 0, 0, 0);
    }

    uint32_t kq[NQ][4];
    const float SC = 0.07216878364870322f * 1.4426950408889634f;

#pragma unroll 1
    for (int ph = 0; ph < 3; ph++) {
        const int layer = ph >> 1;
        const uint32_t tag = layer + 1;
        PROF_T(1 + layer * 16);
        if (ph) {
        {
            const int tl = opq(tid), warp = tl >> 5, lane = tl & 31, g = lane >> 2, t = lane & 3, mat = lane >> 3, r8 = lane & 7;
            const int kh = warp >> 2, mg = warp & 3;
            uint32_t aq[3];
#pragma unroll
            for (int i = 0; i < 3; i++) {
                const int ch = 6 * mg + 2 * i + (mat & 1);
                aq[i] = sb + SM_Q + (80 * kh + (mat >> 1) * 8 + r8) * 128 + (ch >> 3) * 20480 + (((ch & 7) ^ r8) << 4);
            }
#define PF_K5 if (layer == 1 && PFK) tile_keep(&maps.k, (h * SK + (SK - WIN) + c * 1024 + wu * 128 + PFK * 16) * 3);
            uint2 xv = make_uint2(0u, 0u);
            mbar_wait(qbar, 0);
            uint32_t pre[6][4];
#pragma unroll
            for (int n = 0; n < 6; n++) ldsm4t(aq[n % 3] + (n / 3) * 2048, pre[n]);
            if (layer == 1) {
                __syncthreads();
                if (elect_one()) {
                    const uint32_t bar = sb + SM_BAR + wu * 16;
                    asm volatile("mbarrier.expect_tx.relaxed.cta.shared::cta.b64 [%0], 1536;" ::"r"(bar) : "memory");
#pragma unroll
                    for (int k = 0; k < 3; k++)
                        tma2d(sb + SM_Q + v1_pos(3 * wu + k), &maps.vr, 0, (h * SK + (SK - WIN) + c * 1024 + wu * 128) / 2 + 8 + 2 * k, bar, POL_EF);
                }
            }
            const uint32_t pm = opq(g == 1 ? sb + SM_ONE : sb + SM_XS + 160 * (2 * c + kh) + 16 * t), pm2 = opq(pm + 128 - (g == 1 ? 0 : 8 * t));
            const uint32_t dq = opq(sb + SM_R + 8 * (kh * 192 + 48 * mg + g)), ds = opq(sb + SM_ST + 8 * warp + (lane < 16 ? 4 : 0));
            const bool wr = t == 0, ws = (lane & 15) == 0, lo = lane < 16;
            if (wu < 5) {
                const int p0 = xpos(2 * tl), p1 = xpos(2 * tl + 1);
                if (layer == 1) {
                    uint4 v;
                    int it = 0;
                    do { v = ld_pkt(&g_scr.ay[tl]); } while (!__all_sync(0xffffffffu, v.w == 1) && ++it < SPIN_CAP);
                    xv = make_uint2(v.x, v.y);
                    xs32[p0] = xv.x; xs32[p1] = xv.y;
                } else xv = make_uint2(xs32[p0], xs32[p1]);
            }
            if (layer) PC(24);
            if (layer) __syncthreads();
            PF_K5
            if (layer) PC(25);
            PROF_T(13 + layer * 16);
            const float e0 = bf_lo(xv.x), e1 = bf_hi(xv.x), e2 = bf_lo(xv.y), e3 = bf_hi(xv.y);
            const float s1 = (e0 + e1) + (e2 + e3), s2 = (e0 * e0 + e1 * e1) + (e2 * e2 + e3 * e3);
            float sv = lo ? s1 : s2, cc[3][4];
            gemv15<2048>(cc, pre, [&](int i) { return aq[i]; }, pm, pm2, sv, lo ? s2 : s1);
            if (wr) {
#pragma unroll
                for (int i = 0; i < 3; i++) { sts64(dq + 128 * i, cc[i][0], cc[i][1]); sts64(dq + 128 * i + 64, cc[i][2], cc[i][3]); }
            }
            if (ws) sts32(ds, sv);
        }
        const uint32_t pa = opq(sb + SM_R + 32 * opq(tid)), st = opq(sb + SM_ST);
        uint4* const pq = opq(&g_scr.hx[b * 48 + opq(tid)]);
        if (layer) PC(26);
        __syncthreads();
        if (layer) PC(27);
        PROF_T(33 + layer * 16);
        if (wu < 2) {
            float mean, inv;
            ln_stats(st, mean, inv);
            const float4 a0 = lds4f(pa), a1 = lds4f(pa + 16), b0 = lds4f(pa + 1536), b1 = lds4f(pa + 1552);
            float q0 = inv * ((a0.x + b0.x) - mean * (a0.y + b0.y)), q1 = inv * ((a0.z + b0.z) - mean * (a0.w + b0.w));
            float q2 = inv * ((a1.x + b1.x) - mean * (a1.y + b1.y)), q3 = inv * ((a1.z + b1.z) - mean * (a1.w + b1.w));
            st_pktfp(pq, q0, q1, q2, q3, 1, tid < 48);
        }
        if (layer == 1 && tid >= 192 && tid < 194 && b < 108) st_pkt(&g_scr.acc[0][(2 * b + opq(tid) - 192) * ACC_STR], 0, 0, 0, 0);
        }
        if (layer) PC(28);
        if (layer == 1 && (wu & 2)) {
            idle(K5D);
#pragma unroll 1
            for (int w = wu; w >= (wu > 4 ? wu - 2 : wu); w -= 2)
                tile_load(sb + SM_Q + c_slot(w), &maps.k, (h * SK + (SK - WIN) + c * 1024 + w * 128 + 5 * 16) * 3, sb + SM_XBAR + w * 8, 0, 0);
        }

        float sc0 = -INFINITY, sc1 = -INFINITY, sc2 = 0.f, sc3 = 0.f, mw;
        uint32_t pk0, pk1;
        float acc[3][4];
        {
            const uint32_t ring = sb + SM_RING + wu * 2 * TILE, rb = sb + SM_BAR + wu * 16;
            const uint32_t xtile = sb + SM_Q + c_slot(wu), xb = sb + SM_XBAR + wu * 8;
#define V_SEQ(n) ((int)(SEQ1 >> (4 * (n))) & 7)
#define SLOT1(n) (((IN_S1 >> (n)) & 1) ? ring + TILE : ((IN_S0 >> (n)) & 1) ? ring : sb + SM_B + wu * TILE)
#define BAR1(n) (((IN_S1 >> (n)) & 1) ? rb + 8 : ((IN_S0 >> (n)) & 1) ? rb : xb)
#define PAR1(n) ((PARITY1 >> (n)) & 1)
#define PAR2(n) ((PARITY2 >> (n)) & 1)
            const int row0 = (h * SK + (SK - WIN) + c * 1024 + wu * 128) * 3;
            auto issue1 = [&](int n, uint32_t dep, bool vph = false) {
                const CUtensorMap* mp = n < 8 ? &maps.k : &maps.v;
                const int tl = V_SEQ(n), row = row0 + tl * 48;
                const uint32_t dst = SLOT1(n), bar = BAR1(n);
                if (vph && wu < L1R && tl == 7 - (wu & 1)) {
                    tile_load_l1(dst, maps.vp, row, bar, opq(tid) & 31);
                    return;
                }
                tile_load(dst, mp, row, bar, dep, maps.zero);
                if ((RT_SEL >> (tl + (n & 8))) & 1) {
                    if (n != V0_AT + 1) tile_keep(mp, row);
                    else if ((opq(tid) & 31) < 8)
                        asm volatile("cp.async.bulk.prefetch.L2.global.L2::cache_hint [%0], 256, %1;"
                                     ::"l"(static_cast<const char*>(maps.vp) + (size_t)(row + 4 + 6 * (opq(tid) & 31)) * 128), "l"(POL_EN) : "memory");
                }
            };
            auto refill1 = [&](int s, uint32_t dep, bool vph = false) { issue1(s + (!vph || s < V0_AT ? 3 : 2), dep, vph); };
#define LANE_IDS const int tl = opq(tid), lane = tl & 31, g = lane >> 2, t = lane & 3; (void)tl; (void)lane; (void)g; (void)t;
            const uint32_t xl = sb + SM_XL + wu * XSTR;
            if (layer == 0) {
#pragma unroll 1
                for (int s = ph ? Q_AT : 0; s < (ph ? 5 : Q_AT); s++) {
                    LANE_IDS
                    const uint32_t tile = SLOT1(s);
                    mbar_wait(BAR1(s), PAR1(s));
                    const uint32_t scl = s == 0 ? pack_scale(tile, lane, xl + 8) : lds32(xl + 8);
                    pack_tile<false>(tile, s, 3, scl, xl, lane, [](int, uint32_t (&)[3]) {});
#pragma unroll
                    for (int n = 0; n < 5; n++) {
                        if (s == n) {
#pragma unroll
                            for (int m = 0; m < 3; m++) {
                                const uint32_t a = tile + K_OFF(2 * m);
                                lds128(a, kq[9 * n + 3 * m][0], kq[9 * n + 3 * m][1], kq[9 * n + 3 * m][2], kq[9 * n + 3 * m][3]);
                                lds128(a ^ 64, kq[9 * n + 3 * m + 1][0], kq[9 * n + 3 * m + 1][1], kq[9 * n + 3 * m + 1][2], kq[9 * n + 3 * m + 1][3]);
                                lds128(a + 3072, kq[9 * n + 3 * m + 2][0], kq[9 * n + 3 * m + 2][1], kq[9 * n + 3 * m + 2][2], kq[9 * n + 3 * m + 2][3]);
                            }
                        }
                    }
                    __syncwarp();
                    refill1(s, lds32(tile));
                }
                if (!ph) continue;
            }
            {
                const int tl = opq(tid);
                if (tl < 48) {
                    const int w = 2 * tl;
                    const uint32_t pos = opq(sb + SM_QS + 4 * (((w >> 2) & 3) * 24 + 2 * (w >> 4) + ((w >> 1) & 1)));
                    uint4 v[4];
                    int it = 0;
                    bool ok;
                    do {
#pragma unroll
                        for (int k = 0; k < 4; k++) v[k] = ld_pkt(&g_scr.hx[(h * 4 + k) * 48 + tl]);
                        ok = ~((v[0].w & v[1].w) & (v[2].w & v[3].w)) & 1;
                    } while (ok && ++it < SPIN_CAP);
                    sts32(pos, f_(pack2((f_(v[0].x) + f_(v[1].x)) + (f_(v[2].x) + f_(v[3].x)), (f_(v[0].y) + f_(v[1].y)) + (f_(v[2].y) + f_(v[3].y)))));
                    sts32(pos + 48, f_(pack2((f_(v[0].z) + f_(v[1].z)) + (f_(v[2].z) + f_(v[3].z)), (f_(v[0].w) + f_(v[1].w)) + (f_(v[2].w) + f_(v[3].w)))));
                }
            }
            if (layer) PC(29);
            __syncthreads();
            if (layer) PC(30);
            PROF_T(2 + layer * 16);
#define V1_REST(p) ((p) < 6 ? sb + SM_Q + v1_pos(3 * wu + ((p) >> 1)) + 256 * ((p) & 1) : ((sb + SM_R + wu * 784 + 127) & ~127u) - 1536 + 256 * (p))
#define V1_LOAD(bar) if (elect_one()) tma2d(V1_REST(6), &maps.vr, 0, row0 / 6 + 14, bar, POL_EF);
#define V1_EXPECT(bar) { if ((opq(tid) & 31) == 0) asm volatile("mbarrier.expect_tx.relaxed.cta.shared::cta.b64 [%0], 512;" ::"r"(bar) : "memory"); }
            if (layer == 1 && wu < 2) tile_load(xtile, &maps.k, row0 + 5 * 48, xb, 0, 0);
            if (layer == 1 && wu >= 4) idle(STAG);
            {
                uint32_t qf[12];
                int t;
                {
                    const int lane = opq(tid) & 31;
                    t = lane & 3;
                    const uint32_t qa = sb + SM_QS + (2 * t + ((lane >> 2) & 1)) * 48;
#pragma unroll
                    for (int i = 0; i < 3; i++) lds128(qa + 16 * i, qf[4 * i], qf[4 * i + 1], qf[4 * i + 2], qf[4 * i + 3]);
                }
                const uint32_t sq = lds32(xl + 8) - 64u * 0x00800080u;
#pragma unroll
                for (int i = 0; i < 12; i++) qf[i] = bmul2(qf[i], sq);
#define KR_STEP(tau, m) \
                    _Pragma("unroll") for (int i = 2 * (m); i < 2 * (m) + 2; i++) { \
                        const int q0 = 9 * tau + 3 * (i >> 1), r = i & 1; \
                        uint32_t w[4]; \
                        unpack8(kq[q0][2 * r], kq[q0][2 * r + 1], kq[q0 + 2][r], w); \
                        mma16816(cA, w[0], w[1], w[2], w[3], qf[2 * i], qf[2 * i + 1]); \
                        unpack8(kq[q0 + 1][2 * r], kq[q0 + 1][2 * r + 1], kq[q0 + 2][2 + r], w); \
                        mma16816(cB, w[0], w[1], w[2], w[3], qf[2 * i], qf[2 * i + 1]); \
                    }
#define KR_BEGIN float cA[4] = {0.f, 0.f, 0.f, 0.f}, cB[4] = {0.f, 0.f, 0.f, 0.f};
#define KR_END(tau) \
                    const float sA = (cA[0] + cA[3]) * 18446744073709551616.f, sB = (cB[0] + cB[3]) * 18446744073709551616.f; \
                    if (t == (tau & 3)) { if (tau < 4) { sc0 = sA; sc1 = sB; } else { sc2 = sA; sc3 = sB; } }
#define KR_SCORES(tau) { KR_BEGIN KR_STEP(tau, 0) KR_STEP(tau, 1) KR_STEP(tau, 2) KR_END(tau) }
                uint32_t va[3];
                {
                    const int lane = opq(tid) & 31, g = lane >> 2, t = lane & 3;
#pragma unroll
                    for (int i = 0; i < 3; i++) va[i] = ring + V_OFF(2 * i);
                }
#define V_STG(n) _Pragma("unroll") for (int j = 3 * (n); j < 3 * (n) + 3; j++) { \
                    const int i = (j % 12) >> 1; \
                    lds128p(((i & 1) ? (va[i >> 1] ^ 16) + 128 : va[i >> 1]) + (j / 12) * TILE + (j & 1) * 3072, layer, kq[j][0], kq[j][1], kq[j][2], kq[j][3]); }
                uint32_t dep = 0;
                {
                    KR_BEGIN
                    KR_STEP(0, 0) V_STG(0) KR_STEP(0, 1) V_STG(1) KR_STEP(0, 2) V_STG(2)
                    KR_END(0)
                }
                {
                    KR_BEGIN
                    KR_STEP(1, 0) V_STG(3)
                    __syncwarp();
                    dep = lds32(ring);
                    if (layer == 1) tile_load(ring, &maps.k, row0 + 6 * 48, rb, dep, maps.zero);
                    KR_STEP(1, 1) V_STG(4) KR_STEP(1, 2) V_STG(5)
                    KR_END(1)
                }
                {
                    KR_BEGIN
                    KR_STEP(2, 0) V_STG(6) KR_STEP(2, 1) V_STG(7)
                    __syncwarp();
                    dep = lds32(ring + TILE);
                    KR_STEP(2, 2)
                    if (layer == 1) {
                        V1_EXPECT(rb + 8)
                        tile_load(ring + TILE, &maps.k, row0 + 7 * 48, rb + 8, dep, maps.zero);
                        V1_LOAD(rb + 8)
                    }
                    KR_END(2)
                }
#pragma unroll 1
                for (int s = 5; s < 8; s++) {
                    {
                        LANE_IDS
                        const uint32_t tile = !layer ? SLOT1(s) : s == 5 ? xtile : ring + (s - 6) * TILE, tb = !layer ? BAR1(s) : s == 5 ? xb : rb + (s - 6) * 8;
                        const float ur = f_((318u << 23) - (lds32(xl + 8) << 16));
                        mbar_wait(tb, layer ? PAR2(s - 5) : PAR1(s));
                        if (layer) PROF_T(29 + s);
                        float cA[4] = {0.f, 0.f, 0.f, 0.f}, cB[4] = {0.f, 0.f, 0.f, 0.f};
#pragma unroll
                        for (int i = 0; i < 6; i++) {
                            uint32_t a0, a1, a2, a3;
                            lds128(tile + K_OFF(i), a0, a1, a2, a3);
                            mma16816(cA, a0, a1, a2, a3, qf[2 * i], qf[2 * i + 1]);
                            lds128(tile + K_OFF(i) + 3072, a0, a1, a2, a3);
                            mma16816(cB, a0, a1, a2, a3, qf[2 * i], qf[2 * i + 1]);
                        }
                        __syncwarp();
                        const uint32_t last = lds32(tile);
                        if (layer) tile_load(tile, &maps.v, row0 + (s - 2) * 48, tb, last, maps.zero);
                        else refill1(s, last);
                        if (t == (s & 3)) { sc2 = (cA[0] + cA[3]) * ur; sc3 = (cB[0] + cB[3]) * ur; }
                    }
                    if (s == 5) KR_SCORES(3)
                    if (s == 6) {
                        KR_SCORES(4)
                        const int lane = opq(tid) & 31;
                        const uint32_t nx = min(lds32(xl), (uint32_t)XCAP);
#pragma unroll 1
                        for (uint32_t n = 0; n < nx; n++) {
                            const uint32_t id = lds32(xl + 16 + 4 * n);
                            const uint32_t qo = 96 * ((id >> 7) & 3) + 48 * ((id >> 1) & 1) + 16 * ((id >> 5) & 3) + (id & 12) + 2 * (id & 1);
                            const float cr = bf_hi(id) * f_(lds16(sb + SM_QS + qo) << 16);
                            const int d = (int)(16 * ((id >> 9) & 7) + 4 * ((id >> 12) & 3) + ((id >> 13) & 2) + ((id >> 4) & 1) + ((id >> 8) & 128)) - 4 * lane;
                            if (d == 0) sc0 += cr;
                            if (d == 1) sc1 += cr;
                            if (d == 2) sc2 += cr;
                            if (d == 3) sc3 += cr;
                        }
                    }
                }
#undef KR_SCORES
#undef KR_STEP
#undef KR_BEGIN
#undef KR_END
#undef V_STG
                {
                    LANE_IDS
                    if (lds32(xl) > XCAP || !__all_sync(0xffffffffu, (fabsf(sc0) + fabsf(sc1)) + (fabsf(sc2) + fabsf(sc3)) < INFINITY)) {
                        const uint32_t qa = sb + SM_QS + (2 * t + (g & 1)) * 48;
#pragma unroll
                        for (int i = 0; i < 3; i++) lds128(qa + 16 * i, qf[4 * i], qf[4 * i + 1], qf[4 * i + 2], qf[4 * i + 3]);
                        const uint4* kg = reinterpret_cast<const uint4*>(static_cast<const char*>(maps.kp) + (size_t)row0 * 128) + ((g >> 1) + 4 * (g & 1)) * 24 + t;
#pragma unroll 1
                        for (int s = 0; s < 8; s++) {
                            float cA[4] = {0.f, 0.f, 0.f, 0.f}, cB[4] = {0.f, 0.f, 0.f, 0.f};
#pragma unroll
                            for (int i = 0; i < 6; i++) {
                                uint4 u = ldg128(kg + s * 384 + 4 * i);
                                mma16816v(cA, u.x, u.y, u.z, u.w, qf[2 * i], qf[2 * i + 1]);
                                u = ldg128(kg + s * 384 + 4 * i + 192);
                                mma16816v(cB, u.x, u.y, u.z, u.w, qf[2 * i], qf[2 * i + 1]);
                            }
                            if (t == s) { sc0 = cA[0] + cA[3]; sc1 = cB[0] + cB[3]; }
                            if (t + 4 == s) { sc2 = cA[0] + cA[3]; sc3 = cB[0] + cB[3]; }
                        }
                    }
                }
            }
            mw = warp_max(fmaxf(fmaxf(sc0, sc1), fmaxf(sc2, sc3)));
            pk0 = pack2(ex2((sc0 - mw) * SC), ex2((sc1 - mw) * SC));
            pk1 = pack2(ex2((sc2 - mw) * SC), ex2((sc3 - mw) * SC));
            sc2 = (bf_lo(pk0) + bf_hi(pk0)) + (bf_lo(pk1) + bf_hi(pk1));
            sc2 = (float)__reduce_add_sync(0xffffffffu, __float2uint_rn(sc2 * 16777216.f)) * (1.0f / 16777216.f);
            if ((opq(tid) & 31) == 0) st_pkt2(&g_scr.mx[h * 32 + c * 8 + wu], __float_as_uint(mw), (__float_as_uint(sc2) & ~3u) | tag);
            auto head_factor = [&]() {
                const int lane = opq(tid) & 31;
                int it = 0;
                while (!__all_sync(0xffffffffu, (__float_as_uint(sc1) & 3u) == tag) && ++it < SPIN_CAP) {
                    const uint2 mv = ld_pkt2(&g_scr.mx[h * 32 + lane]); sc0 = f_(mv.x); sc1 = f_(mv.y);
                }
                const float e = ex2((sc0 - warp_max(sc0)) * SC);
                const uint32_t d = __reduce_add_sync(0xffffffffu, __float2uint_rn(sc1 * e * 524288.f));
                sc3 = __shfl_sync(0xffffffffu, e, c * 8 + wu) * 524288.f * rcp((float)d);
            };
#pragma unroll
            for (int s = 0; s < 3; s++) { acc[s][0] = acc[s][1] = acc[s][2] = acc[s][3] = 0.f; }
#define P_CONSTS \
                const uint32_t sel0 = g == 0 ? 0x4410u : (g == 1 ? 0x1044u : 0x4444u); \
                const uint32_t sel1 = g == 2 ? 0x4410u : (g == 3 ? 0x1044u : 0x4444u); \
                const int src00 = 4 * (t < 2 ? 4 * t : 4 * (t - 2) + 1);
#define P_FRAGS(tau) \
                const uint32_t pk = ((tau) & 4) ? pk1 : pk0; \
                const uint32_t w0 = __shfl_sync(0xffffffffu, pk, src00 + ((tau) & 3)); \
                const uint32_t w1 = __shfl_sync(0xffffffffu, pk, src00 + ((tau) & 3) + 8); \
                uint32_t pb[4][2]; \
                _Pragma("unroll") for (int j = 0; j < 4; j++) { \
                    const uint32_t src = ((j & 1) ? w1 : w0) >> ((j >> 1) * 16); \
                    pb[j][0] = __byte_perm(src, 0, sel0); pb[j][1] = __byte_perm(src, 0, sel1); \
                }
            if (layer == 0) {
#pragma unroll 1
                for (int s = 8; s < 16; s++) {
                    LANE_IDS
                    P_CONSTS
                    if (s == 13) { const uint2 mv = ld_pkt2(&g_scr.mx[h * 32 + lane]); sc0 = f_(mv.x); sc1 = f_(mv.y); }
                    P_FRAGS(V_SEQ(s))
                    mbar_wait(BAR1(s), PAR1(s));
                    const uint32_t tile = SLOT1(s);
#pragma unroll
                    for (int j = 0; j < 4; j++) {
#pragma unroll
                        for (int u = 0; u < 3; u++) {
                            uint32_t a0, a1, a2, a3;
                            lds128(tile + (j >> 1) * 3072 + V_OFF(3 * (j & 1) + u), a0, a1, a2, a3);
                            mma16816(acc[u], a0, a1, a2, a3, pb[j][0], pb[j][1]);

                        }
                    }
                    __syncwarp();
                    if (s < V0_AT || (s > V0_AT + 1 && s < 14)) refill1(s, lds32(tile), true);
                    if (s == V0_AT || s == V0_AT + 1) {
                        {
                            const uint32_t ar = sb + SM_R + wu * 784 + 32 * g + 16 * t;
                            if (t < 2) {
#pragma unroll
                                for (int u = 0; u < 3; u++) sts128(ar + 256 * u, __float_as_uint(acc[u][0]), __float_as_uint(acc[u][1]), __float_as_uint(acc[u][2]), __float_as_uint(acc[u][3]));
                            }
                        }
                        const uint32_t scl = s == V0_AT ? pack_scale(tile, lane, xl + 12) : lds32(xl + 12);
                        pack_tile<true>(tile, s + 8 - V0_AT, V0_AT + 3 - s, scl, xl, lane, [&](int m, uint32_t (&d)[3]) {
                            if (s != V0_AT && m == 0) {
#pragma unroll
                                for (int k = 0; k < 3; k++) d[k] = ring + 3072 + V_OFF(2 * k + 1);
                            }
                        });
                        if (s != V0_AT) {
                            lds128(tile + V_OFF(2), kq[45][0], kq[45][1], kq[45][2], kq[45][3]);
                            lds128(tile + V_OFF(3), kq[46][0], kq[46][1], kq[46][2], kq[46][3]);
                            lds128(tile + V_OFF(2) + 3072, kq[47][0], kq[47][1], kq[47][2], kq[47][3]);
                            __syncwarp();
                            issue1(V0_AT + 3, lds32(tile));
                        }
                        const int ln = opq(tid) & 31;
                        const uint32_t ar = sb + SM_R + wu * 784 + 8 * (ln & 28) + 16 * (ln & 1);
#pragma unroll
                        for (int u = 0; u < 3; u++) {
                            uint32_t a0, a1, a2, a3;
                            lds128(ar + 256 * u, a0, a1, a2, a3);
                            acc[u][0] = f_(a0); acc[u][1] = f_(a1); acc[u][2] = f_(a2); acc[u][3] = f_(a3);
                        }
                    }
                    if (s == 13) head_factor();
                    if (s >= 14 && elect_one()) {
                        if (atomicAdd(reinterpret_cast<unsigned*>(misc + 3), 1u) == 14u && (int)(now_ns() - lds32(xl + 4)) >= 0) {
                            PROF_X(47);
                            load_wo(maps, sb + SM_B, h, c, wbar, 6);
                            atomicAdd(reinterpret_cast<unsigned*>(misc + 3), 256u);
                        }
                    }
                }
            } else {
                LANE_IDS
                P_CONSTS
#pragma unroll
                for (int k = 0; k < 4; k++) lds128(V1_REST(t + 4 * (k >> 1)) + 16 * g + 128 * (k & 1), kq[36 + k][0], kq[36 + k][1], kq[36 + k][2], kq[36 + k][3]);
#pragma unroll 1
                for (int i = 3; i < 8; i++) {
                    const uint32_t tile = i > 3 ? ring + (i & 1) * TILE : xtile, tb = i > 3 ? rb + (i & 1) * 8 : xb;
                    if (i == 6) { const uint2 mv = ld_pkt2(&g_scr.mx[h * 32 + lane]); sc0 = f_(mv.x); sc1 = f_(mv.y); }
                    if (i == 7) head_factor();
                    if (i == PK_AT) {
                uint32_t nx, nk, ik, iv;
                lds128(xl, nx, nk, ik, iv);
                if (nx <= XCAP) {
                    const uint32_t pks = bmul2(pk0, iv);
#pragma unroll
                    for (int s = 0; s < 2; s++) {
                        const uint32_t pk1 = 0, pk0 = pks;
                        P_FRAGS(s)
#pragma unroll
                        for (int j = 0; j < 4; j++) {
#pragma unroll
                            for (int u = 0; u < 3; u++) {
                                const int i = 3 * (j & 1) + u, m = i >> 1, r = i & 1, hf = j >> 1;
                                if (s == 1 && m == 2) continue;
                                const int ql = s == 0 ? 4 * m + 2 * hf : m == 0 ? 3 + 4 * hf : 45 + hf, qc = s == 0 ? 4 * m + 1 : m == 0 ? 11 : 47;
                                uint32_t w[4];
                                unpack8(kq[ql][2 * r], kq[ql][2 * r + 1], kq[qc][2 * hf + r], w);
                                mma16816(acc[u], w[0], w[1], w[2], w[3], pb[j][0], pb[j][1]);
                            }
                        }
                    }
#pragma unroll 1
                    for (uint32_t n = 0; n < nx; n++) {
                        const uint32_t id = lds32(xl + 16 + 4 * n);
                        const int i = ((id >> 4) & 6) + ((id >> 3) & 1), key = ((id >> 6) & 6) + (i >= 3);
                        const uint32_t pw = __shfl_sync(0xffffffffu, pk0, 8 * (key & 3) + (key & 4) + ((id >> 12) & 3));
                        const float cr = bf_hi(id) * ((id & 16) ? bf_hi(pw) : bf_lo(pw));
                        const int d = (int)(64 * ((id >> 9) & 7) + 4 * (id & 4) + 4 * (i >= 3 ? i - 3 : i) + (id & 3) + ((~id >> 5) & 1024)) - 16 * lane;
#pragma unroll
                        for (int k = 0; k < 12; k++) if (d == k) acc[k >> 2][k & 3] += cr;
                    }
                } else {
                    const uint4* vg = reinterpret_cast<const uint4*>(static_cast<const char*>(maps.vp) + (size_t)row0 * 128) + 48 * t + g;
#pragma unroll 1
                    for (int s = 0; s < 2; s++) {
                        P_FRAGS(s)
#pragma unroll
                        for (int j = 0; j < 4; j++) {
#pragma unroll
                            for (int u = 0; u < 3; u++) {
                                if (s == 1 && (j & 1) && u) continue;
                                const uint4 w = ldg128(vg + 384 * s + 192 * (j >> 1) + 24 * (j & 1) + 8 * u);
                                mma16816v(acc[u], w.x, w.y, w.z, w.w, pb[j][0], pb[j][1]);
                            }
                        }
                    }
                }
#pragma unroll
                for (int s = 2; s > 0; s--) {
                    P_FRAGS(s)
#pragma unroll
                    for (int j = 0; j < 4; j++) {
#pragma unroll
                        for (int u = 0; u < 3; u++) {
                            if (s == 1 && !((j & 1) && u)) continue;
                            const int k = s == 2 ? 12 + 2 * (3 * (j & 1) + u) + (j >> 1) : 35 + (j >> 1) * 2 + u;
                            mma16816(acc[u], kq[k][0], kq[k][1], kq[k][2], kq[k][3], pb[j][0], pb[j][1]);
                        }
                    }
                }
                    }
                    P_FRAGS(i)
                    mbar_wait(tb, PAR2(i));
                    PROF_T(34 + i);
#pragma unroll
                    for (int k = 0; k < 6; k++) {
                        const uint32_t a = tile + V_OFF(k);
                        lds128(a, kq[24 + k][0], kq[24 + k][1], kq[24 + k][2], kq[24 + k][3]);
                        lds128(a + 3072, kq[30 + k][0], kq[30 + k][1], kq[30 + k][2], kq[30 + k][3]);
                    }
#pragma unroll
                    for (int j = 0; j < 4; j++) {
#pragma unroll
                        for (int u = 0; u < 3; u++) {
                            const int k = 24 + 6 * (j >> 1) + 3 * (j & 1) + u;
                            mma16816(acc[u], kq[k][0], kq[k][1], kq[k][2], kq[k][3], pb[j][0], pb[j][1]);
                        }
                    }
                    __syncwarp();
                    if (wu < L1R && i == 5 - (wu & 1)) tile_load_l1(tile, maps.vp, row0 + (i + 2) * 48, tb, lane);
                    else if (i == 4 || i == 5) tile_load(tile, &maps.v, row0 + (i + 2) * 48, tb, lds32(tile), maps.zero);
                    if (i == WO_AT1 && HAS_FFN && elect_one()) {
                        if (atomicAdd(reinterpret_cast<unsigned*>(misc + 2), 1u) == 7u) {
                            PROF_X(63);
                            load_wo(maps, sb + SM_Q, h, c, wbar, KEEP4 && __float_as_uint(misc[1]) >= DN0 ? 5 : 6);
                        }
                    }
                }
            }
#undef P_FRAGS
#undef P_CONSTS
#undef LANE_IDS
        }
        PROF_T(3 + layer * 16);
        PC(layer * 32 + 1);

        {
            const int lane = opq(tid) & 31;
            const uint32_t a = sb + SM_R + wu * 784 + 8 * (lane & 28) + 16 * (lane & 1);
#pragma unroll
            for (int u = 0; u < 3; u++) sts128p(a + 256 * u, acc[u][0] * sc3, acc[u][1] * sc3, acc[u][2] * sc3, acc[u][3] * sc3, lane & 2);
        }
        const uint32_t role1 = layer ? lds32(sb + SM_MISC + 4) : DN0 + NDN;
        const uint32_t pc = opq(sb + SM_R + 16 * opq(tid));
        uint4* const px0 = opq(&g_scr.hx[b * 48 + opq(tid)]);
        __syncthreads();
        PROF_T(4 + layer * 16);
        PC(layer * 32 + 2);
        uint32_t ticket = 0;
        if (layer == 0 && tid == 224)
            asm volatile("atom.relaxed.gpu.global.inc.u32 %0, [%1], 0x7fffffff;" : "=r"(ticket) : "l"(g_scr.ticket + 8 + (b >> 3)) : "memory");
        if (layer == 0 && tid == 224 && lds32(sb + SM_MISC + 12) < 256u) {
            int it = 0;
            while ((int)(now_ns() - lds32(sb + SM_XL + 4)) < 0 && ++it < SPIN_CAP) {}
            PROF_X(47);
            load_wo(maps, sb + SM_B, h, c, wbar, 6);
        }
        uint32_t pr;
        uint4* pacc;
        {
            const int tid = opq(threadIdx.x), warp = tid >> 5, lane = tid & 31, g = lane >> 2, t = lane & 3, mat = lane >> 3, r8 = lane & 7;
            const int kg = warp >> 1, mg = warp & 1;
            const bool wo2 = role1 < DN0 + NDN;
            const uint32_t aw2 = 40960 + (wo2 && KEEP4 && role1 >= DN0 && kg >= 2 ? SM_B - SM_Q : 0);
            uint32_t aw[5];
#pragma unroll
            for (int i = 0; i < 5; i++) {
                const uint32_t lin = ((mat >> 1) * 8 + r8) * 320 + 64 * i + 32 * mg + 16 * (mat & 1);
                aw[i] = sb + (wo2 ? SM_Q : SM_B) + 5120 * kg + (lin ^ ((lin >> 3) & 48));
            }
            float4 o = make_float4(0.f, 0.f, 0.f, 0.f);
            if (threadIdx.x < 48) {
                float4 v[8];
#pragma unroll
                for (int w = 0; w < 8; w++) v[w] = lds4f(pc + w * 784);
                o.x = ((v[0].x + v[1].x) + (v[2].x + v[3].x)) + ((v[4].x + v[5].x) + (v[6].x + v[7].x));
                o.y = ((v[0].y + v[1].y) + (v[2].y + v[3].y)) + ((v[4].y + v[5].y) + (v[6].y + v[7].y));
                o.z = ((v[0].z + v[1].z) + (v[2].z + v[3].z)) + ((v[4].z + v[5].z) + (v[6].z + v[7].z));
                o.w = ((v[0].w + v[1].w) + (v[2].w + v[3].w)) + ((v[4].w + v[5].w) + (v[6].w + v[7].w));
                st_pktf(px0, o.x, o.y, o.z, o.w, 0);
            }
#define CXE 1
            const uint32_t ao = pin(sb + SM_OS + 96 * kg + 16 * t), dw = pin(sb + SM_R + 16 * (16 * mg + g) + 4 * kg);
            pr = pin(sb + SM_R + 48 * tid); pacc = pin(&g_scr.acc[layer][(54 * c + tid) * ACC_STR]);
            const int w = 2 * min(tid, 47);
            const uint32_t d0 = pin(sb + SM_OS + 4 * (24 * ((w >> 3) & 3) + ((w >> 2) & 1) + (w < 64 ? 4 * (w & 3) + 2 * (w >> 5) : 16 + 2 * (w & 3))));
            const uint32_t d1 = pin(d0 + (w < 64 ? 16 : 8));
            const uint4* pp[3];
#pragma unroll
            for (int k = 0; k < 3; k++) pp[k] = pin(&g_scr.hx[(h * 4 + ((c + 1 + k) & 3)) * 48 + min(tid, 47)]);
            bool ok = true;
            if ((PRE1 & 8) && layer) {
#pragma unroll
                for (int ks = 0; ks < 3; ks++) {
                    mbar_wait(wbar + 8 * ks, wo2);
#pragma unroll
                    for (int i = 0; i < 5; i++) ldsm4t(aw[i] + (ks == 2 ? aw2 : 20480 * ks), kq[3 * i + ks]);
                    if (ks == CXE && wu < 2) {
#pragma unroll
                        for (int k = 0; k < 3; k++) { const uint4 v = ld_pkt(pp[k]); kq[20 + k][0] = v.x; kq[20 + k][1] = v.y; kq[20 + k][2] = v.z; kq[20 + k][3] = v.w; }
                    }
                }
                PROF_T(50);
                if (CXE < 3 && wu < 2) {
                    ok = __any_sync(0xffffffffu, (kq[20][3] | kq[21][3] | kq[22][3]) & 1);
                    if (!ok) {
#pragma unroll
                        for (int k = 0; k < 3; k++) { o.x += f_(kq[20 + k][0]); o.y += f_(kq[20 + k][1]); o.z += f_(kq[20 + k][2]); o.w += f_(kq[20 + k][3]); }
                    }
                }
            }
            if (wu < 2) {
                if (ok) {
                    uint4 v3[3];
                    int it = 0;
                    do {
#pragma unroll
                        for (int k = 0; k < 3; k++) v3[k] = ld_pkt(pp[k]);
                        ok = __any_sync(0xffffffffu, (v3[0].w | v3[1].w | v3[2].w) & 1);
                    } while (ok && ++it < SPIN_CAP);
#pragma unroll
                    for (int k = 0; k < 3; k++) { o.x += f_(v3[k].x); o.y += f_(v3[k].y); o.z += f_(v3[k].z); o.w += f_(v3[k].w); }
                }
                sts32p(d0, f_(pack2(o.x, o.y)), tid >= 48);
                sts32p(d1, f_(pack2(o.z, o.w)), tid >= 48);
            }
            PC(layer * 32 + 3);
            __syncthreads();
            PROF_T(5 + layer * 16);
            PC(layer * 32 + 5);
            if (tid == 224 && layer == 0) {
                if (ticket >= 6 + ((b >> 3) & 1)) ticket = DN0 + NDN;
                else asm volatile("atom.relaxed.gpu.global.inc.u32 %0, [%1], 0x7fffffff;" : "=r"(ticket) : "l"(g_scr.ticket) : "memory");
            }
            uint32_t ob[6];
            lds128(ao, ob[0], ob[1], ob[2], ob[3]);
            lds64(ao + 64 - 8 * t, ob[4], ob[5]);
            float cc[5][4];
#pragma unroll
            for (int i = 0; i < 5; i++) cc[i][0] = cc[i][1] = cc[i][2] = cc[i][3] = 0.f;
            if ((PRE1 & 8) && layer) {
#pragma unroll
                for (int ks = 0; ks < 3; ks++) {
#pragma unroll
                    for (int i = 0; i < 5; i++) mma16816(cc[i], kq[3 * i + ks][0], kq[3 * i + ks][1], kq[3 * i + ks][2], kq[3 * i + ks][3], ob[2 * ks], ob[2 * ks + 1]);
                }
            } else {
#pragma unroll
                for (int ks = 0; ks < 3; ks++) {
                    mbar_wait(wbar + 8 * ks, wo2);
                    if (ks == 2) { PC(layer * 32 + 4); PROF_T(48 + layer * 2); }
                    uint32_t a[5][4];
#pragma unroll
                    for (int i = 0; i < 5; i++) ldsm4t(aw[i] + (ks == 2 ? aw2 : 20480 * ks), a[i]);
#pragma unroll
                    for (int i = 0; i < 5; i++) mma16816(cc[i], a[i][0], a[i][1], a[i][2], a[i][3], ob[2 * ks], ob[2 * ks + 1]);
                }
            }
            if (t == 0) {
#pragma unroll
                for (int i = 0; i < 5; i++) { sts32(dw + 512 * i, cc[i][0]); sts32(dw + 512 * i + 128, cc[i][2]); }
            }
        }
        PC(layer * 32 + 6);
        __syncthreads();
        PROF_T(6 + layer * 16);
        PC(layer * 32 + 7);
        if (tid < 54) {
            const float4 v0 = lds4f(pr), v1 = lds4f(pr + 16), v2 = lds4f(pr + 32);
            const float y0 = (v0.x + v0.y) + (v0.z + v0.w), y1 = (v1.x + v1.y) + (v1.z + v1.w), y2 = (v2.x + v2.y) + (v2.z + v2.w);
            red_pkt(pacc, y0, tid == 53 ? 0.f : y1, tid == 53 ? 0.f : y2);
        }
        if (tid == 224 && layer == 0) {
            misc[1] = __uint_as_float(ticket);
            if (ticket < DN0 + NDN && (ticket < NG || !DNTH)) load_ffn(maps, ticket, sb + SM_B, fbar);
        }
        PROF_T(7 + layer * 16);
        PC(layer * 32 + 8);
        __syncthreads();
        const int role = (int)__float_as_uint(misc[1]);
        PC(layer * 32 + 9);
        const uint32_t fbase = sb + SM_B;
        const uint32_t DONE32 = 0x42000000u;
        if (role < NG) {
            const int tid = opq(threadIdx.x), warp = tid >> 5, lane = tid & 31, g = lane >> 2, t = lane & 3, mat = lane >> 3, r8 = lane & 7;
            const uint32_t ag = fbase + (80 * warp + (mat >> 1) * 8 + r8) * 96 + (((mat & 1) ^ (r8 >> 2)) << 4);
            constexpr int GI = 32, GK = 16 * 96;
            const bool on = (g & 1) == (t >> 1), isx = on && g < 2;
            const uint32_t pm = opq(isx ? sb + SM_XS + 160 * warp + 16 * t : sb + (on ? SM_ONE : SM_ZERO)), pm2 = opq(pm + 128 - (isx ? 8 * t : 0));
            const uint32_t dg = opq(sb + SM_R + 4 * (2 * (warp * 48 + g) + t)), ds = opq(sb + SM_ST + 8 * warp + (lane < 16 ? 4 : 0));
            const bool ws = (lane & 15) == 0, lo = lane < 16;
            uint32_t pre[6][4];
            float s1 = 0.f, s2 = 0.f;
            {
                bool hx = wu == 7;
                int it = 0;
                const uint4* px = &g_scr.acc[layer][min(tid, 215) * ACC_STR];
                const int cq = tid / 54, r = tid - 54 * cq, k0 = min(160 * cq + 3 * r, DM - 1);
                const uint32_t w0 = sb + SM_XS + 4 * xpos(k0 >> 1), w1 = sb + SM_XS + 4 * xpos(min((k0 >> 1) + 1, DM / 2 - 1));
                const uint32_t e0 = w0 + 2 * (k0 & 1), e1 = (k0 & 1) ? w1 : w0 + 2, e2 = w1 + 2 * (k0 & 1);
                                auto sts16 = [](uint32_t a, uint32_t x, bool on) {
                    asm volatile("{\n.reg .pred p;\nsetp.ne.u32 p, %2, 0;\n@p st.shared.u16 [%0], %1;\n}" ::"r"(a), "h"((unsigned short)x), "r"((uint32_t)on) : "memory");
                };
                const bool on0 = tid < 216, on1 = on0 && r != 53;
                const float x0 = on0 ? f_(lds16(e0) << 16) : 0.f, x1 = on1 ? f_(lds16(e1) << 16) : 0.f, x2 = on1 ? f_(lds16(e2) << 16) : 0.f;
                auto take_x = [&](const uint4 v) {
                    if (__all_sync(0xffffffffu, v.w == DONE32)) {
                        hx = true;
                        const uint32_t a = pack2(f_(v.x), f_(v.y)), p = pack2(x0 + bf_lo(a), x1 + bf_hi(a)), q = pack2(x2 + bfr(f_(v.z)), 0.f);
                        sts16(e0, p, on0); sts16(e1, p >> 16, on1); sts16(e2, q, on1);
                        const float y0 = on0 ? bf_lo(p) : 0.f, y1 = on0 ? bf_hi(p) : 0.f, y2 = on0 ? bf_lo(q) : 0.f;
                        s1 = y0 + (y1 + y2); s2 = y0 * y0 + (y1 * y1 + y2 * y2);
                    }
                };
                auto try_x = [&]() { take_x(ld_pkt(px)); };
                while (!mbar_test(fbar, 0) && ++it < SPIN_CAP) { if (!hx) try_x(); }
                uint4 v0 = make_uint4(0u, 0u, 0u, 0u);
                if ((PRE1 & 4) && !hx) v0 = ld_pkt(px);
#pragma unroll
                for (int n = 0; n < 6; n++) ldsm4t(ag + (n % 3) * GI + (n / 3) * GK, pre[n]);
                if ((PRE1 & 1) && layer) {
#pragma unroll
                    for (int n = 6; n < 15; n++) ldsm4t(ag + (n % 3) * GI + (n / 3) * GK, kq[n - 6]);
                }
                if ((PRE1 & 4) && !hx) take_x(v0);
                PC(layer * 32 + 10);
                while (!hx && ++it < SPIN_CAP) try_x();
                PC(layer * 32 + 11);
            __syncthreads();
            PC(layer * 32 + 12);
            PROF_T(9 + layer * 16);
            float sv = lo ? s1 : s2, cc[3][4];
            if ((PRE1 & 1) && layer) gemv15r(cc, pre, kq, pm, pm2, sv, lo ? s2 : s1);
            else gemv15<GK>(cc, pre, [&](int i) { return ag + i * GI; }, pm, pm2, sv, lo ? s2 : s1);
#pragma unroll
            for (int i = 0; i < 3; i++) { sts32p(dg + 128 * i, cc[i][0] + cc[i][3], t & 2); sts32p(dg + 128 * i + 64, cc[i][1] + cc[i][2], t & 2); }
            if (ws) sts32(ds, sv);
            const uint32_t pg = opq(sb + SM_R + 8 * (24 * warp + (lane < 24 ? lane : 0))), st = opq(sb + SM_ST);
            uint4* const ph = opq(lane < 24 && lane % 6 == 0 ? &g_scr.ah[role * 8 + 4 * warp + lane / 6] : nullptr);
            PC(layer * 32 + 13);
            __syncthreads();
            PC(layer * 32 + 14);
            PROF_T(43 + layer * 16);
            if (wu < 2) {
                float mean, inv;
                ln_stats(st, mean, inv);
                float2 v[8];
#pragma unroll
                for (int w = 0; w < 8; w++) v[w] = lds2f(pg + w * 384);
                const float gx = ((v[0].x + v[1].x) + (v[2].x + v[3].x)) + ((v[4].x + v[5].x) + (v[6].x + v[7].x));
                const float gs = ((v[0].y + v[1].y) + (v[2].y + v[3].y)) + ((v[4].y + v[5].y) + (v[6].y + v[7].y));
                float ga = inv * (gx - mean * gs);
                if (role < NG / 2) { ga = bfr(ga); ga *= rcp(1.0f + ex2(-1.4426950408889634f * ga)); }
                const uint32_t wd = pack2(ga, __shfl_down_sync(0xffffffffu, ga, 1));
                const uint32_t wa = __shfl_down_sync(0xffffffffu, wd, 2), wb = __shfl_down_sync(0xffffffffu, wd, 4);
                if (ph) st_pkt(ph, wd, wa, wb, tag);
            }
            if (HOLD & 2) __syncthreads();
            }
            PROF_T(10 + layer * 16);
            PC(layer * 32 + 15);
        } else if (role < DN0 + NDN) {
            const int j = role - DN0;
            const int tid = opq(threadIdx.x), warp = tid >> 5, lane = tid & 31, g = lane >> 2, t = lane & 3, mat = lane >> 3, r8 = lane & 7;
            float xres = 0.f;
            uint32_t xr0 = 0, xr1 = 0;
            if (wu == 0) {
                const int col = 16 * j + (lane & 15), cc = col / 160, r = col - 160 * cc, e = r % 3;
                const uint4* px = &g_scr.acc[layer][(54 * cc + r / 3) * ACC_STR];
                const float x0 = __bfloat162float(reinterpret_cast<const __nv_bfloat16*>(xs32)[2 * xpos(col >> 1) + (col & 1)]);
                uint4 v;
                int it = 0;
                bool ld = DNTH && layer == 0;
                do {
                    v = ld_pkt(px);
                    if (ld && f_(__shfl_sync(0xffffffffu, v.w, 0)) >= (float)DNTH) { ld = false; if (lane == 0) load_ffn(maps, role, sb + SM_B, fbar); }
                } while (!__all_sync(0xffffffffu, v.w == DONE32) && ++it < SPIN_CAP);
                if (ld && lane == 0) load_ffn(maps, role, sb + SM_B, fbar);
                xres = x0 + bfr(f_(e == 0 ? v.x : (e == 1 ? v.y : v.z)));
                const int p4 = 4 * (lane & 3);
                xr0 = pack2(__shfl_sync(0xffffffffu, xres, p4), __shfl_sync(0xffffffffu, xres, p4 + 1));
                xr1 = pack2(__shfl_sync(0xffffffffu, xres, p4 + 2), __shfl_sync(0xffffffffu, xres, p4 + 3));
            }
            PC(layer * 32 + 17);
            PROF_T(9 + layer * 16);
            const uint32_t ad = fbase + (192 * warp + (mat >> 1) * 8 + r8) * 32 + (((mat & 1) ^ (r8 >> 2)) << 4);
            uint32_t* hs = reinterpret_cast<uint32_t*>(rr) + warp * 96;
            uint32_t pre[NPRE][4];
            {
                uint32_t pos[3];
#pragma unroll
                for (int i = 0; i < 3; i++) { const int w = 3 * lane + i; pos[i] = pin(sb + SM_R + 384 * warp + 4 * ((w & ~15) + 4 * (w & 3) + ((w >> 2) & 1) + ((w >> 2) & 2))); }
                uint4 v = make_uint4(0u, 0u, 0u, 0u), u = v;
                if (layer == 0) { v = ld_pkt(&g_scr.ah[tid]); u = ld_pkt(&g_scr.ah[256 + tid]); }
                mbar_wait(fbar, 0);
#pragma unroll
                for (int n = 0; n < NPRE; n++) ldsm4t(ad + n * 512, pre[n]);
                if ((PRE1 & 2) && layer) {
#pragma unroll
                    for (int n = NPRE; n < 12; n++) ldsm4t(ad + n * 512, kq[12 + n]);
                }
                PC(layer * 32 + 18);
                int it = 0;
                while (!__all_sync(0xffffffffu, v.w == tag && u.w == tag) && ++it < SPIN_CAP) { v = ld_pkt(&g_scr.ah[tid]); u = ld_pkt(&g_scr.ah[256 + tid]); }
                PC(layer * 32 + 19);
                sts32(pos[0], f_(bmul2(v.x, u.x))); sts32(pos[1], f_(bmul2(v.y, u.y))); sts32(pos[2], f_(bmul2(v.z, u.z)));
            __syncwarp();
            PROF_T(11 + layer * 16);
            PC(layer * 32 + 20);
            float ca[4] = {0.f, 0.f, 0.f, 0.f}, cb[4] = {0.f, 0.f, 0.f, 0.f};
            if ((PRE1 & 2) && layer) {
                float cc[4] = {0.f, 0.f, 0.f, 0.f}, cd[4] = {0.f, 0.f, 0.f, 0.f};
#pragma unroll
                for (int jj = 0; jj < 6; jj++) {
                    const uint4 hv = *reinterpret_cast<const uint4*>(hs + 16 * jj + 4 * t);
                    const uint32_t (&f0)[4] = 2 * jj < NPRE ? pre[2 * jj < NPRE ? 2 * jj : 0] : kq[12 + 2 * jj];
                    const uint32_t (&f1)[4] = 2 * jj + 1 < NPRE ? pre[2 * jj + 1 < NPRE ? 2 * jj + 1 : 0] : kq[13 + 2 * jj];
                    if (jj & 1) { mma16816(cc, f0[0], f0[1], f0[2], f0[3], hv.x, hv.y); mma16816(cd, f1[0], f1[1], f1[2], f1[3], hv.z, hv.w); }
                    else { mma16816(ca, f0[0], f0[1], f0[2], f0[3], hv.x, hv.y); mma16816(cb, f1[0], f1[1], f1[2], f1[3], hv.z, hv.w); }
                }
#pragma unroll
                for (int e = 0; e < 4; e++) { ca[e] += cc[e]; cb[e] += cd[e]; }
            } else {
#pragma unroll
                for (int jj = 0; jj < 6; jj++) {
                    const uint4 hv = *reinterpret_cast<const uint4*>(hs + 16 * jj + 4 * t);
                    uint32_t a[4];
                    if (2 * jj < NPRE) { a[0] = pre[2 * jj][0]; a[1] = pre[2 * jj][1]; a[2] = pre[2 * jj][2]; a[3] = pre[2 * jj][3]; }
                    else ldsm4t(ad + 2 * jj * 512, a);
                    mma16816(ca, a[0], a[1], a[2], a[3], hv.x, hv.y);
                    if (2 * jj + 1 < NPRE) { a[0] = pre[2 * jj + 1][0]; a[1] = pre[2 * jj + 1][1]; a[2] = pre[2 * jj + 1][2]; a[3] = pre[2 * jj + 1][3]; }
                    else ldsm4t(ad + (2 * jj + 1) * 512, a);
                    mma16816(cb, a[0], a[1], a[2], a[3], hv.z, hv.w);
                }
            }
            if (t == 0) { rr[768 + warp * 16 + g] = ca[0] + cb[0]; rr[768 + warp * 16 + 8 + g] = ca[2] + cb[2]; }
            const uint32_t pd = opq(sb + SM_R + 3072 + 16 * (lane & 3));
            uint4* const py = opq(&g_scr.ay[j * 4 + lane]);
            uint2* const po = opq(reinterpret_cast<uint2*>(out + 16 * j) + lane);
            PC(layer * 32 + 21);
            __syncthreads();
            PC(layer * 32 + 22);
            if (wu == 0) {
                float4 p[8];
#pragma unroll
                for (int w = 0; w < 8; w++) p[w] = lds4f(pd + 64 * w);
                const uint32_t y0 = pack2(((p[0].x + p[1].x) + (p[2].x + p[3].x)) + ((p[4].x + p[5].x) + (p[6].x + p[7].x)),
                                          ((p[0].y + p[1].y) + (p[2].y + p[3].y)) + ((p[4].y + p[5].y) + (p[6].y + p[7].y)));
                const uint32_t y1 = pack2(((p[0].z + p[1].z) + (p[2].z + p[3].z)) + ((p[4].z + p[5].z) + (p[6].z + p[7].z)),
                                          ((p[0].w + p[1].w) + (p[2].w + p[3].w)) + ((p[4].w + p[5].w) + (p[6].w + p[7].w)));
                uint32_t wd, wn;
                asm("add.rn.bf16x2 %0, %1, %2;" : "=r"(wd) : "r"(xr0), "r"(y0));
                asm("add.rn.bf16x2 %0, %1, %2;" : "=r"(wn) : "r"(xr1), "r"(y1));
                asm volatile("{\n.reg .pred p;\nsetp.ne.u32 p, %3, 0;\n@p st.global.v2.u32 [%0], {%1,%2};\n}" ::"l"(po), "r"(wd), "r"(wn), "r"((uint32_t)(layer && tid < 4)) : "memory");
                st_pktp(py, wd, wn, 0, tag, tid < 4);
            }
            if (HOLD & 1) __syncthreads();
            }
            PROF_T(12 + layer * 16);
            PC(layer * 32 + 23);
        }
    }
}

typedef CUresult (*EncodeFn)(CUtensorMap*, CUtensorMapDataType, cuuint32_t, void*, const cuuint64_t*, const cuuint64_t*, const cuuint32_t*,
                             const cuuint32_t*, CUtensorMapInterleave, CUtensorMapSwizzle, CUtensorMapL2promotion, CUtensorMapFloatOOBfill);

void make_map(EncodeFn enc, CUtensorMap* m, const void* base, int rank, uint64_t d0, uint64_t d1, uint64_t d2, uint64_t s1, uint64_t s2,
              uint32_t b0, uint32_t b1, uint32_t b2, CUtensorMapSwizzle sw, CUtensorMapL2promotion pr = CU_TENSOR_MAP_L2_PROMOTION_NONE) {
    cuuint64_t dims[3] = {d0, d1, d2};
    cuuint64_t strides[2] = {s1, s2};
    cuuint32_t box[3] = {b0, b1, b2};
    cuuint32_t es[3] = {1, 1, 1};
    enc(m, CU_TENSOR_MAP_DATA_TYPE_BFLOAT16, rank, const_cast<void*>(base), dims, strides, box, es, CU_TENSOR_MAP_INTERLEAVE_NONE, sw,
        pr, CU_TENSOR_MAP_FLOAT_OOB_FILL_NONE);
}

}

extern "C" void kernel_launch(void* const* d_in, const int* in_sizes, int n_in, void* d_out, int out_size) {
    (void)in_sizes; (void)n_in; (void)out_size;
    static EncodeFn enc = nullptr;
    if (!enc) {
        void* fn = nullptr;
        cudaDriverEntryPointQueryResult qr;
        cudaGetDriverEntryPoint("cuTensorMapEncodeTiled", &fn, cudaEnableDefault, &qr);
        enc = reinterpret_cast<EncodeFn>(fn);
        cudaFuncSetAttribute(decode_kernel, cudaFuncAttributeMaxDynamicSharedMemorySize, SM_TOTAL);
    }
    Maps maps;
    make_map(enc, &maps.k, d_in[1], 2, 64, (uint64_t)NH * SK * 3, 1, 128, 0, 64, 48, 1, CU_TENSOR_MAP_SWIZZLE_128B);
    make_map(enc, &maps.v, d_in[2], 2, 64, (uint64_t)NH * SK * 3, 1, 128, 0, 64, 48, 1, CU_TENSOR_MAP_SWIZZLE_128B);
    make_map(enc, &maps.wq, d_in[3], 3, 64, DM, NH * DH / 64, NH * DH * 2, 128, 64, 160, 3, CU_TENSOR_MAP_SWIZZLE_128B);
    make_map(enc, &maps.wo, d_in[4], 3, 32, DM / 32, NH * DH, 64, DM * 2, 32, 5, 32, CU_TENSOR_MAP_SWIZZLE_64B);
    make_map(enc, &maps.vr, (const char*)d_in[2] + 512, 2, 128, (uint64_t)NH * SK / 2, 1, 768, 0, 128, 2, 1, CU_TENSOR_MAP_SWIZZLE_NONE);
    constexpr int GW = 48;
    make_map(enc, &maps.w1, d_in[6], 3, FF, 160, 4, FF * 2, 160 * FF * 2, GW, 160, 4, CU_TENSOR_MAP_SWIZZLE_NONE, FFN_PROMO);
    make_map(enc, &maps.w3, d_in[7], 3, FF, 160, 4, FF * 2, 160 * FF * 2, GW, 160, 4, CU_TENSOR_MAP_SWIZZLE_NONE, FFN_PROMO);
    make_map(enc, &maps.w2, d_in[8], 3, DM, 256, 6, DM * 2, 256 * DM * 2, 16, 256, 6, CU_TENSOR_MAP_SWIZZLE_32B, FFN_PROMO);
    maps.vp = d_in[2];
    maps.kp = d_in[1];
    maps.zero = 0;
    decode_kernel<<<NCTA, NT, SM_TOTAL, cudaStreamPerThread>>>(maps, (const __nv_bfloat16*)d_in[0], (__nv_bfloat16*)d_out);
}
```

```cpp
#include <cuda_runtime.h>
#include <cuda_bf16.h>
#include <cuda.h>
#include <stdint.h>
#include <math.h>

namespace {

constexpr int DM = 640;
constexpr int NH = 32;
constexpr int DH = 192;
constexpr int SK = 32768;
constexpr int WIN = 4096;
constexpr int FF = 1536;
constexpr int NCTA = 128;
constexpr int NT = 256;
constexpr int TILE = 6144;
constexpr int NG = 64;
constexpr int DN0 = 64;
constexpr int NDN = 40;

constexpr int SM_RING = 0;
constexpr int SM_B = 8 * 2 * TILE;
constexpr int SM_Q = SM_B + 61440;
__host__ __device__ constexpr int c_slot(int w) { return w < 2 ? 4096 + 10240 * w : 12288 + 6144 * w; }
__host__ __device__ constexpr int v1_pos(int n) { return 10240 * (n >> 3) + 512 * (n & 7); }
constexpr int SM_XS = SM_Q + 61440;
constexpr int SM_R = SM_XS + 1280;
constexpr int SM_ST = SM_R + 4096;
constexpr int SM_QS = SM_R + 6272;
constexpr int SM_OS = SM_QS + 384;
constexpr int SM_BAR = SM_OS + 384;
constexpr int SM_XBAR = SM_BAR + 24 * 8;
constexpr int SM_MISC = SM_XBAR + 8 * 8;
constexpr int SM_ONE = SM_MISC + 16;
constexpr int SM_ZERO = SM_ONE + 160;
constexpr int XCAP = 48;
constexpr int XSTR = 16 + 4 * XCAP;
constexpr int SM_XL = SM_ZERO + 160;
constexpr int SM_TOTAL = SM_XL + 8 * XSTR;
static_assert(SM_TOTAL <= 232448, "shared memory");

constexpr unsigned long long POL_EF = 0x12F0000000000000ull;
constexpr unsigned long long POL_EN = 0x16F0000000000000ull;

#define RT_MASK 0xF2E0u
#define RT_MASK2 0xEAE0u
#define WO_AT1 5
#define FFN_PROMO CU_TENSOR_MAP_L2_PROMOTION_NONE
#define FFN_POL POL_EF
#define HAS_FFN (__float_as_uint(misc[1]) < DN0 + NDN)
#define ACC_STR 1
#define NPRE 6

#define STAG 200
#define L1R 3
#define PRE1 13
#define HOLD 2
#define DNTH 23
constexpr int V0_AT = 8;
constexpr unsigned long long SEQ1 = 0x2765431076543210ull;
constexpr uint32_t IN_S1 = 0xAA49, IN_S0 = 0x124, PARITY1 = 0x6638, PARITY2 = 0xCE;
#define KEEP4 1
constexpr int NQ = 48;
constexpr int SPIN_CAP = 1 << 19;
constexpr uint32_t ONES = 0x3F803F80u;

struct alignas(1024) Scratch {
    uint4 hx[NCTA * 48];
    uint4 pad0[32 * 5 * 32 + 160];
    uint4 acc[2][216 * 8];
    uint4 ay[160];
    uint4 ah[NG * 8];
    uint2 mx[NH * 32];
    uint32_t ticket[32];
    uint32_t pad1[32];
};
__device__ Scratch g_scr;
#define PROF_T(i)
#define PROF_X(i)
#define PC(i)

__device__ __forceinline__ uint32_t smem_u32(const void* p) { return (uint32_t)__cvta_generic_to_shared(p); }
__device__ __forceinline__ void mbar_init(uint32_t bar, uint32_t cnt) {
    asm volatile("mbarrier.init.shared::cta.b64 [%0], %1;" ::"r"(bar), "r"(cnt) : "memory");
}
__device__ __forceinline__ void mbar_expect_tx(uint32_t bar, uint32_t bytes) {
    asm volatile("mbarrier.arrive.expect_tx.shared::cta.b64 _, [%0], %1;" ::"r"(bar), "r"(bytes) : "memory");
}
__device__ __forceinline__ bool mbar_test(uint32_t bar, uint32_t parity) {
    uint32_t done;
    asm volatile("{\n.reg .pred p;\nmbarrier.try_wait.parity.shared::cta.b64 p, [%1], %2;\nselp.u32 %0, 1, 0, p;\n}"
                 : "=r"(done) : "r"(bar), "r"(parity) : "memory");
    return done;
}
__device__ __forceinline__ void mbar_wait(uint32_t bar, uint32_t parity) {
    int it = 0;
    while (!mbar_test(bar, parity) && ++it < SPIN_CAP) {}
}
__device__ __forceinline__ void tma2d(uint32_t dst, const CUtensorMap* map, int c0, int c1, uint32_t bar, unsigned long long pol) {
    asm volatile("cp.async.bulk.tensor.2d.shared::cluster.global.mbarrier::complete_tx::bytes.L2::cache_hint [%0], [%1, {%3, %4}], [%2], %5;"
                 ::"r"(dst), "l"(map), "r"(bar), "r"(c0), "r"(c1), "l"(pol) : "memory");
}
__device__ __forceinline__ void tma3d(uint32_t dst, const CUtensorMap* map, int c0, int c1, int c2, uint32_t bar, unsigned long long pol) {
    asm volatile("cp.async.bulk.tensor.3d.shared::cluster.global.mbarrier::complete_tx::bytes.L2::cache_hint [%0], [%1, {%3, %4, %5}], [%2], %6;"
                 ::"r"(dst), "l"(map), "r"(bar), "r"(c0), "r"(c1), "r"(c2), "l"(pol) : "memory");
}
__device__ __forceinline__ void tile_load(uint32_t dst, const CUtensorMap* map, int row, uint32_t bar, uint32_t dep, uint32_t zero) {
    asm volatile("{\n.reg .pred p;\n.reg .b32 n;\nmad.lo.u32 n, %5, %6, 6144;\nelect.sync _|p, 0xffffffff;\n"
                 "@p mbarrier.arrive.expect_tx.shared::cta.b64 _, [%2], n;\n"
                 "@p cp.async.bulk.tensor.2d.shared::cluster.global.mbarrier::complete_tx::bytes.L2::cache_hint [%0], [%1, {0, %3}], [%2], %4;\n}"
                 ::"r"(dst), "l"(map), "r"(bar), "r"(row), "l"(POL_EF), "r"(dep), "r"(zero) : "memory");
}
__device__ __forceinline__ void tile_keep(const CUtensorMap* map, int row) {
    asm volatile("{\n.reg .pred p;\nelect.sync _|p, 0xffffffff;\n"
                 "@p cp.async.bulk.prefetch.tensor.2d.L2.global.L2::cache_hint [%0, {0, %1}], %2;\n}"
                 ::"l"(map), "r"(row), "l"(POL_EN) : "memory");
}
__device__ __forceinline__ void tile_load_l1(uint32_t dst, const void* base, int row, uint32_t bar, int lane) {
    const char* g = static_cast<const char*>(base) + (size_t)row * 128 + lane * 16;
    const uint32_t s0 = dst + (lane >> 3) * 128 + (((lane & 7) ^ (lane >> 3)) << 4), s1 = s0 ^ 64;
#pragma unroll
    for (int k = 0; k < 12; k++)
        asm volatile("cp.async.ca.shared.global.L2::cache_hint [%0], [%1], 16, %2;" ::"r"(((k & 1) ? s1 : s0) + k * 512), "l"(g + k * 512), "l"(POL_EF) : "memory");
    asm volatile("cp.async.mbarrier.arrive.shared::cta.b64 [%0];" ::"r"(bar) : "memory");
    __syncwarp();
    if (lane == 0) asm volatile("mbarrier.arrive.shared::cta.b64 _, [%0];" ::"r"(bar) : "memory");
}
__device__ __forceinline__ bool elect_one() {
    uint32_t p;
    asm volatile("{\n.reg .pred p;\nelect.sync _|p, 0xffffffff;\nselp.u32 %0, 1, 0, p;\n}" : "=r"(p));
    return p;
}
__device__ __forceinline__ void lds128(uint32_t addr, uint32_t& a, uint32_t& b, uint32_t& c, uint32_t& d) {
    asm volatile("ld.shared.v4.u32 {%0,%1,%2,%3}, [%4];" : "=r"(a), "=r"(b), "=r"(c), "=r"(d) : "r"(addr) : "memory");
}
__device__ __forceinline__ void lds128p(uint32_t addr, uint32_t on, uint32_t& a, uint32_t& b, uint32_t& c, uint32_t& d) {
    asm volatile("{\n.reg .pred p;\nsetp.ne.u32 p, %5, 0;\n@p ld.shared.v4.u32 {%0,%1,%2,%3}, [%4];\n}" : "+r"(a), "+r"(b), "+r"(c), "+r"(d) : "r"(addr), "r"(on) : "memory");
}
__device__ __forceinline__ void lds64(uint32_t addr, uint32_t& a, uint32_t& b) {
    asm volatile("ld.shared.v2.u32 {%0,%1}, [%2];" : "=r"(a), "=r"(b) : "r"(addr) : "memory");
}
__device__ __forceinline__ void ldsm4t(uint32_t addr, uint32_t (&a)[4]) {
    asm volatile("ldmatrix.sync.aligned.m8n8.x4.trans.shared.b16 {%0,%1,%2,%3}, [%4];" : "=r"(a[0]), "=r"(a[1]), "=r"(a[2]), "=r"(a[3]) : "r"(addr) : "memory");
}
__device__ __forceinline__ void mma16816(float (&c)[4], uint32_t a0, uint32_t a1, uint32_t a2, uint32_t a3, uint32_t b0, uint32_t b1) {
    asm("mma.sync.aligned.m16n8k16.row.col.f32.bf16.bf16.f32 {%0,%1,%2,%3}, {%4,%5,%6,%7}, {%8,%9}, {%0,%1,%2,%3};"
        : "+f"(c[0]), "+f"(c[1]), "+f"(c[2]), "+f"(c[3]) : "r"(a0), "r"(a1), "r"(a2), "r"(a3), "r"(b0), "r"(b1));
}
__device__ __forceinline__ void mma16816v(float (&c)[4], uint32_t a0, uint32_t a1, uint32_t a2, uint32_t a3, uint32_t b0, uint32_t b1) {
    asm volatile("mma.sync.aligned.m16n8k16.row.col.f32.bf16.bf16.f32 {%0,%1,%2,%3}, {%4,%5,%6,%7}, {%8,%9}, {%0,%1,%2,%3};"
        : "+f"(c[0]), "+f"(c[1]), "+f"(c[2]), "+f"(c[3]) : "r"(a0), "r"(a1), "r"(a2), "r"(a3), "r"(b0), "r"(b1));
}
__device__ __forceinline__ int xpos(int w) {
    const int seg = w / 40, r = w - 40 * seg;
    return 40 * seg + (r < 32 ? (r & 16) + 4 * (r & 3) + ((r >> 2) & 3) : 32 + 2 * (r & 3) + ((r >> 2) & 1));
}
#define NA_LD ""
#define NA_ST ""
__device__ __forceinline__ void st_pkt(uint4* p, uint32_t a, uint32_t b, uint32_t c, uint32_t d) {
    asm volatile("{\n.reg .b128 t;\n.reg .b64 lo, hi;\nmov.b64 lo, {%1,%2};\nmov.b64 hi, {%3,%4};\nmov.b128 t, {lo,hi};\nst.relaxed.gpu.global" NA_ST ".b128 [%0], t;\n}"
                 ::"l"(p), "r"(a), "r"(b), "r"(c), "r"(d) : "memory");
}
__device__ __forceinline__ void red_pkt(uint4* p, float a, float b, float c) {
    asm volatile("red.relaxed.gpu.global.add.v4.f32 [%0], {%1,%2,%3,%4};" ::"l"(p), "f"(a), "f"(b), "f"(c), "f"(1.0f) : "memory");
}
__device__ __forceinline__ void st_pktp(uint4* p, uint32_t a, uint32_t b, uint32_t c, uint32_t d, bool on) {
    asm volatile("{\n.reg .pred p;\n.reg .b128 t;\n.reg .b64 lo, hi;\nsetp.ne.u32 p, %5, 0;\nmov.b64 lo, {%1,%2};\nmov.b64 hi, {%3,%4};\nmov.b128 t, {lo,hi};\n"
                 "@p st.relaxed.gpu.global.b128 [%0], t;\n}" ::"l"(p), "r"(a), "r"(b), "r"(c), "r"(d), "r"((uint32_t)on) : "memory");
}
__device__ __forceinline__ void st_pktfp(uint4* p, float a, float b, float c, float d, uint32_t bit, bool on) {
    st_pktp(p, __float_as_uint(a), __float_as_uint(b), __float_as_uint(c), (__float_as_uint(d) & ~1u) | bit, on);
}
__device__ __forceinline__ uint4 ld_pkt(const uint4* p) {
    uint4 v;
    asm volatile("{\n.reg .b128 t;\n.reg .b64 lo, hi;\nld.relaxed.gpu.global" NA_LD ".b128 t, [%4];\nmov.b128 {lo,hi}, t;\nmov.b64 {%0,%1}, lo;\nmov.b64 {%2,%3}, hi;\n}"
                 : "=r"(v.x), "=r"(v.y), "=r"(v.z), "=r"(v.w) : "l"(p) : "memory");
    return v;
}
__device__ __forceinline__ uint2 ld_pkt2(const uint2* p) {
    unsigned long long v;
    asm volatile("ld.relaxed.gpu.global" NA_LD ".b64 %0, [%1];" : "=l"(v) : "l"(p) : "memory");
    return make_uint2((uint32_t)v, (uint32_t)(v >> 32));
}
__device__ __forceinline__ void st_pkt2(uint2* p, uint32_t a, uint32_t b) {
    asm volatile("st.relaxed.gpu.global" NA_ST ".b64 [%0], %1;" ::"l"(p), "l"((unsigned long long)a | ((unsigned long long)b << 32)) : "memory");
}
__device__ __forceinline__ float ex2(float x) { float y; asm("ex2.approx.ftz.f32 %0, %1;" : "=f"(y) : "f"(x)); return y; }
__device__ __forceinline__ float rcp(float x) { float y; asm("rcp.approx.ftz.f32 %0, %1;" : "=f"(y) : "f"(x)); return y; }
__device__ __forceinline__ uint32_t pack2(float lo, float hi) {
    uint32_t r; asm("cvt.rn.bf16x2.f32 %0, %1, %2;" : "=r"(r) : "f"(hi), "f"(lo)); return r;
}
__device__ __forceinline__ float bf_lo(uint32_t w) { return __uint_as_float(w << 16); }
__device__ __forceinline__ float bf_hi(uint32_t w) { return __uint_as_float(w & 0xffff0000u); }
__device__ __forceinline__ float bfr(float x) { return bf_lo(pack2(x, 0.f)); }
__device__ __forceinline__ float f_(uint32_t u) { return __uint_as_float(u); }

template <int SK, typename AddrF>
__device__ __forceinline__ void gemv15(float (&cc)[3][4], uint32_t (&pre)[6][4], AddrF ad, uint32_t px, uint32_t px2, float& sv, float so) {
    uint32_t x0[4], x1[4], a[3][4];
    asm volatile("ld.shared.v4.u32 {%0,%1,%2,%3}, [%20];\nld.shared.v4.u32 {%4,%5,%6,%7}, [%20+64];\n"
                 "ldmatrix.sync.aligned.m8n8.x4.trans.shared.b16 {%8,%9,%10,%11}, [%21];\n"
                 "ldmatrix.sync.aligned.m8n8.x4.trans.shared.b16 {%12,%13,%14,%15}, [%22];\n"
                 "ldmatrix.sync.aligned.m8n8.x4.trans.shared.b16 {%16,%17,%18,%19}, [%23];\nbar.warp.sync 0xffffffff;"
                 : "=r"(x0[0]), "=r"(x0[1]), "=r"(x0[2]), "=r"(x0[3]), "=r"(x1[0]), "=r"(x1[1]), "=r"(x1[2]), "=r"(x1[3]),
                   "=r"(a[0][0]), "=r"(a[0][1]), "=r"(a[0][2]), "=r"(a[0][3]), "=r"(a[1][0]), "=r"(a[1][1]), "=r"(a[1][2]), "=r"(a[1][3]),
                   "=r"(a[2][0]), "=r"(a[2][1]), "=r"(a[2][2]), "=r"(a[2][3])
                 : "r"(px), "r"(ad(0) + 2 * SK), "r"(ad(1) + 2 * SK), "r"(ad(2) + 2 * SK) : "memory");
    __syncwarp();
    sv += __shfl_xor_sync(0xffffffffu, so, 16);
#pragma unroll
    for (int i = 0; i < 3; i++) {
        cc[i][0] = cc[i][1] = cc[i][2] = cc[i][3] = 0.f;
        mma16816v(cc[i], pre[i][0], pre[i][1], pre[i][2], pre[i][3], x0[0], x0[1]);
    }
    sv += __shfl_xor_sync(0xffffffffu, sv, 8);
#pragma unroll
    for (int i = 0; i < 3; i++) {
        mma16816v(cc[i], pre[3 + i][0], pre[3 + i][1], pre[3 + i][2], pre[3 + i][3], x0[2], x0[3]);
        ldsm4t(ad(i) + 3 * SK, pre[i]);
    }
    lds64(px2, x0[0], x0[1]);
    __syncwarp();
    sv += __shfl_xor_sync(0xffffffffu, sv, 4);
#pragma unroll
    for (int i = 0; i < 3; i++) {
        mma16816v(cc[i], a[i][0], a[i][1], a[i][2], a[i][3], x1[0], x1[1]);
        ldsm4t(ad(i) + 4 * SK, pre[3 + i]);
    }
    __syncwarp();
    sv += __shfl_xor_sync(0xffffffffu, sv, 2);
#pragma unroll
    for (int i = 0; i < 3; i++) mma16816v(cc[i], pre[i][0], pre[i][1], pre[i][2], pre[i][3], x1[2], x1[3]);
    sv += __shfl_xor_sync(0xffffffffu, sv, 1);
#pragma unroll
    for (int i = 0; i < 3; i++) mma16816v(cc[i], pre[3 + i][0], pre[3 + i][1], pre[3 + i][2], pre[3 + i][3], x0[0], x0[1]);
}
__device__ __forceinline__ void gemv15r(float (&cc)[3][4], const uint32_t (&pre)[6][4], const uint32_t (&ext)[NQ][4], uint32_t px, uint32_t px2, float& sv, float so) {
    uint32_t x0[4], x1[4], x2[2];
    float cd[3][4];
    lds128(px, x0[0], x0[1], x0[2], x0[3]);
    lds128(px + 64, x1[0], x1[1], x1[2], x1[3]);
    lds64(px2, x2[0], x2[1]);
    sv += __shfl_xor_sync(0xffffffffu, so, 16);
#pragma unroll
    for (int i = 0; i < 3; i++) {
        cc[i][0] = cc[i][1] = cc[i][2] = cc[i][3] = cd[i][0] = cd[i][1] = cd[i][2] = cd[i][3] = 0.f;
        mma16816v(cc[i], pre[i][0], pre[i][1], pre[i][2], pre[i][3], x0[0], x0[1]);
        mma16816v(cd[i], pre[3 + i][0], pre[3 + i][1], pre[3 + i][2], pre[3 + i][3], x0[2], x0[3]);
    }
    sv += __shfl_xor_sync(0xffffffffu, sv, 8);
#pragma unroll
    for (int i = 0; i < 3; i++) {
        mma16816v(cc[i], ext[i][0], ext[i][1], ext[i][2], ext[i][3], x1[0], x1[1]);
        mma16816v(cd[i], ext[3 + i][0], ext[3 + i][1], ext[3 + i][2], ext[3 + i][3], x1[2], x1[3]);
    }
    sv += __shfl_xor_sync(0xffffffffu, sv, 4);
#pragma unroll
    for (int i = 0; i < 3; i++) mma16816v(cc[i], ext[6 + i][0], ext[6 + i][1], ext[6 + i][2], ext[6 + i][3], x2[0], x2[1]);
    sv += __shfl_xor_sync(0xffffffffu, sv, 2);
    sv += __shfl_xor_sync(0xffffffffu, sv, 1);
#pragma unroll
    for (int i = 0; i < 3; i++) { cc[i][0] += cd[i][0]; cc[i][1] += cd[i][1]; cc[i][2] += cd[i][2]; cc[i][3] += cd[i][3]; }
}

__device__ __forceinline__ float warp_max(float x) {
    int i = __float_as_int(x);
    i = __reduce_max_sync(0xffffffffu, i ^ ((i >> 31) & 0x7fffffff));
    return __int_as_float(i ^ ((i >> 31) & 0x7fffffff));
}
__device__ __forceinline__ void idle(uint32_t clk) {
    uint32_t t0, t;
    asm volatile("mov.u32 %0, %%clock;" : "=r"(t0) :: "memory");
    do asm volatile("mov.u32 %0, %%clock;" : "=r"(t) :: "memory"); while (t - t0 < clk);
}
__device__ __forceinline__ uint32_t now_ns() { uint32_t t; asm volatile("mov.u32 %0, %%globaltimer_lo;" : "=r"(t)); return t; }
__device__ __forceinline__ int opq(int x) { asm volatile("" : "+r"(x)); return x; }
__device__ __forceinline__ uint32_t opq(uint32_t x) { asm volatile("" : "+r"(x)); return x; }
__device__ __forceinline__ uint32_t pin(uint32_t x) { return __shfl_sync(0xffffffffu, x, threadIdx.x & 31); }
template <typename T> __device__ __forceinline__ T* pin(T* p) {
    const unsigned long long v = (unsigned long long)p;
    return (T*)((unsigned long long)pin((uint32_t)v) | (unsigned long long)pin((uint32_t)(v >> 32)) << 32);
}
template <typename T> __device__ __forceinline__ T* opq(T* p) { asm volatile("" : "+l"(p)); return p; }
__device__ __forceinline__ float4 lds4f(uint32_t a) { float4 v; asm volatile("ld.shared.v4.f32 {%0,%1,%2,%3}, [%4];" : "=f"(v.x), "=f"(v.y), "=f"(v.z), "=f"(v.w) : "r"(a) : "memory"); return v; }
__device__ __forceinline__ float2 lds2f(uint32_t a) { float2 v; asm volatile("ld.shared.v2.f32 {%0,%1}, [%2];" : "=f"(v.x), "=f"(v.y) : "r"(a) : "memory"); return v; }
__device__ __forceinline__ void ln_stats(uint32_t st, float& mean, float& inv) {
    const float4 a = lds4f(st), b = lds4f(st + 16), c = lds4f(st + 32), d = lds4f(st + 48);
    const float s2 = ((a.x + a.z) + (b.x + b.z)) + ((c.x + c.z) + (d.x + d.z));
    const float md = (((a.y + a.w) + (b.y + b.w)) + ((c.y + c.w) + (d.y + d.w))) * (1.0f / DM);
    const float var = fmaxf(s2 * (1.0f / DM) - md * md, 0.f);
    mean = bfr(md);
    asm("rsqrt.approx.ftz.f32 %0, %1;" : "=f"(inv) : "f"(var + 1e-5f));
}
__device__ __forceinline__ void sts32(uint32_t a, float v) { asm volatile("st.shared.f32 [%0], %1;" ::"r"(a), "f"(v) : "memory"); }
__device__ __forceinline__ void sts32p(uint32_t a, float v, uint32_t off) {
    asm volatile("{\n.reg .pred p;\nsetp.eq.u32 p, %2, 0;\n@p st.shared.f32 [%0], %1;\n}" ::"r"(a), "f"(v), "r"(off) : "memory");
}
__device__ __forceinline__ void sts128p(uint32_t a, float x, float y, float z, float w, uint32_t off) {
    asm volatile("{\n.reg .pred p;\nsetp.eq.u32 p, %5, 0;\n@p st.shared.v4.f32 [%0], {%1,%2,%3,%4};\n}" ::"r"(a), "f"(x), "f"(y), "f"(z), "f"(w), "r"(off) : "memory");
}
__device__ __forceinline__ void sts64(uint32_t a, float v, float w) { asm volatile("st.shared.v2.f32 [%0], {%1,%2};" ::"r"(a), "f"(v), "f"(w) : "memory"); }

__device__ __forceinline__ uint32_t prmt(uint32_t a, uint32_t b, uint32_t s) { uint32_t r; asm("prmt.b32 %0, %1, %2, %3;" : "=r"(r) : "r"(a), "r"(b), "r"(s)); return r; }
__device__ __forceinline__ uint32_t bmul2(uint32_t a, uint32_t b) { uint32_t r; asm("mul.rn.bf16x2 %0, %1, %2;" : "=r"(r) : "r"(a), "r"(b)); return r; }
__device__ __forceinline__ void sts128(uint32_t addr, uint32_t a, uint32_t b, uint32_t c, uint32_t d) {
    asm volatile("st.shared.v4.u32 [%0], {%1,%2,%3,%4};" ::"r"(addr), "r"(a), "r"(b), "r"(c), "r"(d) : "memory");
}
__device__ __forceinline__ uint4 ldg128(const uint4* p) {
    uint4 v;
    asm volatile("ld.volatile.global.v4.u32 {%0,%1,%2,%3}, [%4];" : "=r"(v.x), "=r"(v.y), "=r"(v.z), "=r"(v.w) : "l"(p) : "memory");
    return v;
}
__device__ __forceinline__ uint32_t lds32(uint32_t a) { uint32_t v; asm volatile("ld.shared.u32 %0, [%1];" : "=r"(v) : "r"(a) : "memory"); return v; }
__device__ __forceinline__ uint32_t lds16(uint32_t a) { unsigned short v; asm volatile("ld.shared.u16 %0, [%1];" : "=h"(v) : "r"(a) : "memory"); return v; }
__device__ __forceinline__ void unpack8(uint32_t la, uint32_t lb, uint32_t c, uint32_t (&w)[4]) {
    const uint32_t ha = c & 0x87878787u, hb = __funnelshift_l(c, c, 4) & 0x87878787u;
    w[0] = prmt(la, ha, 0x5140); w[1] = prmt(la, ha, 0x7362); w[2] = prmt(lb, hb, 0x5140); w[3] = prmt(lb, hb, 0x7362);
}
__device__ __forceinline__ uint32_t bdiff2(uint32_t y, uint32_t inv, uint32_t x) {
    uint32_t r;
    asm("{\n.reg .b32 n;\nneg.bf16x2 n, %3;\nfma.rn.bf16x2 %0, %1, %2, n;\n}" : "=r"(r) : "r"(y), "r"(inv), "r"(x));
    return r;
}
__device__ __forceinline__ uint32_t pack_scale(uint32_t tile, int lane, uint32_t inv_addr) {
    uint32_t m = 0;
#pragma unroll 1
    for (int k = 0; k < 12; k++) {
        uint32_t a, b, c, d;
        lds128(tile + k * 512 + lane * 16, a, b, c, d);
        asm("max.xorsign.abs.bf16x2 %0, %0, %1;" : "+r"(a) : "r"(b));
        asm("max.xorsign.abs.bf16x2 %0, %0, %1;" : "+r"(c) : "r"(d));
        asm("max.xorsign.abs.bf16x2 %0, %0, %1;" : "+r"(a) : "r"(c));
        asm("max.xorsign.abs.bf16x2 %0, %0, %1;" : "+r"(m) : "r"(a));
    }
    m = __reduce_max_sync(0xffffffffu, max(m & 0x7fffu, (m >> 16) & 0x7fffu));
    const uint32_t inv = (112u + min((m + 0x28u) >> 7, 141u)) * 0x00800080u;
    if (lane == 0) asm volatile("st.shared.u32 [%0], %1;" ::"r"(inv_addr), "r"(inv) : "memory");
    return inv;
}

#define K_OFF(i) ((uint32_t)((3 * ((g >> 1) + 4 * (g & 1)) + ((i) >> 1)) * 128 + ((t ^ ((3 * ((g >> 1) + 4 * (g & 1)) + ((i) >> 1)) & 7) ^ (((i) & 1) << 2)) << 4)))
#define V_OFF(i) ((uint32_t)((6 * t + (i)) * 128 + ((g ^ ((6 * t + (i)) & 7)) << 4)))
template <bool ISV, typename DST>
__device__ __forceinline__ void pack_tile(uint32_t tile, int tau, int nm, uint32_t inv, uint32_t xl, int lane, DST dst) {
    const int g = lane >> 2, t = lane & 3;
    const uint32_t scl = 254u * 0x00800080u - inv;
#pragma unroll 1
    for (int m = 0; m < nm; m++) {
        const int row = ISV ? 6 * t + 2 * m : 3 * ((g >> 1) + 4 * (g & 1)) + m;
        const uint32_t a0 = tile + row * 128 + (((ISV ? g : t) ^ (row & 7)) << 4), a1 = ISV ? (a0 ^ 16) + 128 : a0 ^ 64;
        uint32_t l[8], cw[4], ck = 0, cd = 0;
#pragma unroll
        for (int r = 0; r < 4; r++) {
            uint32_t w0, w1, w2, w3;
            lds128(((r & 1) ? a1 : a0) + (r >> 1) * 3072, w0, w1, w2, w3);
            const uint32_t y0 = bmul2(w0, scl), y1 = bmul2(w1, scl), y2 = bmul2(w2, scl), y3 = bmul2(w3, scl);
            cd |= bdiff2(y0, inv, w0) | bdiff2(y1, inv, w1);
            cd |= bdiff2(y2, inv, w2) | bdiff2(y3, inv, w3);
            const uint32_t ha = prmt(y0, y1, 0x7531), hb = prmt(y2, y3, 0x7531);
            l[2 * r] = prmt(y0, y1, 0x6420); l[2 * r + 1] = prmt(y2, y3, 0x6420);
            asm("lop3.b32 %0, %1, 0x87878787, %2, 0xe2;" : "=r"(cw[r]) : "r"(ha), "r"(__funnelshift_r(hb, hb, 4)));
            ck |= ha | hb;
        }
        const uint32_t bad = __ballot_sync(0xffffffffu, (ck & 0x78787878u) | cd);
        if (bad) {
            const int src = __ffs(bad) - 1;
            const uint32_t b0 = __shfl_sync(0xffffffffu, a0, src), b1 = __shfl_sync(0xffffffffu, a1, src), n0 = lds32(xl);
            const uint32_t ax = ((lane & 8) ? b1 : b0) + (lane >> 4) * 3072 + 2 * (lane & 7), x = lds16(ax), y = bmul2(x, scl);
            const bool out = (y & 0x7800u) | bdiff2(y, inv, x);
            const uint32_t n = n0 + __popc(__ballot_sync(0xffffffffu, out) << (31 - lane)) - 1;
            if (out) {
                asm volatile("st.shared.u16 [%0], %1;" ::"r"(ax), "h"((unsigned short)0) : "memory");
                if (n < XCAP) sts32(xl + 16 + 4 * n, f_(x << 16 | tau << 12 | src << 7 | m << 5 | lane));
            }
            if (lane == 31) sts32(xl, f_(n + 1));
            __syncwarp();
            if (n0 <= XCAP) { m--; continue; }
        }
        uint32_t d[3] = {a0, a1, a0 + 3072};
        dst(m, d);
        sts128(d[0], l[0], l[1], l[2], l[3]);
        sts128(d[1], l[4], l[5], l[6], l[7]);
        sts128(d[2], cw[0], cw[1], cw[2], cw[3]);
    }
}

struct Maps { CUtensorMap k, v, wq, wo, w1, w3, w2, vr; const void* vp; const void* kp; uint32_t zero; };
#define RT_SEL ((wu & 1) ? RT_MASK2 : RT_MASK)
#define PFK 5
#define Q_AT 3
#define WO_T0 32200
#define K5D 370
#define PK_AT 6

__device__ __forceinline__ void load_ffn(const Maps& maps, int b, uint32_t dst, uint32_t bar) {
    const bool gu = b < NG;
    mbar_expect_tx(bar, gu ? 61440 : 49152);
    tma3d(dst, gu ? (b < NG / 2 ? &maps.w1 : &maps.w3) : &maps.w2, gu ? 48 * (b & (NG / 2 - 1)) : 16 * (b - DN0), 0, 0, bar, FFN_POL);
}

__device__ __forceinline__ void load_wo(const Maps& maps, uint32_t dst, int h, int c, uint32_t bar, int nbox) {
#pragma unroll 1
    for (int i = 0; i < nbox; i++) {
        if (!(i & 1)) mbar_expect_tx(bar + 4 * i, i + 1 < nbox ? 20480 : 10240);
        tma3d(dst + i * 10240, &maps.wo, 0, 5 * c, h * DH + 32 * i, bar + 4 * (i & 6), POL_EF);
    }
}

__global__ void __launch_bounds__(NT, 1)
decode_kernel(const __grid_constant__ Maps maps, const __nv_bfloat16* __restrict__ x_in, __nv_bfloat16* __restrict__ out) {
    extern __shared__ __align__(1024) unsigned char smem[];
    const int tid = threadIdx.x, warp = tid >> 5, lane = tid & 31;
    const int wu = __shfl_sync(0xffffffffu, tid >> 5, 0);
    const int b = blockIdx.x, h = b >> 2, c = b & 3;
    const uint32_t sb = smem_u32(smem);
    const uint32_t qbar = sb + SM_BAR + 16 * 8, fbar = qbar + 8, wbar = qbar + 16;
    uint32_t* xs32 = reinterpret_cast<uint32_t*>(smem + SM_XS);
    float* rr = reinterpret_cast<float*>(smem + SM_R);
    float* misc = reinterpret_cast<float*>(smem + SM_MISC);

    PROF_T(0);
    {
        uint2 xv = make_uint2(0u, 0u);
        const uint32_t t_start = now_ns();
        if (elect_one()) {
            const uint32_t rb = sb + SM_BAR + wu * 16, xb = sb + SM_XBAR + wu * 8;
            mbar_init(rb, 1); mbar_init(rb + 8, 1); mbar_init(xb, 1);
            if (wu == 0) mbar_init(qbar, 1);
            asm volatile("fence.mbarrier_init.release.cluster;" ::: "memory");
            const int row = (h * SK + (SK - WIN) + c * 1024 + wu * 128) * 3;
            const uint32_t ring = sb + SM_RING + wu * 2 * TILE;
#pragma unroll
            for (int n = 0; n < 3; n++) {
                const uint32_t bar = ((IN_S1 >> n) & 1) ? rb + 8 : ((IN_S0 >> n) & 1) ? rb : xb;
                mbar_expect_tx(bar, TILE);
                tma2d(((IN_S1 >> n) & 1) ? ring + TILE : ((IN_S0 >> n) & 1) ? ring : sb + SM_B + wu * TILE, &maps.k, 0, row + 48 * n, bar, POL_EF);
                if (n == 0 && wu == 0) {
                    mbar_expect_tx(qbar, 61440);
                    tma3d(sb + SM_Q, &maps.wq, 0, 160 * c, 3 * h, qbar, POL_EF);
                }
            }
            if (wu == 1) {
                mbar_init(fbar, 1);
#pragma unroll
                for (int i = 0; i < 3; i++) mbar_init(wbar + 8 * i, 1);
                asm volatile("fence.mbarrier_init.release.cluster;" ::: "memory");
            }
            if (wu >= 2) {
                const CUtensorMap* mp = wu == 2 ? &maps.v : wu == 3 ? &maps.wo : wu == 4 ? &maps.w1 : wu == 5 ? &maps.w3 : wu == 6 ? &maps.w2 : &maps.vr;
                asm volatile("prefetch.tensormap [%0];" ::"l"(mp) : "memory");
            }
        }
        if (tid < 160) asm volatile("ld.global.nc.v2.u32 {%0,%1}, [%2];" : "=r"(xv.x), "=r"(xv.y) : "l"(x_in + 4 * tid) : "memory");
        if (tid == 96) { misc[2] = 0.f; misc[3] = 0.f; }
        if (lane == 1) *reinterpret_cast<uint2*>(smem + SM_XL + warp * XSTR) = make_uint2(0u, t_start + WO_T0);
        if (tid >= 128 && tid < 148) {
            const uint32_t v = tid < 138 ? ONES : 0u;
            reinterpret_cast<uint4*>(smem + SM_ONE)[tid - 128] = make_uint4(v, v, v, v);
        }
        if (tid < 160) { xs32[xpos(2 * tid)] = xv.x; xs32[xpos(2 * tid + 1)] = xv.y; }
        __syncthreads();
        PROF_T(14);
        if (b == 0 && tid >= 232) asm volatile("st.relaxed.gpu.global.u32 [%0], %1;" ::"l"(g_scr.ticket + tid - 232), "r"(0) : "memory");
        if (tid == 64 || (tid == 65 && b < 216 - NCTA)) st_pkt(&g_scr.acc[1][(b + NCTA * (tid - 64)) * ACC_STR], 0, 0, 0, 0);
    }

    uint32_t kq[NQ][4];
    const float SC = 0.07216878364870322f * 1.4426950408889634f;

#pragma unroll 1
    for (int ph = 0; ph < 3; ph++) {
        const int layer = ph >> 1;
        const uint32_t tag = layer + 1;
        PROF_T(1 + layer * 16);
        if (ph) {
        {
            const int tl = opq(tid), warp = tl >> 5, lane = tl & 31, g = lane >> 2, t = lane & 3, mat = lane >> 3, r8 = lane & 7;
            const int kh = warp >> 2, mg = warp & 3;
            uint32_t aq[3];
#pragma unroll
            for (int i = 0; i < 3; i++) {
                const int ch = 6 * mg + 2 * i + (mat & 1);
                aq[i] = sb + SM_Q + (80 * kh + (mat >> 1) * 8 + r8) * 128 + (ch >> 3) * 20480 + (((ch & 7) ^ r8) << 4);
            }
#define PF_K5 if (layer == 1 && PFK) tile_keep(&maps.k, (h * SK + (SK - WIN) + c * 1024 + wu * 128 + PFK * 16) * 3);
            uint2 xv = make_uint2(0u, 0u);
            mbar_wait(qbar, 0);
            uint32_t pre[6][4];
#pragma unroll
            for (int n = 0; n < 6; n++) ldsm4t(aq[n % 3] + (n / 3) * 2048, pre[n]);
            if (layer == 1) {
                __syncthreads();
                if (elect_one()) {
                    const uint32_t bar = sb + SM_BAR + wu * 16;
                    asm volatile("mbarrier.expect_tx.relaxed.cta.shared::cta.b64 [%0], 1536;" ::"r"(bar) : "memory");
#pragma unroll
                    for (int k = 0; k < 3; k++)
                        tma2d(sb + SM_Q + v1_pos(3 * wu + k), &maps.vr, 0, (h * SK + (SK - WIN) + c * 1024 + wu * 128) / 2 + 8 + 2 * k, bar, POL_EF);
                }
            }
            const uint32_t pm = opq(g == 1 ? sb + SM_ONE : sb + SM_XS + 160 * (2 * c + kh) + 16 * t), pm2 = opq(pm + 128 - (g == 1 ? 0 : 8 * t));
            const uint32_t dq = opq(sb + SM_R + 8 * (kh * 192 + 48 * mg + g)), ds = opq(sb + SM_ST + 8 * warp + (lane < 16 ? 4 : 0));
            const bool wr = t == 0, ws = (lane & 15) == 0, lo = lane < 16;
            if (wu < 5) {
                const int p0 = xpos(2 * tl), p1 = xpos(2 * tl + 1);
                if (layer == 1) {
                    uint4 v;
                    int it = 0;
                    do { v = ld_pkt(&g_scr.ay[tl]); } while (!__all_sync(0xffffffffu, v.w == 1) && ++it < SPIN_CAP);
                    xv = make_uint2(v.x, v.y);
                    xs32[p0] = xv.x; xs32[p1] = xv.y;
                } else xv = make_uint2(xs32[p0], xs32[p1]);
            }
            if (layer) PC(24);
            if (layer) __syncthreads();
            PF_K5
            if (layer) PC(25);
            PROF_T(13 + layer * 16);
            const float e0 = bf_lo(xv.x), e1 = bf_hi(xv.x), e2 = bf_lo(xv.y), e3 = bf_hi(xv.y);
            const float s1 = (e0 + e1) + (e2 + e3), s2 = (e0 * e0 + e1 * e1) + (e2 * e2 + e3 * e3);
            float sv = lo ? s1 : s2, cc[3][4];
            gemv15<2048>(cc, pre, [&](int i) { return aq[i]; }, pm, pm2, sv, lo ? s2 : s1);
            if (wr) {
#pragma unroll
                for (int i = 0; i < 3; i++) { sts64(dq + 128 * i, cc[i][0], cc[i][1]); sts64(dq + 128 * i + 64, cc[i][2], cc[i][3]); }
            }
            if (ws) sts32(ds, sv);
        }
        const uint32_t pa = opq(sb + SM_R + 32 * opq(tid)), st = opq(sb + SM_ST);
        uint4* const pq = opq(&g_scr.hx[b * 48 + opq(tid)]);
        if (layer) PC(26);
        __syncthreads();
        if (layer) PC(27);
        PROF_T(33 + layer * 16);
        if (wu < 2) {
            float mean, inv;
            ln_stats(st, mean, inv);
            const float4 a0 = lds4f(pa), a1 = lds4f(pa + 16), b0 = lds4f(pa + 1536), b1 = lds4f(pa + 1552);
            float q0 = inv * ((a0.x + b0.x) - mean * (a0.y + b0.y)), q1 = inv * ((a0.z + b0.z) - mean * (a0.w + b0.w));
            float q2 = inv * ((a1.x + b1.x) - mean * (a1.y + b1.y)), q3 = inv * ((a1.z + b1.z) - mean * (a1.w + b1.w));
            st_pktfp(pq, q0, q1, q2, q3, 1, tid < 48);
        }
        if (layer == 1 && tid >= 192 && tid < 194 && b < 108) st_pkt(&g_scr.acc[0][(2 * b + opq(tid) - 192) * ACC_STR], 0, 0, 0, 0);
        }
        if (layer) PC(28);
        if (layer == 1 && (wu & 2)) {
            idle(K5D);
#pragma unroll 1
            for (int w = wu; w >= (wu > 4 ? wu - 2 : wu); w -= 2)
                tile_load(sb + SM_Q + c_slot(w), &maps.k, (h * SK + (SK - WIN) + c * 1024 + w * 128 + 5 * 16) * 3, sb + SM_XBAR + w * 8, 0, 0);
        }

        float sc0 = -INFINITY, sc1 = -INFINITY, sc2 = 0.f, sc3 = 0.f, mw;
        uint32_t pk0, pk1;
        float acc[3][4];
        {
            const uint32_t ring = sb + SM_RING + wu * 2 * TILE, rb = sb + SM_BAR + wu * 16;
            const uint32_t xtile = sb + SM_Q + c_slot(wu), xb = sb + SM_XBAR + wu * 8;
#define V_SEQ(n) ((int)(SEQ1 >> (4 * (n))) & 7)
#define SLOT1(n) (((IN_S1 >> (n)) & 1) ? ring + TILE : ((IN_S0 >> (n)) & 1) ? ring : sb + SM_B + wu * TILE)
#define BAR1(n) (((IN_S1 >> (n)) & 1) ? rb + 8 : ((IN_S0 >> (n)) & 1) ? rb : xb)
#define PAR1(n) ((PARITY1 >> (n)) & 1)
#define PAR2(n) ((PARITY2 >> (n)) & 1)
            const int row0 = (h * SK + (SK - WIN) + c * 1024 + wu * 128) * 3;
            auto issue1 = [&](int n, uint32_t dep, bool vph = false) {
                const CUtensorMap* mp = n < 8 ? &maps.k : &maps.v;
                const int tl = V_SEQ(n), row = row0 + tl * 48;
                const uint32_t dst = SLOT1(n), bar = BAR1(n);
                if (vph && wu < L1R && tl == 7 - (wu & 1)) {
                    tile_load_l1(dst, maps.vp, row, bar, opq(tid) & 31);
                    return;
                }
                tile_load(dst, mp, row, bar, dep, maps.zero);
                if ((RT_SEL >> (tl + (n & 8))) & 1) {
                    if (n != V0_AT + 1) tile_keep(mp, row);
                    else if ((opq(tid) & 31) < 8)
                        asm volatile("cp.async.bulk.prefetch.L2.global.L2::cache_hint [%0], 256, %1;"
                                     ::"l"(static_cast<const char*>(maps.vp) + (size_t)(row + 4 + 6 * (opq(tid) & 31)) * 128), "l"(POL_EN) : "memory");
                }
            };
            auto refill1 = [&](int s, uint32_t dep, bool vph = false) { issue1(s + (!vph || s < V0_AT ? 3 : 2), dep, vph); };
#define LANE_IDS const int tl = opq(tid), lane = tl & 31, g = lane >> 2, t = lane & 3; (void)tl; (void)lane; (void)g; (void)t;
            const uint32_t xl = sb + SM_XL + wu * XSTR;
            if (layer == 0) {
#pragma unroll 1
                for (int s = ph ? Q_AT : 0; s < (ph ? 5 : Q_AT); s++) {
                    LANE_IDS
                    const uint32_t tile = SLOT1(s);
                    mbar_wait(BAR1(s), PAR1(s));
                    const uint32_t scl = s == 0 ? pack_scale(tile, lane, xl + 8) : lds32(xl + 8);
                    pack_tile<false>(tile, s, 3, scl, xl, lane, [](int, uint32_t (&)[3]) {});
#pragma unroll
                    for (int n = 0; n < 5; n++) {
                        if (s == n) {
#pragma unroll
                            for (int m = 0; m < 3; m++) {
                                const uint32_t a = tile + K_OFF(2 * m);
                                lds128(a, kq[9 * n + 3 * m][0], kq[9 * n + 3 * m][1], kq[9 * n + 3 * m][2], kq[9 * n + 3 * m][3]);
                                lds128(a ^ 64, kq[9 * n + 3 * m + 1][0], kq[9 * n + 3 * m + 1][1], kq[9 * n + 3 * m + 1][2], kq[9 * n + 3 * m + 1][3]);
                                lds128(a + 3072, kq[9 * n + 3 * m + 2][0], kq[9 * n + 3 * m + 2][1], kq[9 * n + 3 * m + 2][2], kq[9 * n + 3 * m + 2][3]);
                            }
                        }
                    }
                    __syncwarp();
                    refill1(s, lds32(tile));
                }
                if (!ph) continue;
            }
            {
                const int tl = opq(tid);
                if (tl < 48) {
                    const int w = 2 * tl;
                    const uint32_t pos = opq(sb + SM_QS + 4 * (((w >> 2) & 3) * 24 + 2 * (w >> 4) + ((w >> 1) & 1)));
                    uint4 v[4];
                    int it = 0;
                    bool ok;
                    do {
#pragma unroll
                        for (int k = 0; k < 4; k++) v[k] = ld_pkt(&g_scr.hx[(h * 4 + k) * 48 + tl]);
                        ok = ~((v[0].w & v[1].w) & (v[2].w & v[3].w)) & 1;
                    } while (ok && ++it < SPIN_CAP);
                    sts32(pos, f_(pack2((f_(v[0].x) + f_(v[1].x)) + (f_(v[2].x) + f_(v[3].x)), (f_(v[0].y) + f_(v[1].y)) + (f_(v[2].y) + f_(v[3].y)))));
                    sts32(pos + 48, f_(pack2((f_(v[0].z) + f_(v[1].z)) + (f_(v[2].z) + f_(v[3].z)), (f_(v[0].w) + f_(v[1].w)) + (f_(v[2].w) + f_(v[3].w)))));
                }
            }
            if (layer) PC(29);
            __syncthreads();
            if (layer) PC(30);
            PROF_T(2 + layer * 16);
#define V1_REST(p) ((p) < 6 ? sb + SM_Q + v1_pos(3 * wu + ((p) >> 1)) + 256 * ((p) & 1) : ((sb + SM_R + wu * 784 + 127) & ~127u) - 1536 + 256 * (p))
#define V1_LOAD(bar) if (elect_one()) tma2d(V1_REST(6), &maps.vr, 0, row0 / 6 + 14, bar, POL_EF);
#define V1_EXPECT(bar) { if ((opq(tid) & 31) == 0) asm volatile("mbarrier.expect_tx.relaxed.cta.shared::cta.b64 [%0], 512;" ::"r"(bar) : "memory"); }
            if (layer == 1 && wu < 2) tile_load(xtile, &maps.k, row0 + 5 * 48, xb, 0, 0);
            if (layer == 1 && wu >= 4) idle(STAG);
            {
                uint32_t qf[12];
                int t;
                {
                    const int lane = opq(tid) & 31;
                    t = lane & 3;
                    const uint32_t qa = sb + SM_QS + (2 * t + ((lane >> 2) & 1)) * 48;
#pragma unroll
                    for (int i = 0; i < 3; i++) lds128(qa + 16 * i, qf[4 * i], qf[4 * i + 1], qf[4 * i + 2], qf[4 * i + 3]);
                }
                const uint32_t sq = lds32(xl + 8) - 64u * 0x00800080u;
#pragma unroll
                for (int i = 0; i < 12; i++) qf[i] = bmul2(qf[i], sq);
#define KR_STEP(tau, m) \
                    _Pragma("unroll") for (int i = 2 * (m); i < 2 * (m) + 2; i++) { \
                        const int q0 = 9 * tau + 3 * (i >> 1), r = i & 1; \
                        uint32_t w[4]; \
                        unpack8(kq[q0][2 * r], kq[q0][2 * r + 1], kq[q0 + 2][r], w); \
                        mma16816(cA, w[0], w[1], w[2], w[3], qf[2 * i], qf[2 * i + 1]); \
                        unpack8(kq[q0 + 1][2 * r], kq[q0 + 1][2 * r + 1], kq[q0 + 2][2 + r], w); \
                        mma16816(cB, w[0], w[1], w[2], w[3], qf[2 * i], qf[2 * i + 1]); \
                    }
#define KR_BEGIN float cA[4] = {0.f, 0.f, 0.f, 0.f}, cB[4] = {0.f, 0.f, 0.f, 0.f};
#define KR_END(tau) \
                    const float sA = (cA[0] + cA[3]) * 18446744073709551616.f, sB = (cB[0] + cB[3]) * 18446744073709551616.f; \
                    if (t == (tau & 3)) { if (tau < 4) { sc0 = sA; sc1 = sB; } else { sc2 = sA; sc3 = sB; } }
#define KR_SCORES(tau) { KR_BEGIN KR_STEP(tau, 0) KR_STEP(tau, 1) KR_STEP(tau, 2) KR_END(tau) }
                uint32_t va[3];
                {
                    const int lane = opq(tid) & 31, g = lane >> 2, t = lane & 3;
#pragma unroll
                    for (int i = 0; i < 3; i++) va[i] = ring + V_OFF(2 * i);
                }
#define V_STG(n) _Pragma("unroll") for (int j = 3 * (n); j < 3 * (n) + 3; j++) { \
                    const int i = (j % 12) >> 1; \
                    lds128p(((i & 1) ? (va[i >> 1] ^ 16) + 128 : va[i >> 1]) + (j / 12) * TILE + (j & 1) * 3072, layer, kq[j][0], kq[j][1], kq[j][2], kq[j][3]); }
                uint32_t dep = 0;
                {
                    KR_BEGIN
                    KR_STEP(0, 0) V_STG(0) KR_STEP(0, 1) V_STG(1) KR_STEP(0, 2) V_STG(2)
                    KR_END(0)
                }
                {
                    KR_BEGIN
                    KR_STEP(1, 0) V_STG(3)
                    __syncwarp();
                    dep = lds32(ring);
                    if (layer == 1) tile_load(ring, &maps.k, row0 + 6 * 48, rb, dep, maps.zero);
                    KR_STEP(1, 1) V_STG(4) KR_STEP(1, 2) V_STG(5)
                    KR_END(1)
                }
                {
                    KR_BEGIN
                    KR_STEP(2, 0) V_STG(6) KR_STEP(2, 1) V_STG(7)
                    __syncwarp();
                    dep = lds32(ring + TILE);
                    KR_STEP(2, 2)
                    if (layer == 1) {
                        V1_EXPECT(rb + 8)
                        tile_load(ring + TILE, &maps.k, row0 + 7 * 48, rb + 8, dep, maps.zero);
                        V1_LOAD(rb + 8)
                    }
                    KR_END(2)
                }
#pragma unroll 1
                for (int s = 5; s < 8; s++) {
                    {
                        LANE_IDS
                        const uint32_t tile = !layer ? SLOT1(s) : s == 5 ? xtile : ring + (s - 6) * TILE, tb = !layer ? BAR1(s) : s == 5 ? xb : rb + (s - 6) * 8;
                        const float ur = f_((318u << 23) - (lds32(xl + 8) << 16));
                        mbar_wait(tb, layer ? PAR2(s - 5) : PAR1(s));
                        if (layer) PROF_T(29 + s);
                        float cA[4] = {0.f, 0.f, 0.f, 0.f}, cB[4] = {0.f, 0.f, 0.f, 0.f};
#pragma unroll
                        for (int i = 0; i < 6; i++) {
                            uint32_t a0, a1, a2, a3;
                            lds128(tile + K_OFF(i), a0, a1, a2, a3);
                            mma16816(cA, a0, a1, a2, a3, qf[2 * i], qf[2 * i + 1]);
                            lds128(tile + K_OFF(i) + 3072, a0, a1, a2, a3);
                            mma16816(cB, a0, a1, a2, a3, qf[2 * i], qf[2 * i + 1]);
                        }
                        __syncwarp();
                        const uint32_t last = lds32(tile);
                        if (layer) tile_load(tile, &maps.v, row0 + (s - 2) * 48, tb, last, maps.zero);
                        else refill1(s, last);
                        if (t == (s & 3)) { sc2 = (cA[0] + cA[3]) * ur; sc3 = (cB[0] + cB[3]) * ur; }
                    }
                    if (s == 5) KR_SCORES(3)
                    if (s == 6) {
                        KR_SCORES(4)
                        const int lane = opq(tid) & 31;
                        const uint32_t nx = min(lds32(xl), (uint32_t)XCAP);
#pragma unroll 1
                        for (uint32_t n = 0; n < nx; n++) {
                            const uint32_t id = lds32(xl + 16 + 4 * n);
                            const uint32_t qo = 96 * ((id >> 7) & 3) + 48 * ((id >> 1) & 1) + 16 * ((id >> 5) & 3) + (id & 12) + 2 * (id & 1);
                            const float cr = bf_hi(id) * f_(lds16(sb + SM_QS + qo) << 16);
                            const int d = (int)(16 * ((id >> 9) & 7) + 4 * ((id >> 12) & 3) + ((id >> 13) & 2) + ((id >> 4) & 1) + ((id >> 8) & 128)) - 4 * lane;
                            if (d == 0) sc0 += cr;
                            if (d == 1) sc1 += cr;
                            if (d == 2) sc2 += cr;
                            if (d == 3) sc3 += cr;
                        }
                    }
                }
#undef KR_SCORES
#undef KR_STEP
#undef KR_BEGIN
#undef KR_END
#undef V_STG
                {
                    LANE_IDS
                    if (lds32(xl) > XCAP || !__all_sync(0xffffffffu, (fabsf(sc0) + fabsf(sc1)) + (fabsf(sc2) + fabsf(sc3)) < INFINITY)) {
                        const uint32_t qa = sb + SM_QS + (2 * t + (g & 1)) * 48;
#pragma unroll
                        for (int i = 0; i < 3; i++) lds128(qa + 16 * i, qf[4 * i], qf[4 * i + 1], qf[4 * i + 2], qf[4 * i + 3]);
                        const uint4* kg = reinterpret_cast<const uint4*>(static_cast<const char*>(maps.kp) + (size_t)row0 * 128) + ((g >> 1) + 4 * (g & 1)) * 24 + t;
#pragma unroll 1
                        for (int s = 0; s < 8; s++) {
                            float cA[4] = {0.f, 0.f, 0.f, 0.f}, cB[4] = {0.f, 0.f, 0.f, 0.f};
#pragma unroll
                            for (int i = 0; i < 6; i++) {
                                uint4 u = ldg128(kg + s * 384 + 4 * i);
                                mma16816v(cA, u.x, u.y, u.z, u.w, qf[2 * i], qf[2 * i + 1]);
                                u = ldg128(kg + s * 384 + 4 * i + 192);
                                mma16816v(cB, u.x, u.y, u.z, u.w, qf[2 * i], qf[2 * i + 1]);
                            }
                            if (t == s) { sc0 = cA[0] + cA[3]; sc1 = cB[0] + cB[3]; }
                            if (t + 4 == s) { sc2 = cA[0] + cA[3]; sc3 = cB[0] + cB[3]; }
                        }
                    }
                }
            }
            mw = warp_max(fmaxf(fmaxf(sc0, sc1), fmaxf(sc2, sc3)));
            pk0 = pack2(ex2((sc0 - mw) * SC), ex2((sc1 - mw) * SC));
            pk1 = pack2(ex2((sc2 - mw) * SC), ex2((sc3 - mw) * SC));
            sc2 = (bf_lo(pk0) + bf_hi(pk0)) + (bf_lo(pk1) + bf_hi(pk1));
            sc2 = (float)__reduce_add_sync(0xffffffffu, __float2uint_rn(sc2 * 16777216.f)) * (1.0f / 16777216.f);
            if ((opq(tid) & 31) == 0) st_pkt2(&g_scr.mx[h * 32 + c * 8 + wu], __float_as_uint(mw), (__float_as_uint(sc2) & ~3u) | tag);
            auto head_factor = [&]() {
                const int lane = opq(tid) & 31;
                int it = 0;
                while (!__all_sync(0xffffffffu, (__float_as_uint(sc1) & 3u) == tag) && ++it < SPIN_CAP) {
                    const uint2 mv = ld_pkt2(&g_scr.mx[h * 32 + lane]); sc0 = f_(mv.x); sc1 = f_(mv.y);
                }
                const float e = ex2((sc0 - warp_max(sc0)) * SC);
                const uint32_t d = __reduce_add_sync(0xffffffffu, __float2uint_rn(sc1 * e * 524288.f));
                sc3 = __shfl_sync(0xffffffffu, e, c * 8 + wu) * 524288.f * rcp((float)d);
            };
#pragma unroll
            for (int s = 0; s < 3; s++) { acc[s][0] = acc[s][1] = acc[s][2] = acc[s][3] = 0.f; }
#define P_CONSTS \
                const uint32_t sel0 = g == 0 ? 0x4410u : (g == 1 ? 0x1044u : 0x4444u); \
                const uint32_t sel1 = g == 2 ? 0x4410u : (g == 3 ? 0x1044u : 0x4444u); \
                const int src00 = 4 * (t < 2 ? 4 * t : 4 * (t - 2) + 1);
#define P_FRAGS(tau) \
                const uint32_t pk = ((tau) & 4) ? pk1 : pk0; \
                const uint32_t w0 = __shfl_sync(0xffffffffu, pk, src00 + ((tau) & 3)); \
                const uint32_t w1 = __shfl_sync(0xffffffffu, pk, src00 + ((tau) & 3) + 8); \
                uint32_t pb[4][2]; \
                _Pragma("unroll") for (int j = 0; j < 4; j++) { \
                    const uint32_t src = ((j & 1) ? w1 : w0) >> ((j >> 1) * 16); \
                    pb[j][0] = __byte_perm(src, 0, sel0); pb[j][1] = __byte_perm(src, 0, sel1); \
                }
            if (layer == 0) {
#pragma unroll 1
                for (int s = 8; s < 16; s++) {
                    LANE_IDS
                    P_CONSTS
                    if (s == 13) { const uint2 mv = ld_pkt2(&g_scr.mx[h * 32 + lane]); sc0 = f_(mv.x); sc1 = f_(mv.y); }
                    P_FRAGS(V_SEQ(s))
                    mbar_wait(BAR1(s), PAR1(s));
                    const uint32_t tile = SLOT1(s);
#pragma unroll
                    for (int j = 0; j < 4; j++) {
#pragma unroll
                        for (int u = 0; u < 3; u++) {
                            uint32_t a0, a1, a2, a3;
                            lds128(tile + (j >> 1) * 3072 + V_OFF(3 * (j & 1) + u), a0, a1, a2, a3);
                            mma16816(acc[u], a0, a1, a2, a3, pb[j][0], pb[j][1]);

                        }
                    }
                    __syncwarp();
                    if (s < V0_AT || (s > V0_AT + 1 && s < 14)) refill1(s, lds32(tile), true);
                    if (s == V0_AT || s == V0_AT + 1) {
                        {
                            const uint32_t ar = sb + SM_R + wu * 784 + 32 * g + 16 * t;
                            if (t < 2) {
#pragma unroll
                                for (int u = 0; u < 3; u++) sts128(ar + 256 * u, __float_as_uint(acc[u][0]), __float_as_uint(acc[u][1]), __float_as_uint(acc[u][2]), __float_as_uint(acc[u][3]));
                            }
                        }
                        const uint32_t scl = s == V0_AT ? pack_scale(tile, lane, xl + 12) : lds32(xl + 12);
                        pack_tile<true>(tile, s + 8 - V0_AT, V0_AT + 3 - s, scl, xl, lane, [&](int m, uint32_t (&d)[3]) {
                            if (s != V0_AT && m == 0) {
#pragma unroll
                                for (int k = 0; k < 3; k++) d[k] = ring + 3072 + V_OFF(2 * k + 1);
                            }
                        });
                        if (s != V0_AT) {
                            lds128(tile + V_OFF(2), kq[45][0], kq[45][1], kq[45][2], kq[45][3]);
                            lds128(tile + V_OFF(3), kq[46][0], kq[46][1], kq[46][2], kq[46][3]);
                            lds128(tile + V_OFF(2) + 3072, kq[47][0], kq[47][1], kq[47][2], kq[47][3]);
                            __syncwarp();
                            issue1(V0_AT + 3, lds32(tile));
                        }
                        const int ln = opq(tid) & 31;
                        const uint32_t ar = sb + SM_R + wu * 784 + 8 * (ln & 28) + 16 * (ln & 1);
#pragma unroll
                        for (int u = 0; u < 3; u++) {
                            uint32_t a0, a1, a2, a3;
                            lds128(ar + 256 * u, a0, a1, a2, a3);
                            acc[u][0] = f_(a0); acc[u][1] = f_(a1); acc[u][2] = f_(a2); acc[u][3] = f_(a3);
                        }
                    }
                    if (s == 13) head_factor();
                    if (s >= 14 && elect_one()) {
                        if (atomicAdd(reinterpret_cast<unsigned*>(misc + 3), 1u) == 14u && (int)(now_ns() - lds32(xl + 4)) >= 0) {
                            PROF_X(47);
                            load_wo(maps, sb + SM_B, h, c, wbar, 6);
                            atomicAdd(reinterpret_cast<unsigned*>(misc + 3), 256u);
                        }
                    }
                }
            } else {
                LANE_IDS
                P_CONSTS
#pragma unroll
                for (int k = 0; k < 4; k++) lds128(V1_REST(t + 4 * (k >> 1)) + 16 * g + 128 * (k & 1), kq[36 + k][0], kq[36 + k][1], kq[36 + k][2], kq[36 + k][3]);
#pragma unroll 1
                for (int i = 3; i < 8; i++) {
                    const uint32_t tile = i > 3 ? ring + (i & 1) * TILE : xtile, tb = i > 3 ? rb + (i & 1) * 8 : xb;
                    if (i == 6) { const uint2 mv = ld_pkt2(&g_scr.mx[h * 32 + lane]); sc0 = f_(mv.x); sc1 = f_(mv.y); }
                    if (i == 7) head_factor();
                    if (i == PK_AT) {
                uint32_t nx, nk, ik, iv;
                lds128(xl, nx, nk, ik, iv);
                if (nx <= XCAP) {
                    const uint32_t pks = bmul2(pk0, iv);
#pragma unroll
                    for (int s = 0; s < 2; s++) {
                        const uint32_t pk1 = 0, pk0 = pks;
                        P_FRAGS(s)
#pragma unroll
                        for (int j = 0; j < 4; j++) {
#pragma unroll
                            for (int u = 0; u < 3; u++) {
                                const int i = 3 * (j & 1) + u, m = i >> 1, r = i & 1, hf = j >> 1;
                                if (s == 1 && m == 2) continue;
                                const int ql = s == 0 ? 4 * m + 2 * hf : m == 0 ? 3 + 4 * hf : 45 + hf, qc = s == 0 ? 4 * m + 1 : m == 0 ? 11 : 47;
                                uint32_t w[4];
                                unpack8(kq[ql][2 * r], kq[ql][2 * r + 1], kq[qc][2 * hf + r], w);
                                mma16816(acc[u], w[0], w[1], w[2], w[3], pb[j][0], pb[j][1]);
                            }
                        }
                    }
#pragma unroll 1
                    for (uint32_t n = 0; n < nx; n++) {
                        const uint32_t id = lds32(xl + 16 + 4 * n);
                        const int i = ((id >> 4) & 6) + ((id >> 3) & 1), key = ((id >> 6) & 6) + (i >= 3);
                        const uint32_t pw = __shfl_sync(0xffffffffu, pk0, 8 * (key & 3) + (key & 4) + ((id >> 12) & 3));
                        const float cr = bf_hi(id) * ((id & 16) ? bf_hi(pw) : bf_lo(pw));
                        const int d = (int)(64 * ((id >> 9) & 7) + 4 * (id & 4) + 4 * (i >= 3 ? i - 3 : i) + (id & 3) + ((~id >> 5) & 1024)) - 16 * lane;
#pragma unroll
                        for (int k = 0; k < 12; k++) if (d == k) acc[k >> 2][k & 3] += cr;
                    }
                } else {
                    const uint4* vg = reinterpret_cast<const uint4*>(static_cast<const char*>(maps.vp) + (size_t)row0 * 128) + 48 * t + g;
#pragma unroll 1
                    for (int s = 0; s < 2; s++) {
                        P_FRAGS(s)
#pragma unroll
                        for (int j = 0; j < 4; j++) {
#pragma unroll
                            for (int u = 0; u < 3; u++) {
                                if (s == 1 && (j & 1) && u) continue;
                                const uint4 w = ldg128(vg + 384 * s + 192 * (j >> 1) + 24 * (j & 1) + 8 * u);
                                mma16816v(acc[u], w.x, w.y, w.z, w.w, pb[j][0], pb[j][1]);
                            }
                        }
                    }
                }
#pragma unroll
                for (int s = 2; s > 0; s--) {
                    P_FRAGS(s)
#pragma unroll
                    for (int j = 0; j < 4; j++) {
#pragma unroll
                        for (int u = 0; u < 3; u++) {
                            if (s == 1 && !((j & 1) && u)) continue;
                            const int k = s == 2 ? 12 + 2 * (3 * (j & 1) + u) + (j >> 1) : 35 + (j >> 1) * 2 + u;
                            mma16816(acc[u], kq[k][0], kq[k][1], kq[k][2], kq[k][3], pb[j][0], pb[j][1]);
                        }
                    }
                }
                    }
                    P_FRAGS(i)
                    mbar_wait(tb, PAR2(i));
                    PROF_T(34 + i);
#pragma unroll
                    for (int k = 0; k < 6; k++) {
                        const uint32_t a = tile + V_OFF(k);
                        lds128(a, kq[24 + k][0], kq[24 + k][1], kq[24 + k][2], kq[24 + k][3]);
                        lds128(a + 3072, kq[30 + k][0], kq[30 + k][1], kq[30 + k][2], kq[30 + k][3]);
                    }
#pragma unroll
                    for (int j = 0; j < 4; j++) {
#pragma unroll
                        for (int u = 0; u < 3; u++) {
                            const int k = 24 + 6 * (j >> 1) + 3 * (j & 1) + u;
                            mma16816(acc[u], kq[k][0], kq[k][1], kq[k][2], kq[k][3], pb[j][0], pb[j][1]);
                        }
                    }
                    __syncwarp();
                    if (wu < L1R && i == 5 - (wu & 1)) tile_load_l1(tile, maps.vp, row0 + (i + 2) * 48, tb, lane);
                    else if (i == 4 || i == 5) tile_load(tile, &maps.v, row0 + (i + 2) * 48, tb, lds32(tile), maps.zero);
                    if (i == WO_AT1 && HAS_FFN && elect_one()) {
                        if (atomicAdd(reinterpret_cast<unsigned*>(misc + 2), 1u) == 7u) {
                            PROF_X(63);
                            load_wo(maps, sb + SM_Q, h, c, wbar, KEEP4 && __float_as_uint(misc[1]) >= DN0 ? 5 : 6);
                        }
                    }
                }
            }
#undef P_FRAGS
#undef P_CONSTS
#undef LANE_IDS
        }
        PROF_T(3 + layer * 16);
        PC(layer * 32 + 1);

        {
            const int lane = opq(tid) & 31;
            const uint32_t a = sb + SM_R + wu * 784 + 8 * (lane & 28) + 16 * (lane & 1);
#pragma unroll
            for (int u = 0; u < 3; u++) sts128p(a + 256 * u, acc[u][0] * sc3, acc[u][1] * sc3, acc[u][2] * sc3, acc[u][3] * sc3, lane & 2);
        }
        const uint32_t role1 = layer ? lds32(sb + SM_MISC + 4) : DN0 + NDN;
        const uint32_t pc = opq(sb + SM_R + 16 * opq(tid));
        uint4* const px0 = opq(&g_scr.hx[b * 48 + opq(tid)]);
        __syncthreads();
        PROF_T(4 + layer * 16);
        PC(layer * 32 + 2);
        float4 o = make_float4(0.f, 0.f, 0.f, 0.f);
        if (wu < 2) {
            float4 v[8];
#pragma unroll
            for (int w = 0; w < 8; w++) v[w] = lds4f(pc + w * 784);
            o.x = ((v[0].x + v[1].x) + (v[2].x + v[3].x)) + ((v[4].x + v[5].x) + (v[6].x + v[7].x));
            o.y = ((v[0].y + v[1].y) + (v[2].y + v[3].y)) + ((v[4].y + v[5].y) + (v[6].y + v[7].y));
            o.z = ((v[0].z + v[1].z) + (v[2].z + v[3].z)) + ((v[4].z + v[5].z) + (v[6].z + v[7].z));
            o.w = ((v[0].w + v[1].w) + (v[2].w + v[3].w)) + ((v[4].w + v[5].w) + (v[6].w + v[7].w));
            o.w = f_(__float_as_uint(o.w) & ~1u);
            st_pktp(px0, __float_as_uint(o.x), __float_as_uint(o.y), __float_as_uint(o.z), __float_as_uint(o.w), threadIdx.x < 48);
        }
        uint32_t ticket = 0;
        if (layer == 0 && tid == 224)
            asm volatile("atom.relaxed.gpu.global.inc.u32 %0, [%1], 0x7fffffff;" : "=r"(ticket) : "l"(g_scr.ticket + 8 + (b >> 3)) : "memory");
        if (layer == 0 && tid == 224 && lds32(sb + SM_MISC + 12) < 256u) {
            int it = 0;
            while ((int)(now_ns() - lds32(sb + SM_XL + 4)) < 0 && ++it < SPIN_CAP) {}
            PROF_X(47);
            load_wo(maps, sb + SM_B, h, c, wbar, 6);
        }
        uint32_t pr;
        uint4* pacc;
        {
            const int tid = opq(threadIdx.x), warp = tid >> 5, lane = tid & 31, g = lane >> 2, t = lane & 3, mat = lane >> 3, r8 = lane & 7;
            const int kg = warp >> 1, mg = warp & 1;
            const bool wo2 = role1 < DN0 + NDN;
            const uint32_t aw2 = 40960 + (wo2 && KEEP4 && role1 >= DN0 && kg >= 2 ? SM_B - SM_Q : 0);
            uint32_t aw[5];
#pragma unroll
            for (int i = 0; i < 5; i++) {
                const uint32_t lin = ((mat >> 1) * 8 + r8) * 320 + 64 * i + 32 * mg + 16 * (mat & 1);
                aw[i] = sb + (wo2 ? SM_Q : SM_B) + 5120 * kg + (lin ^ ((lin >> 3) & 48));
            }
#define CXE 1
            const uint32_t ao = pin(sb + SM_OS + 96 * kg + 16 * t), dw = pin(sb + SM_R + 16 * (16 * mg + g) + 4 * kg);
            pr = pin(sb + SM_R + 48 * tid); pacc = pin(&g_scr.acc[layer][(54 * c + tid) * ACC_STR]);
            const int w = 2 * min(tid, 47);
            const uint32_t d0 = pin(sb + SM_OS + 4 * (24 * ((w >> 3) & 3) + ((w >> 2) & 1) + (w < 64 ? 4 * (w & 3) + 2 * (w >> 5) : 16 + 2 * (w & 3))));
            const uint32_t d1 = pin(d0 + (w < 64 ? 16 : 8));
            const uint4* pp[3];
#pragma unroll
            for (int k = 0; k < 3; k++) pp[k] = pin(&g_scr.hx[(h * 4 + ((c + 1 + k) & 3)) * 48 + min(tid, 47)]);
            bool ok = true;
            if ((PRE1 & 8) && layer) {
#pragma unroll
                for (int ks = 0; ks < 3; ks++) {
                    mbar_wait(wbar + 8 * ks, wo2);
#pragma unroll
                    for (int i = 0; i < 5; i++) ldsm4t(aw[i] + (ks == 2 ? aw2 : 20480 * ks), kq[3 * i + ks]);
                    if (ks == CXE && wu < 2) {
#pragma unroll
                        for (int k = 0; k < 3; k++) { const uint4 v = ld_pkt(pp[k]); kq[20 + k][0] = v.x; kq[20 + k][1] = v.y; kq[20 + k][2] = v.z; kq[20 + k][3] = v.w; }
                    }
                }
                PROF_T(50);
                if (CXE < 3 && wu < 2) {
                    ok = __any_sync(0xffffffffu, (kq[20][3] | kq[21][3] | kq[22][3]) & 1);
                    if (!ok) {
#pragma unroll
                        for (int k = 0; k < 3; k++) { o.x += f_(kq[20 + k][0]); o.y += f_(kq[20 + k][1]); o.z += f_(kq[20 + k][2]); o.w += f_(kq[20 + k][3]); }
                    }
                }
            }
            if (wu < 2) {
                if (ok) {
                    uint4 v3[3];
                    int it = 0;
                    do {
#pragma unroll
                        for (int k = 0; k < 3; k++) v3[k] = ld_pkt(pp[k]);
                        ok = __any_sync(0xffffffffu, (v3[0].w | v3[1].w | v3[2].w) & 1);
                    } while (ok && ++it < SPIN_CAP);
#pragma unroll
                    for (int k = 0; k < 3; k++) { o.x += f_(v3[k].x); o.y += f_(v3[k].y); o.z += f_(v3[k].z); o.w += f_(v3[k].w); }
                }
                sts32p(d0, f_(pack2(o.x, o.y)), tid >= 48);
                sts32p(d1, f_(pack2(o.z, o.w)), tid >= 48);
            }
            PC(layer * 32 + 3);
            __syncthreads();
            PROF_T(5 + layer * 16);
            PC(layer * 32 + 5);
            if (tid == 224 && layer == 0) {
                if (ticket >= 6 + ((b >> 3) & 1)) ticket = DN0 + NDN;
                else asm volatile("atom.relaxed.gpu.global.inc.u32 %0, [%1], 0x7fffffff;" : "=r"(ticket) : "l"(g_scr.ticket) : "memory");
            }
            uint32_t ob[6];
            lds128(ao, ob[0], ob[1], ob[2], ob[3]);
            lds64(ao + 64 - 8 * t, ob[4], ob[5]);
            float cc[5][4];
#pragma unroll
            for (int i = 0; i < 5; i++) cc[i][0] = cc[i][1] = cc[i][2] = cc[i][3] = 0.f;
            if ((PRE1 & 8) && layer) {
#pragma unroll
                for (int ks = 0; ks < 3; ks++) {
#pragma unroll
                    for (int i = 0; i < 5; i++) mma16816(cc[i], kq[3 * i + ks][0], kq[3 * i + ks][1], kq[3 * i + ks][2], kq[3 * i + ks][3], ob[2 * ks], ob[2 * ks + 1]);
                }
            } else {
#pragma unroll
                for (int ks = 0; ks < 3; ks++) {
                    mbar_wait(wbar + 8 * ks, wo2);
                    if (ks == 2) { PC(layer * 32 + 4); PROF_T(48 + layer * 2); }
                    uint32_t a[5][4];
#pragma unroll
                    for (int i = 0; i < 5; i++) ldsm4t(aw[i] + (ks == 2 ? aw2 : 20480 * ks), a[i]);
#pragma unroll
                    for (int i = 0; i < 5; i++) mma16816(cc[i], a[i][0], a[i][1], a[i][2], a[i][3], ob[2 * ks], ob[2 * ks + 1]);
                }
            }
            if (t == 0) {
#pragma unroll
                for (int i = 0; i < 5; i++) { sts32(dw + 512 * i, cc[i][0]); sts32(dw + 512 * i + 128, cc[i][2]); }
            }
        }
        PC(layer * 32 + 6);
        __syncthreads();
        PROF_T(6 + layer * 16);
        PC(layer * 32 + 7);
        if (tid < 54) {
            const float4 v0 = lds4f(pr), v1 = lds4f(pr + 16), v2 = lds4f(pr + 32);
            const float y0 = (v0.x + v0.y) + (v0.z + v0.w), y1 = (v1.x + v1.y) + (v1.z + v1.w), y2 = (v2.x + v2.y) + (v2.z + v2.w);
            red_pkt(pacc, y0, tid == 53 ? 0.f : y1, tid == 53 ? 0.f : y2);
        }
        if (tid == 224 && layer == 0) {
            misc[1] = __uint_as_float(ticket);
            if (ticket < DN0 + NDN && (ticket < NG || !DNTH)) load_ffn(maps, ticket, sb + SM_B, fbar);
        }
        PROF_T(7 + layer * 16);
        PC(layer * 32 + 8);
        __syncthreads();
        const int role = (int)__float_as_uint(misc[1]);
        PC(layer * 32 + 9);
        const uint32_t fbase = sb + SM_B;
        const uint32_t DONE32 = 0x42000000u;
        if (role < NG) {
            const int tid = opq(threadIdx.x), warp = tid >> 5, lane = tid & 31, g = lane >> 2, t = lane & 3, mat = lane >> 3, r8 = lane & 7;
            const uint32_t ag = fbase + (80 * warp + (mat >> 1) * 8 + r8) * 96 + (((mat & 1) ^ (r8 >> 2)) << 4);
            constexpr int GI = 32, GK = 16 * 96;
            const bool on = (g & 1) == (t >> 1), isx = on && g < 2;
            const uint32_t pm = opq(isx ? sb + SM_XS + 160 * warp + 16 * t : sb + (on ? SM_ONE : SM_ZERO)), pm2 = opq(pm + 128 - (isx ? 8 * t : 0));
            const uint32_t dg = opq(sb + SM_R + 4 * (2 * (warp * 48 + g) + t)), ds = opq(sb + SM_ST + 8 * warp + (lane < 16 ? 4 : 0));
            const bool ws = (lane & 15) == 0, lo = lane < 16;
            uint32_t pre[6][4];
            float s1 = 0.f, s2 = 0.f;
            {
                bool hx = wu == 7;
                int it = 0;
                const uint4* px = &g_scr.acc[layer][min(tid, 215) * ACC_STR];
                const int cq = tid / 54, r = tid - 54 * cq, k0 = min(160 * cq + 3 * r, DM - 1);
                const uint32_t w0 = sb + SM_XS + 4 * xpos(k0 >> 1), w1 = sb + SM_XS + 4 * xpos(min((k0 >> 1) + 1, DM / 2 - 1));
                const uint32_t e0 = w0 + 2 * (k0 & 1), e1 = (k0 & 1) ? w1 : w0 + 2, e2 = w1 + 2 * (k0 & 1);
                                auto sts16 = [](uint32_t a, uint32_t x, bool on) {
                    asm volatile("{\n.reg .pred p;\nsetp.ne.u32 p, %2, 0;\n@p st.shared.u16 [%0], %1;\n}" ::"r"(a), "h"((unsigned short)x), "r"((uint32_t)on) : "memory");
                };
                const bool on0 = tid < 216, on1 = on0 && r != 53;
                const float x0 = on0 ? f_(lds16(e0) << 16) : 0.f, x1 = on1 ? f_(lds16(e1) << 16) : 0.f, x2 = on1 ? f_(lds16(e2) << 16) : 0.f;
                auto take_x = [&](const uint4 v) {
                    if (__all_sync(0xffffffffu, v.w == DONE32)) {
                        hx = true;
                        const uint32_t a = pack2(f_(v.x), f_(v.y)), p = pack2(x0 + bf_lo(a), x1 + bf_hi(a)), q = pack2(x2 + bfr(f_(v.z)), 0.f);
                        sts16(e0, p, on0); sts16(e1, p >> 16, on1); sts16(e2, q, on1);
                        const float y0 = on0 ? bf_lo(p) : 0.f, y1 = on0 ? bf_hi(p) : 0.f, y2 = on0 ? bf_lo(q) : 0.f;
                        s1 = y0 + (y1 + y2); s2 = y0 * y0 + (y1 * y1 + y2 * y2);
                    }
                };
                auto try_x = [&]() { take_x(ld_pkt(px)); };
                while (!mbar_test(fbar, 0) && ++it < SPIN_CAP) { if (!hx) try_x(); }
                uint4 v0 = make_uint4(0u, 0u, 0u, 0u);
                if ((PRE1 & 4) && !hx) v0 = ld_pkt(px);
#pragma unroll
                for (int n = 0; n < 6; n++) ldsm4t(ag + (n % 3) * GI + (n / 3) * GK, pre[n]);
                if ((PRE1 & 1) && layer) {
#pragma unroll
                    for (int n = 6; n < 15; n++) ldsm4t(ag + (n % 3) * GI + (n / 3) * GK, kq[n - 6]);
                }
                if ((PRE1 & 4) && !hx) take_x(v0);
                PC(layer * 32 + 10);
                while (!hx && ++it < SPIN_CAP) try_x();
                PC(layer * 32 + 11);
            __syncthreads();
            PC(layer * 32 + 12);
            PROF_T(9 + layer * 16);
            float sv = lo ? s1 : s2, cc[3][4];
            if ((PRE1 & 1) && layer) gemv15r(cc, pre, kq, pm, pm2, sv, lo ? s2 : s1);
            else gemv15<GK>(cc, pre, [&](int i) { return ag + i * GI; }, pm, pm2, sv, lo ? s2 : s1);
#pragma unroll
            for (int i = 0; i < 3; i++) { sts32p(dg + 128 * i, cc[i][0] + cc[i][3], t & 2); sts32p(dg + 128 * i + 64, cc[i][1] + cc[i][2], t & 2); }
            if (ws) sts32(ds, sv);
            const uint32_t pg = opq(sb + SM_R + 8 * (24 * warp + (lane < 24 ? lane : 0))), st = opq(sb + SM_ST);
            uint4* const ph = opq(lane < 24 && lane % 6 == 0 ? &g_scr.ah[role * 8 + 4 * warp + lane / 6] : nullptr);
            PC(layer * 32 + 13);
            __syncthreads();
            PC(layer * 32 + 14);
            PROF_T(43 + layer * 16);
            if (wu < 2) {
                float mean, inv;
                ln_stats(st, mean, inv);
                float2 v[8];
#pragma unroll
                for (int w = 0; w < 8; w++) v[w] = lds2f(pg + w * 384);
                const float gx = ((v[0].x + v[1].x) + (v[2].x + v[3].x)) + ((v[4].x + v[5].x) + (v[6].x + v[7].x));
                const float gs = ((v[0].y + v[1].y) + (v[2].y + v[3].y)) + ((v[4].y + v[5].y) + (v[6].y + v[7].y));
                float ga = inv * (gx - mean * gs);
                if (role < NG / 2) { ga = bfr(ga); ga *= rcp(1.0f + ex2(-1.4426950408889634f * ga)); }
                const uint32_t wd = pack2(ga, __shfl_down_sync(0xffffffffu, ga, 1));
                const uint32_t wa = __shfl_down_sync(0xffffffffu, wd, 2), wb = __shfl_down_sync(0xffffffffu, wd, 4);
                if (ph) st_pkt(ph, wd, wa, wb, tag);
            }
            if (HOLD & 2) __syncthreads();
            }
            PROF_T(10 + layer * 16);
            PC(layer * 32 + 15);
        } else if (role < DN0 + NDN) {
            const int j = role - DN0;
            const int tid = opq(threadIdx.x), warp = tid >> 5, lane = tid & 31, g = lane >> 2, t = lane & 3, mat = lane >> 3, r8 = lane & 7;
            float xres = 0.f;
            uint32_t xr0 = 0, xr1 = 0;
            if (wu == 0) {
                const int col = 16 * j + (lane & 15), cc = col / 160, r = col - 160 * cc, e = r % 3;
                const uint4* px = &g_scr.acc[layer][(54 * cc + r / 3) * ACC_STR];
                const float x0 = __bfloat162float(reinterpret_cast<const __nv_bfloat16*>(xs32)[2 * xpos(col >> 1) + (col & 1)]);
                uint4 v;
                int it = 0;
                bool ld = DNTH && layer == 0;
                do {
                    v = ld_pkt(px);
                    if (ld && f_(__shfl_sync(0xffffffffu, v.w, 0)) >= (float)DNTH) { ld = false; if (lane == 0) load_ffn(maps, role, sb + SM_B, fbar); }
                } while (!__all_sync(0xffffffffu, v.w == DONE32) && ++it < SPIN_CAP);
                if (ld && lane == 0) load_ffn(maps, role, sb + SM_B, fbar);
                xres = x0 + bfr(f_(e == 0 ? v.x : (e == 1 ? v.y : v.z)));
                const int p4 = 4 * (lane & 3);
                xr0 = pack2(__shfl_sync(0xffffffffu, xres, p4), __shfl_sync(0xffffffffu, xres, p4 + 1));
                xr1 = pack2(__shfl_sync(0xffffffffu, xres, p4 + 2), __shfl_sync(0xffffffffu, xres, p4 + 3));
            }
            PC(layer * 32 + 17);
            PROF_T(9 + layer * 16);
            const uint32_t ad = fbase + (192 * warp + (mat >> 1) * 8 + r8) * 32 + (((mat & 1) ^ (r8 >> 2)) << 4);
            uint32_t* hs = reinterpret_cast<uint32_t*>(rr) + warp * 96;
            uint32_t pre[NPRE][4];
            {
                uint32_t pos[3];
#pragma unroll
                for (int i = 0; i < 3; i++) { const int w = 3 * lane + i; pos[i] = pin(sb + SM_R + 384 * warp + 4 * ((w & ~15) + 4 * (w & 3) + ((w >> 2) & 1) + ((w >> 2) & 2))); }
                uint4 v = make_uint4(0u, 0u, 0u, 0u), u = v;
                if (layer == 0) { v = ld_pkt(&g_scr.ah[tid]); u = ld_pkt(&g_scr.ah[256 + tid]); }
                mbar_wait(fbar, 0);
#pragma unroll
                for (int n = 0; n < NPRE; n++) ldsm4t(ad + n * 512, pre[n]);
                if ((PRE1 & 2) && layer) {
#pragma unroll
                    for (int n = NPRE; n < 12; n++) ldsm4t(ad + n * 512, kq[12 + n]);
                }
                PC(layer * 32 + 18);
                int it = 0;
                while (!__all_sync(0xffffffffu, v.w == tag && u.w == tag) && ++it < SPIN_CAP) { v = ld_pkt(&g_scr.ah[tid]); u = ld_pkt(&g_scr.ah[256 + tid]); }
                PC(layer * 32 + 19);
                sts32(pos[0], f_(bmul2(v.x, u.x))); sts32(pos[1], f_(bmul2(v.y, u.y))); sts32(pos[2], f_(bmul2(v.z, u.z)));
            __syncwarp();
            PROF_T(11 + layer * 16);
            PC(layer * 32 + 20);
            float ca[4] = {0.f, 0.f, 0.f, 0.f}, cb[4] = {0.f, 0.f, 0.f, 0.f};
            if ((PRE1 & 2) && layer) {
                float cc[4] = {0.f, 0.f, 0.f, 0.f}, cd[4] = {0.f, 0.f, 0.f, 0.f};
#pragma unroll
                for (int jj = 0; jj < 6; jj++) {
                    const uint4 hv = *reinterpret_cast<const uint4*>(hs + 16 * jj + 4 * t);
                    const uint32_t (&f0)[4] = 2 * jj < NPRE ? pre[2 * jj < NPRE ? 2 * jj : 0] : kq[12 + 2 * jj];
                    const uint32_t (&f1)[4] = 2 * jj + 1 < NPRE ? pre[2 * jj + 1 < NPRE ? 2 * jj + 1 : 0] : kq[13 + 2 * jj];
                    if (jj & 1) { mma16816(cc, f0[0], f0[1], f0[2], f0[3], hv.x, hv.y); mma16816(cd, f1[0], f1[1], f1[2], f1[3], hv.z, hv.w); }
                    else { mma16816(ca, f0[0], f0[1], f0[2], f0[3], hv.x, hv.y); mma16816(cb, f1[0], f1[1], f1[2], f1[3], hv.z, hv.w); }
                }
#pragma unroll
                for (int e = 0; e < 4; e++) { ca[e] += cc[e]; cb[e] += cd[e]; }
            } else {
#pragma unroll
                for (int jj = 0; jj < 6; jj++) {
                    const uint4 hv = *reinterpret_cast<const uint4*>(hs + 16 * jj + 4 * t);
                    uint32_t a[4];
                    if (2 * jj < NPRE) { a[0] = pre[2 * jj][0]; a[1] = pre[2 * jj][1]; a[2] = pre[2 * jj][2]; a[3] = pre[2 * jj][3]; }
                    else ldsm4t(ad + 2 * jj * 512, a);
                    mma16816(ca, a[0], a[1], a[2], a[3], hv.x, hv.y);
                    if (2 * jj + 1 < NPRE) { a[0] = pre[2 * jj + 1][0]; a[1] = pre[2 * jj + 1][1]; a[2] = pre[2 * jj + 1][2]; a[3] = pre[2 * jj + 1][3]; }
                    else ldsm4t(ad + (2 * jj + 1) * 512, a);
                    mma16816(cb, a[0], a[1], a[2], a[3], hv.z, hv.w);
                }
            }
            if (t == 0) { rr[768 + warp * 16 + g] = ca[0] + cb[0]; rr[768 + warp * 16 + 8 + g] = ca[2] + cb[2]; }
            const uint32_t pd = opq(sb + SM_R + 3072 + 16 * (lane & 3));
            uint4* const py = opq(&g_scr.ay[j * 4 + lane]);
            uint2* const po = opq(reinterpret_cast<uint2*>(out + 16 * j) + lane);
            PC(layer * 32 + 21);
            __syncthreads();
            PC(layer * 32 + 22);
            if (wu == 0) {
                float4 p[8];
#pragma unroll
                for (int w = 0; w < 8; w++) p[w] = lds4f(pd + 64 * w);
                const uint32_t y0 = pack2(((p[0].x + p[1].x) + (p[2].x + p[3].x)) + ((p[4].x + p[5].x) + (p[6].x + p[7].x)),
                                          ((p[0].y + p[1].y) + (p[2].y + p[3].y)) + ((p[4].y + p[5].y) + (p[6].y + p[7].y)));
                const uint32_t y1 = pack2(((p[0].z + p[1].z) + (p[2].z + p[3].z)) + ((p[4].z + p[5].z) + (p[6].z + p[7].z)),
                                          ((p[0].w + p[1].w) + (p[2].w + p[3].w)) + ((p[4].w + p[5].w) + (p[6].w + p[7].w)));
                uint32_t wd, wn;
                asm("add.rn.bf16x2 %0, %1, %2;" : "=r"(wd) : "r"(xr0), "r"(y0));
                asm("add.rn.bf16x2 %0, %1, %2;" : "=r"(wn) : "r"(xr1), "r"(y1));
                asm volatile("{\n.reg .pred p;\nsetp.ne.u32 p, %3, 0;\n@p st.global.v2.u32 [%0], {%1,%2};\n}" ::"l"(po), "r"(wd), "r"(wn), "r"((uint32_t)(layer && tid < 4)) : "memory");
                st_pktp(py, wd, wn, 0, tag, tid < 4);
            }
            if (HOLD & 1) __syncthreads();
            }
            PROF_T(12 + layer * 16);
            PC(layer * 32 + 23);
        }
    }
}

typedef CUresult (*EncodeFn)(CUtensorMap*, CUtensorMapDataType, cuuint32_t, void*, const cuuint64_t*, const cuuint64_t*, const cuuint32_t*,
                             const cuuint32_t*, CUtensorMapInterleave, CUtensorMapSwizzle, CUtensorMapL2promotion, CUtensorMapFloatOOBfill);

void make_map(EncodeFn enc, CUtensorMap* m, const void* base, int rank, uint64_t d0, uint64_t d1, uint64_t d2, uint64_t s1, uint64_t s2,
              uint32_t b0, uint32_t b1, uint32_t b2, CUtensorMapSwizzle sw, CUtensorMapL2promotion pr = CU_TENSOR_MAP_L2_PROMOTION_NONE) {
    cuuint64_t dims[3] = {d0, d1, d2};
    cuuint64_t strides[2] = {s1, s2};
    cuuint32_t box[3] = {b0, b1, b2};
    cuuint32_t es[3] = {1, 1, 1};
    enc(m, CU_TENSOR_MAP_DATA_TYPE_BFLOAT16, rank, const_cast<void*>(base), dims, strides, box, es, CU_TENSOR_MAP_INTERLEAVE_NONE, sw,
        pr, CU_TENSOR_MAP_FLOAT_OOB_FILL_NONE);
}

}

extern "C" void kernel_launch(void* const* d_in, const int* in_sizes, int n_in, void* d_out, int out_size) {
    (void)in_sizes; (void)n_in; (void)out_size;
    static EncodeFn enc = nullptr;
    if (!enc) {
        void* fn = nullptr;
        cudaDriverEntryPointQueryResult qr;
        cudaGetDriverEntryPoint("cuTensorMapEncodeTiled", &fn, cudaEnableDefault, &qr);
        enc = reinterpret_cast<EncodeFn>(fn);
        cudaFuncSetAttribute(decode_kernel, cudaFuncAttributeMaxDynamicSharedMemorySize, SM_TOTAL);
    }
    Maps maps;
    make_map(enc, &maps.k, d_in[1], 2, 64, (uint64_t)NH * SK * 3, 1, 128, 0, 64, 48, 1, CU_TENSOR_MAP_SWIZZLE_128B);
    make_map(enc, &maps.v, d_in[2], 2, 64, (uint64_t)NH * SK * 3, 1, 128, 0, 64, 48, 1, CU_TENSOR_MAP_SWIZZLE_128B);
    make_map(enc, &maps.wq, d_in[3], 3, 64, DM, NH * DH / 64, NH * DH * 2, 128, 64, 160, 3, CU_TENSOR_MAP_SWIZZLE_128B);
    make_map(enc, &maps.wo, d_in[4], 3, 32, DM / 32, NH * DH, 64, DM * 2, 32, 5, 32, CU_TENSOR_MAP_SWIZZLE_64B);
    make_map(enc, &maps.vr, (const char*)d_in[2] + 512, 2, 128, (uint64_t)NH * SK / 2, 1, 768, 0, 128, 2, 1, CU_TENSOR_MAP_SWIZZLE_NONE);
    constexpr int GW = 48;
    make_map(enc, &maps.w1, d_in[6], 3, FF, 160, 4, FF * 2, 160 * FF * 2, GW, 160, 4, CU_TENSOR_MAP_SWIZZLE_NONE, FFN_PROMO);
    make_map(enc, &maps.w3, d_in[7], 3, FF, 160, 4, FF * 2, 160 * FF * 2, GW, 160, 4, CU_TENSOR_MAP_SWIZZLE_NONE, FFN_PROMO);
    make_map(enc, &maps.w2, d_in[8], 3, DM, 256, 6, DM * 2, 256 * DM * 2, 16, 256, 6, CU_TENSOR_MAP_SWIZZLE_32B, FFN_PROMO);
    maps.vp = d_in[2];
    maps.kp = d_in[1];
    maps.zero = 0;
    decode_kernel<<<NCTA, NT, SM_TOTAL, cudaStreamPerThread>>>(maps, (const __nv_bfloat16*)d_in[0], (__nv_bfloat16*)d_out);
}
```

```cpp
#include <cuda_runtime.h>
#include <cuda_bf16.h>
#include <cuda.h>
#include <stdint.h>
#include <math.h>

namespace {

constexpr int DM = 640;
constexpr int NH = 32;
constexpr int DH = 192;
constexpr int SK = 32768;
constexpr int WIN = 4096;
constexpr int FF = 1536;
constexpr int NCTA = 128;
constexpr int NT = 256;
constexpr int TILE = 6144;
constexpr int NG = 64;
constexpr int DN0 = 64;
constexpr int NDN = 40;

constexpr int SM_RING = 0;
constexpr int SM_B = 8 * 2 * TILE;
constexpr int SM_Q = SM_B + 61440;
__host__ __device__ constexpr int c_slot(int w) { return w < 2 ? 4096 + 10240 * w : 12288 + 6144 * w; }
__host__ __device__ constexpr int v1_pos(int n) { return 10240 * (n >> 3) + 512 * (n & 7); }
constexpr int SM_XS = SM_Q + 61440;
constexpr int SM_R = SM_XS + 1280;
constexpr int SM_ST = SM_R + 4096;
constexpr int SM_QS = SM_R + 6272;
constexpr int SM_OS = SM_QS + 384;
constexpr int SM_BAR = SM_OS + 384;
constexpr int SM_XBAR = SM_BAR + 24 * 8;
constexpr int SM_MISC = SM_XBAR + 8 * 8;
constexpr int SM_ONE = SM_MISC + 16;
constexpr int SM_ZERO = SM_ONE + 160;
constexpr int XCAP = 48;
constexpr int XSTR = 16 + 4 * XCAP;
constexpr int SM_XL = SM_ZERO + 160;
constexpr int SM_TOTAL = SM_XL + 8 * XSTR;
static_assert(SM_TOTAL <= 232448, "shared memory");

constexpr unsigned long long POL_EF = 0x12F0000000000000ull;
constexpr unsigned long long POL_EN = 0x16F0000000000000ull;

#define RT_MASK 0xF2E0u
#define RT_MASK2 0xEAE0u
#define WO_AT1 5
#define FFN_PROMO CU_TENSOR_MAP_L2_PROMOTION_NONE
#define FFN_POL POL_EF
#define HAS_FFN (__float_as_uint(misc[1]) < DN0 + NDN)
#define ACC_STR 1
#define NPRE 6

#define STAG 200
#define L1R 3
#define PRE1 13
#define HOLD 2
#define DNTH 23
constexpr int V0_AT = 8;
constexpr unsigned long long SEQ1 = 0x2765431076543210ull;
constexpr uint32_t IN_S1 = 0xAA49, IN_S0 = 0x124, PARITY1 = 0x6638, PARITY2 = 0xCE;
#define KEEP4 1
constexpr int NQ = 48;
constexpr int SPIN_CAP = 1 << 19;
constexpr uint32_t ONES = 0x3F803F80u;

struct alignas(1024) Scratch {
    uint4 hx[NCTA * 48];
    uint4 pad0[32 * 5 * 32 + 160];
    uint4 acc[2][216 * 8];
    uint4 ay[160];
    uint4 ah[NG * 8];
    uint2 mx[NH * 32];
    uint32_t ticket[32];
    uint32_t pad1[32];
};
__device__ Scratch g_scr;
#define PROF_T(i)
#define PROF_X(i)
#define PC(i)

__device__ __forceinline__ uint32_t smem_u32(const void* p) { return (uint32_t)__cvta_generic_to_shared(p); }
__device__ __forceinline__ void mbar_init(uint32_t bar, uint32_t cnt) {
    asm volatile("mbarrier.init.shared::cta.b64 [%0], %1;" ::"r"(bar), "r"(cnt) : "memory");
}
__device__ __forceinline__ void mbar_expect_tx(uint32_t bar, uint32_t bytes) {
    asm volatile("mbarrier.arrive.expect_tx.shared::cta.b64 _, [%0], %1;" ::"r"(bar), "r"(bytes) : "memory");
}
__device__ __forceinline__ bool mbar_test(uint32_t bar, uint32_t parity) {
    uint32_t done;
    asm volatile("{\n.reg .pred p;\nmbarrier.try_wait.parity.shared::cta.b64 p, [%1], %2;\nselp.u32 %0, 1, 0, p;\n}"
                 : "=r"(done) : "r"(bar), "r"(parity) : "memory");
    return done;
}
__device__ __forceinline__ void mbar_wait(uint32_t bar, uint32_t parity) {
    int it = 0;
    while (!mbar_test(bar, parity) && ++it < SPIN_CAP) {}
}
__device__ __forceinline__ void tma2d(uint32_t dst, const CUtensorMap* map, int c0, int c1, uint32_t bar, unsigned long long pol) {
    asm volatile("cp.async.bulk.tensor.2d.shared::cluster.global.mbarrier::complete_tx::bytes.L2::cache_hint [%0], [%1, {%3, %4}], [%2], %5;"
                 ::"r"(dst), "l"(map), "r"(bar), "r"(c0), "r"(c1), "l"(pol) : "memory");
}
__device__ __forceinline__ void tma3d(uint32_t dst, const CUtensorMap* map, int c0, int c1, int c2, uint32_t bar, unsigned long long pol) {
    asm volatile("cp.async.bulk.tensor.3d.shared::cluster.global.mbarrier::complete_tx::bytes.L2::cache_hint [%0], [%1, {%3, %4, %5}], [%2], %6;"
                 ::"r"(dst), "l"(map), "r"(bar), "r"(c0), "r"(c1), "r"(c2), "l"(pol) : "memory");
}
__device__ __forceinline__ void tile_load(uint32_t dst, const CUtensorMap* map, int row, uint32_t bar, uint32_t dep, uint32_t zero) {
    asm volatile("{\n.reg .pred p;\n.reg .b32 n;\nmad.lo.u32 n, %5, %6, 6144;\nelect.sync _|p, 0xffffffff;\n"
                 "@p mbarrier.arrive.expect_tx.shared::cta.b64 _, [%2], n;\n"
                 "@p cp.async.bulk.tensor.2d.shared::cluster.global.mbarrier::complete_tx::bytes.L2::cache_hint [%0], [%1, {0, %3}], [%2], %4;\n}"
                 ::"r"(dst), "l"(map), "r"(bar), "r"(row), "l"(POL_EF), "r"(dep), "r"(zero) : "memory");
}
__device__ __forceinline__ void tile_keep(const CUtensorMap* map, int row) {
    asm volatile("{\n.reg .pred p;\nelect.sync _|p, 0xffffffff;\n"
                 "@p cp.async.bulk.prefetch.tensor.2d.L2.global.L2::cache_hint [%0, {0, %1}], %2;\n}"
                 ::"l"(map), "r"(row), "l"(POL_EN) : "memory");
}
__device__ __forceinline__ void tile_load_l1(uint32_t dst, const void* base, int row, uint32_t bar, int lane) {
    const char* g = static_cast<const char*>(base) + (size_t)row * 128 + lane * 16;
    const uint32_t s0 = dst + (lane >> 3) * 128 + (((lane & 7) ^ (lane >> 3)) << 4), s1 = s0 ^ 64;
#pragma unroll
    for (int k = 0; k < 12; k++)
        asm volatile("cp.async.ca.shared.global.L2::cache_hint [%0], [%1], 16, %2;" ::"r"(((k & 1) ? s1 : s0) + k * 512), "l"(g + k * 512), "l"(POL_EF) : "memory");
    asm volatile("cp.async.mbarrier.arrive.shared::cta.b64 [%0];" ::"r"(bar) : "memory");
    __syncwarp();
    if (lane == 0) asm volatile("mbarrier.arrive.shared::cta.b64 _, [%0];" ::"r"(bar) : "memory");
}
__device__ __forceinline__ bool elect_one() {
    uint32_t p;
    asm volatile("{\n.reg .pred p;\nelect.sync _|p, 0xffffffff;\nselp.u32 %0, 1, 0, p;\n}" : "=r"(p));
    return p;
}
__device__ __forceinline__ void lds128(uint32_t addr, uint32_t& a, uint32_t& b, uint32_t& c, uint32_t& d) {
    asm volatile("ld.shared.v4.u32 {%0,%1,%2,%3}, [%4];" : "=r"(a), "=r"(b), "=r"(c), "=r"(d) : "r"(addr) : "memory");
}
__device__ __forceinline__ void lds128p(uint32_t addr, uint32_t on, uint32_t& a, uint32_t& b, uint32_t& c, uint32_t& d) {
    asm volatile("{\n.reg .pred p;\nsetp.ne.u32 p, %5, 0;\n@p ld.shared.v4.u32 {%0,%1,%2,%3}, [%4];\n}" : "+r"(a), "+r"(b), "+r"(c), "+r"(d) : "r"(addr), "r"(on) : "memory");
}
__device__ __forceinline__ void lds64(uint32_t addr, uint32_t& a, uint32_t& b) {
    asm volatile("ld.shared.v2.u32 {%0,%1}, [%2];" : "=r"(a), "=r"(b) : "r"(addr) : "memory");
}
__device__ __forceinline__ void ldsm4t(uint32_t addr, uint32_t (&a)[4]) {
    asm volatile("ldmatrix.sync.aligned.m8n8.x4.trans.shared.b16 {%0,%1,%2,%3}, [%4];" : "=r"(a[0]), "=r"(a[1]), "=r"(a[2]), "=r"(a[3]) : "r"(addr) : "memory");
}
__device__ __forceinline__ void mma16816(float (&c)[4], uint32_t a0, uint32_t a1, uint32_t a2, uint32_t a3, uint32_t b0, uint32_t b1) {
    asm("mma.sync.aligned.m16n8k16.row.col.f32.bf16.bf16.f32 {%0,%1,%2,%3}, {%4,%5,%6,%7}, {%8,%9}, {%0,%1,%2,%3};"
        : "+f"(c[0]), "+f"(c[1]), "+f"(c[2]), "+f"(c[3]) : "r"(a0), "r"(a1), "r"(a2), "r"(a3), "r"(b0), "r"(b1));
}
__device__ __forceinline__ void mma16816v(float (&c)[4], uint32_t a0, uint32_t a1, uint32_t a2, uint32_t a3, uint32_t b0, uint32_t b1) {
    asm volatile("mma.sync.aligned.m16n8k16.row.col.f32.bf16.bf16.f32 {%0,%1,%2,%3}, {%4,%5,%6,%7}, {%8,%9}, {%0,%1,%2,%3};"
        : "+f"(c[0]), "+f"(c[1]), "+f"(c[2]), "+f"(c[3]) : "r"(a0), "r"(a1), "r"(a2), "r"(a3), "r"(b0), "r"(b1));
}
__device__ __forceinline__ int xpos(int w) {
    const int seg = w / 40, r = w - 40 * seg;
    return 40 * seg + (r < 32 ? (r & 16) + 4 * (r & 3) + ((r >> 2) & 3) : 32 + 2 * (r & 3) + ((r >> 2) & 1));
}
#define NA_LD ""
#define NA_ST ""
__device__ __forceinline__ void st_pkt(uint4* p, uint32_t a, uint32_t b, uint32_t c, uint32_t d) {
    asm volatile("{\n.reg .b128 t;\n.reg .b64 lo, hi;\nmov.b64 lo, {%1,%2};\nmov.b64 hi, {%3,%4};\nmov.b128 t, {lo,hi};\nst.relaxed.gpu.global" NA_ST ".b128 [%0], t;\n}"
                 ::"l"(p), "r"(a), "r"(b), "r"(c), "r"(d) : "memory");
}
__device__ __forceinline__ void red_pkt(uint4* p, float a, float b, float c) {
    asm volatile("red.relaxed.gpu.global.add.v4.f32 [%0], {%1,%2,%3,%4};" ::"l"(p), "f"(a), "f"(b), "f"(c), "f"(1.0f) : "memory");
}
__device__ __forceinline__ void st_pktp(uint4* p, uint32_t a, uint32_t b, uint32_t c, uint32_t d, bool on) {
    asm volatile("{\n.reg .pred p;\n.reg .b128 t;\n.reg .b64 lo, hi;\nsetp.ne.u32 p, %5, 0;\nmov.b64 lo, {%1,%2};\nmov.b64 hi, {%3,%4};\nmov.b128 t, {lo,hi};\n"
                 "@p st.relaxed.gpu.global.b128 [%0], t;\n}" ::"l"(p), "r"(a), "r"(b), "r"(c), "r"(d), "r"((uint32_t)on) : "memory");
}
__device__ __forceinline__ void st_pktfp(uint4* p, float a, float b, float c, float d, uint32_t bit, bool on) {
    st_pktp(p, __float_as_uint(a), __float_as_uint(b), __float_as_uint(c), (__float_as_uint(d) & ~1u) | bit, on);
}
__device__ __forceinline__ uint4 ld_pkt(const uint4* p) {
    uint4 v;
    asm volatile("{\n.reg .b128 t;\n.reg .b64 lo, hi;\nld.relaxed.gpu.global" NA_LD ".b128 t, [%4];\nmov.b128 {lo,hi}, t;\nmov.b64 {%0,%1}, lo;\nmov.b64 {%2,%3}, hi;\n}"
                 : "=r"(v.x), "=r"(v.y), "=r"(v.z), "=r"(v.w) : "l"(p) : "memory");
    return v;
}
__device__ __forceinline__ uint2 ld_pkt2(const uint2* p) {
    unsigned long long v;
    asm volatile("ld.relaxed.gpu.global" NA_LD ".b64 %0, [%1];" : "=l"(v) : "l"(p) : "memory");
    return make_uint2((uint32_t)v, (uint32_t)(v >> 32));
}
__device__ __forceinline__ void st_pkt2(uint2* p, uint32_t a, uint32_t b) {
    asm volatile("st.relaxed.gpu.global" NA_ST ".b64 [%0], %1;" ::"l"(p), "l"((unsigned long long)a | ((unsigned long long)b << 32)) : "memory");
}
__device__ __forceinline__ float ex2(float x) { float y; asm("ex2.approx.ftz.f32 %0, %1;" : "=f"(y) : "f"(x)); return y; }
__device__ __forceinline__ float rcp(float x) { float y; asm("rcp.approx.ftz.f32 %0, %1;" : "=f"(y) : "f"(x)); return y; }
__device__ __forceinline__ uint32_t pack2(float lo, float hi) {
    uint32_t r; asm("cvt.rn.bf16x2.f32 %0, %1, %2;" : "=r"(r) : "f"(hi), "f"(lo)); return r;
}
__device__ __forceinline__ float bf_lo(uint32_t w) { return __uint_as_float(w << 16); }
__device__ __forceinline__ float bf_hi(uint32_t w) { return __uint_as_float(w & 0xffff0000u); }
__device__ __forceinline__ float bfr(float x) { return bf_lo(pack2(x, 0.f)); }
__device__ __forceinline__ float f_(uint32_t u) { return __uint_as_float(u); }

template <int SK, typename AddrF>
__device__ __forceinline__ void gemv15(float (&cc)[3][4], uint32_t (&pre)[6][4], AddrF ad, uint32_t px, uint32_t px2, float& sv, float so) {
    uint32_t x0[4], x1[4], a[3][4];
    asm volatile("ld.shared.v4.u32 {%0,%1,%2,%3}, [%20];\nld.shared.v4.u32 {%4,%5,%6,%7}, [%20+64];\n"
                 "ldmatrix.sync.aligned.m8n8.x4.trans.shared.b16 {%8,%9,%10,%11}, [%21];\n"
                 "ldmatrix.sync.aligned.m8n8.x4.trans.shared.b16 {%12,%13,%14,%15}, [%22];\n"
                 "ldmatrix.sync.aligned.m8n8.x4.trans.shared.b16 {%16,%17,%18,%19}, [%23];\nbar.warp.sync 0xffffffff;"
                 : "=r"(x0[0]), "=r"(x0[1]), "=r"(x0[2]), "=r"(x0[3]), "=r"(x1[0]), "=r"(x1[1]), "=r"(x1[2]), "=r"(x1[3]),
                   "=r"(a[0][0]), "=r"(a[0][1]), "=r"(a[0][2]), "=r"(a[0][3]), "=r"(a[1][0]), "=r"(a[1][1]), "=r"(a[1][2]), "=r"(a[1][3]),
                   "=r"(a[2][0]), "=r"(a[2][1]), "=r"(a[2][2]), "=r"(a[2][3])
                 : "r"(px), "r"(ad(0) + 2 * SK), "r"(ad(1) + 2 * SK), "r"(ad(2) + 2 * SK) : "memory");
    __syncwarp();
    sv += __shfl_xor_sync(0xffffffffu, so, 16);
#pragma unroll
    for (int i = 0; i < 3; i++) {
        cc[i][0] = cc[i][1] = cc[i][2] = cc[i][3] = 0.f;
        mma16816v(cc[i], pre[i][0], pre[i][1], pre[i][2], pre[i][3], x0[0], x0[1]);
    }
    sv += __shfl_xor_sync(0xffffffffu, sv, 8);
#pragma unroll
    for (int i = 0; i < 3; i++) {
        mma16816v(cc[i], pre[3 + i][0], pre[3 + i][1], pre[3 + i][2], pre[3 + i][3], x0[2], x0[3]);
        ldsm4t(ad(i) + 3 * SK, pre[i]);
    }
    lds64(px2, x0[0], x0[1]);
    __syncwarp();
    sv += __shfl_xor_sync(0xffffffffu, sv, 4);
#pragma unroll
    for (int i = 0; i < 3; i++) {
        mma16816v(cc[i], a[i][0], a[i][1], a[i][2], a[i][3], x1[0], x1[1]);
        ldsm4t(ad(i) + 4 * SK, pre[3 + i]);
    }
    __syncwarp();
    sv += __shfl_xor_sync(0xffffffffu, sv, 2);
#pragma unroll
    for (int i = 0; i < 3; i++) mma16816v(cc[i], pre[i][0], pre[i][1], pre[i][2], pre[i][3], x1[2], x1[3]);
    sv += __shfl_xor_sync(0xffffffffu, sv, 1);
#pragma unroll
    for (int i = 0; i < 3; i++) mma16816v(cc[i], pre[3 + i][0], pre[3 + i][1], pre[3 + i][2], pre[3 + i][3], x0[0], x0[1]);
}
__device__ __forceinline__ void gemv15r(float (&cc)[3][4], const uint32_t (&pre)[6][4], const uint32_t (&ext)[NQ][4], uint32_t px, uint32_t px2, float& sv, float so) {
    uint32_t x0[4], x1[4], x2[2];
    float cd[3][4];
    lds128(px, x0[0], x0[1], x0[2], x0[3]);
    lds128(px + 64, x1[0], x1[1], x1[2], x1[3]);
    lds64(px2, x2[0], x2[1]);
    sv += __shfl_xor_sync(0xffffffffu, so, 16);
#pragma unroll
    for (int i = 0; i < 3; i++) {
        cc[i][0] = cc[i][1] = cc[i][2] = cc[i][3] = cd[i][0] = cd[i][1] = cd[i][2] = cd[i][3] = 0.f;
        mma16816v(cc[i], pre[i][0], pre[i][1], pre[i][2], pre[i][3], x0[0], x0[1]);
        mma16816v(cd[i], pre[3 + i][0], pre[3 + i][1], pre[3 + i][2], pre[3 + i][3], x0[2], x0[3]);
    }
    sv += __shfl_xor_sync(0xffffffffu, sv, 8);
#pragma unroll
    for (int i = 0; i < 3; i++) {
        mma16816v(cc[i], ext[i][0], ext[i][1], ext[i][2], ext[i][3], x1[0], x1[1]);
        mma16816v(cd[i], ext[3 + i][0], ext[3 + i][1], ext[3 + i][2], ext[3 + i][3], x1[2], x1[3]);
    }
    sv += __shfl_xor_sync(0xffffffffu, sv, 4);
#pragma unroll
    for (int i = 0; i < 3; i++) mma16816v(cc[i], ext[6 + i][0], ext[6 + i][1], ext[6 + i][2], ext[6 + i][3], x2[0], x2[1]);
    sv += __shfl_xor_sync(0xffffffffu, sv, 2);
    sv += __shfl_xor_sync(0xffffffffu, sv, 1);
#pragma unroll
    for (int i = 0; i < 3; i++) { cc[i][0] += cd[i][0]; cc[i][1] += cd[i][1]; cc[i][2] += cd[i][2]; cc[i][3] += cd[i][3]; }
}

__device__ __forceinline__ float warp_max(float x) {
    int i = __float_as_int(x);
    i = __reduce_max_sync(0xffffffffu, i ^ ((i >> 31) & 0x7fffffff));
    return __int_as_float(i ^ ((i >> 31) & 0x7fffffff));
}
__device__ __forceinline__ void idle(uint32_t clk) {
    uint32_t t0, t;
    asm volatile("mov.u32 %0, %%clock;" : "=r"(t0) :: "memory");
    do asm volatile("mov.u32 %0, %%clock;" : "=r"(t) :: "memory"); while (t - t0 < clk);
}
__device__ __forceinline__ uint32_t now_ns() { uint32_t t; asm volatile("mov.u32 %0, %%globaltimer_lo;" : "=r"(t)); return t; }
__device__ __forceinline__ int opq(int x) { asm volatile("" : "+r"(x)); return x; }
__device__ __forceinline__ uint32_t opq(uint32_t x) { asm volatile("" : "+r"(x)); return x; }
__device__ __forceinline__ uint32_t pin(uint32_t x) { return __shfl_sync(0xffffffffu, x, threadIdx.x & 31); }
template <typename T> __device__ __forceinline__ T* pin(T* p) {
    const unsigned long long v = (unsigned long long)p;
    return (T*)((unsigned long long)pin((uint32_t)v) | (unsigned long long)pin((uint32_t)(v >> 32)) << 32);
}
template <typename T> __device__ __forceinline__ T* opq(T* p) { asm volatile("" : "+l"(p)); return p; }
__device__ __forceinline__ float4 lds4f(uint32_t a) { float4 v; asm volatile("ld.shared.v4.f32 {%0,%1,%2,%3}, [%4];" : "=f"(v.x), "=f"(v.y), "=f"(v.z), "=f"(v.w) : "r"(a) : "memory"); return v; }
__device__ __forceinline__ float2 lds2f(uint32_t a) { float2 v; asm volatile("ld.shared.v2.f32 {%0,%1}, [%2];" : "=f"(v.x), "=f"(v.y) : "r"(a) : "memory"); return v; }
__device__ __forceinline__ void ln_stats(uint32_t st, float& mean, float& inv) {
    const float4 a = lds4f(st), b = lds4f(st + 16), c = lds4f(st + 32), d = lds4f(st + 48);
    const float s2 = ((a.x + a.z) + (b.x + b.z)) + ((c.x + c.z) + (d.x + d.z));
    const float md = (((a.y + a.w) + (b.y + b.w)) + ((c.y + c.w) + (d.y + d.w))) * (1.0f / DM);
    const float var = fmaxf(s2 * (1.0f / DM) - md * md, 0.f);
    mean = bfr(md);
    asm("rsqrt.approx.ftz.f32 %0, %1;" : "=f"(inv) : "f"(var + 1e-5f));
}
__device__ __forceinline__ void sts32(uint32_t a, float v) { asm volatile("st.shared.f32 [%0], %1;" ::"r"(a), "f"(v) : "memory"); }
__device__ __forceinline__ void sts32p(uint32_t a, float v, uint32_t off) {
    asm volatile("{\n.reg .pred p;\nsetp.eq.u32 p, %2, 0;\n@p st.shared.f32 [%0], %1;\n}" ::"r"(a), "f"(v), "r"(off) : "memory");
}
__device__ __forceinline__ void sts128p(uint32_t a, float x, float y, float z, float w, uint32_t off) {
    asm volatile("{\n.reg .pred p;\nsetp.eq.u32 p, %5, 0;\n@p st.shared.v4.f32 [%0], {%1,%2,%3,%4};\n}" ::"r"(a), "f"(x), "f"(y), "f"(z), "f"(w), "r"(off) : "memory");
}
__device__ __forceinline__ void sts64(uint32_t a, float v, float w) { asm volatile("st.shared.v2.f32 [%0], {%1,%2};" ::"r"(a), "f"(v), "f"(w) : "memory"); }

__device__ __forceinline__ uint32_t prmt(uint32_t a, uint32_t b, uint32_t s) { uint32_t r; asm("prmt.b32 %0, %1, %2, %3;" : "=r"(r) : "r"(a), "r"(b), "r"(s)); return r; }
__device__ __forceinline__ uint32_t bmul2(uint32_t a, uint32_t b) { uint32_t r; asm("mul.rn.bf16x2 %0, %1, %2;" : "=r"(r) : "r"(a), "r"(b)); return r; }
__device__ __forceinline__ void sts128(uint32_t addr, uint32_t a, uint32_t b, uint32_t c, uint32_t d) {
    asm volatile("st.shared.v4.u32 [%0], {%1,%2,%3,%4};" ::"r"(addr), "r"(a), "r"(b), "r"(c), "r"(d) : "memory");
}
__device__ __forceinline__ uint4 ldg128(const uint4* p) {
    uint4 v;
    asm volatile("ld.volatile.global.v4.u32 {%0,%1,%2,%3}, [%4];" : "=r"(v.x), "=r"(v.y), "=r"(v.z), "=r"(v.w) : "l"(p) : "memory");
    return v;
}
__device__ __forceinline__ uint32_t lds32(uint32_t a) { uint32_t v; asm volatile("ld.shared.u32 %0, [%1];" : "=r"(v) : "r"(a) : "memory"); return v; }
__device__ __forceinline__ uint32_t lds16(uint32_t a) { unsigned short v; asm volatile("ld.shared.u16 %0, [%1];" : "=h"(v) : "r"(a) : "memory"); return v; }
__device__ __forceinline__ void unpack8(uint32_t la, uint32_t lb, uint32_t c, uint32_t (&w)[4]) {
    const uint32_t ha = c & 0x87878787u, hb = __funnelshift_l(c, c, 4) & 0x87878787u;
    w[0] = prmt(la, ha, 0x5140); w[1] = prmt(la, ha, 0x7362); w[2] = prmt(lb, hb, 0x5140); w[3] = prmt(lb, hb, 0x7362);
}
__device__ __forceinline__ uint32_t bdiff2(uint32_t y, uint32_t inv, uint32_t x) {
    uint32_t r;
    asm("{\n.reg .b32 n;\nneg.bf16x2 n, %3;\nfma.rn.bf16x2 %0, %1, %2, n;\n}" : "=r"(r) : "r"(y), "r"(inv), "r"(x));
    return r;
}
__device__ __forceinline__ uint32_t pack_scale(uint32_t tile, int lane, uint32_t inv_addr) {
    uint32_t m = 0;
#pragma unroll 1
    for (int k = 0; k < 12; k++) {
        uint32_t a, b, c, d;
        lds128(tile + k * 512 + lane * 16, a, b, c, d);
        asm("max.xorsign.abs.bf16x2 %0, %0, %1;" : "+r"(a) : "r"(b));
        asm("max.xorsign.abs.bf16x2 %0, %0, %1;" : "+r"(c) : "r"(d));
        asm("max.xorsign.abs.bf16x2 %0, %0, %1;" : "+r"(a) : "r"(c));
        asm("max.xorsign.abs.bf16x2 %0, %0, %1;" : "+r"(m) : "r"(a));
    }
    m = __reduce_max_sync(0xffffffffu, max(m & 0x7fffu, (m >> 16) & 0x7fffu));
    const uint32_t inv = (112u + min((m + 0x28u) >> 7, 141u)) * 0x00800080u;
    if (lane == 0) asm volatile("st.shared.u32 [%0], %1;" ::"r"(inv_addr), "r"(inv) : "memory");
    return inv;
}

#define K_OFF(i) ((uint32_t)((3 * ((g >> 1) + 4 * (g & 1)) + ((i) >> 1)) * 128 + ((t ^ ((3 * ((g >> 1) + 4 * (g & 1)) + ((i) >> 1)) & 7) ^ (((i) & 1) << 2)) << 4)))
#define V_OFF(i) ((uint32_t)((6 * t + (i)) * 128 + ((g ^ ((6 * t + (i)) & 7)) << 4)))
template <bool ISV, typename DST>
__device__ __forceinline__ void pack_tile(uint32_t tile, int tau, int nm, uint32_t inv, uint32_t xl, int lane, DST dst) {
    const int g = lane >> 2, t = lane & 3;
    const uint32_t scl = 254u * 0x00800080u - inv;
#pragma unroll 1
    for (int m = 0; m < nm; m++) {
        const int row = ISV ? 6 * t + 2 * m : 3 * ((g >> 1) + 4 * (g & 1)) + m;
        const uint32_t a0 = tile + row * 128 + (((ISV ? g : t) ^ (row & 7)) << 4), a1 = ISV ? (a0 ^ 16) + 128 : a0 ^ 64;
        uint32_t l[8], cw[4], ck = 0, cd = 0;
#pragma unroll
        for (int r = 0; r < 4; r++) {
            uint32_t w0, w1, w2, w3;
            lds128(((r & 1) ? a1 : a0) + (r >> 1) * 3072, w0, w1, w2, w3);
            const uint32_t y0 = bmul2(w0, scl), y1 = bmul2(w1, scl), y2 = bmul2(w2, scl), y3 = bmul2(w3, scl);
            cd |= bdiff2(y0, inv, w0) | bdiff2(y1, inv, w1);
            cd |= bdiff2(y2, inv, w2) | bdiff2(y3, inv, w3);
            const uint32_t ha = prmt(y0, y1, 0x7531), hb = prmt(y2, y3, 0x7531);
            l[2 * r] = prmt(y0, y1, 0x6420); l[2 * r + 1] = prmt(y2, y3, 0x6420);
            asm("lop3.b32 %0, %1, 0x87878787, %2, 0xe2;" : "=r"(cw[r]) : "r"(ha), "r"(__funnelshift_r(hb, hb, 4)));
            ck |= ha | hb;
        }
        const uint32_t bad = __ballot_sync(0xffffffffu, (ck & 0x78787878u) | cd);
        if (bad) {
            const int src = __ffs(bad) - 1;
            const uint32_t b0 = __shfl_sync(0xffffffffu, a0, src), b1 = __shfl_sync(0xffffffffu, a1, src), n0 = lds32(xl);
            const uint32_t ax = ((lane & 8) ? b1 : b0) + (lane >> 4) * 3072 + 2 * (lane & 7), x = lds16(ax), y = bmul2(x, scl);
            const bool out = (y & 0x7800u) | bdiff2(y, inv, x);
            const uint32_t n = n0 + __popc(__ballot_sync(0xffffffffu, out) << (31 - lane)) - 1;
            if (out) {
                asm volatile("st.shared.u16 [%0], %1;" ::"r"(ax), "h"((unsigned short)0) : "memory");
                if (n < XCAP) sts32(xl + 16 + 4 * n, f_(x << 16 | tau << 12 | src << 7 | m << 5 | lane));
            }
            if (lane == 31) sts32(xl, f_(n + 1));
            __syncwarp();
            if (n0 <= XCAP) { m--; continue; }
        }
        uint32_t d[3] = {a0, a1, a0 + 3072};
        dst(m, d);
        sts128(d[0], l[0], l[1], l[2], l[3]);
        sts128(d[1], l[4], l[5], l[6], l[7]);
        sts128(d[2], cw[0], cw[1], cw[2], cw[3]);
    }
}

struct Maps { CUtensorMap k, v, wq, wo, w1, w3, w2, vr; const void* vp; const void* kp; uint32_t zero; };
#define RT_SEL ((wu & 1) ? RT_MASK2 : RT_MASK)
#define PFK 5
#define Q_AT 3
#define WO_T0 32200
#define K5D 370
#define PK_AT 6

__device__ __forceinline__ void load_ffn(const Maps& maps, int b, uint32_t dst, uint32_t bar) {
    const bool gu = b < NG;
    mbar_expect_tx(bar, gu ? 61440 : 49152);
    tma3d(dst, gu ? (b < NG / 2 ? &maps.w1 : &maps.w3) : &maps.w2, gu ? 48 * (b & (NG / 2 - 1)) : 16 * (b - DN0), 0, 0, bar, FFN_POL);
}

__device__ __forceinline__ void load_wo(const Maps& maps, uint32_t dst, int h, int c, uint32_t bar, int nbox) {
#pragma unroll 1
    for (int i = 0; i < nbox; i++) {
        if (!(i & 1)) mbar_expect_tx(bar + 4 * i, i + 1 < nbox ? 20480 : 10240);
        tma3d(dst + i * 10240, &maps.wo, 0, 5 * c, h * DH + 32 * i, bar + 4 * (i & 6), POL_EF);
    }
}

__global__ void __launch_bounds__(NT, 1)
decode_kernel(const __grid_constant__ Maps maps, const __nv_bfloat16* __restrict__ x_in, __nv_bfloat16* __restrict__ out) {
    extern __shared__ __align__(1024) unsigned char smem[];
    const int tid = threadIdx.x, warp = tid >> 5, lane = tid & 31;
    const int wu = __shfl_sync(0xffffffffu, tid >> 5, 0);
    const int b = blockIdx.x, h = b >> 2, c = b & 3;
    const uint32_t sb = smem_u32(smem);
    const uint32_t qbar = sb + SM_BAR + 16 * 8, fbar = qbar + 8, wbar = qbar + 16;
    uint32_t* xs32 = reinterpret_cast<uint32_t*>(smem + SM_XS);
    float* rr = reinterpret_cast<float*>(smem + SM_R);
    float* misc = reinterpret_cast<float*>(smem + SM_MISC);

    PROF_T(0);
    {
        uint2 xv = make_uint2(0u, 0u);
        const uint32_t t_start = now_ns();
        if (elect_one()) {
            const uint32_t rb = sb + SM_BAR + wu * 16, xb = sb + SM_XBAR + wu * 8;
            mbar_init(rb, 1); mbar_init(rb + 8, 1); mbar_init(xb, 1);
            if (wu == 0) mbar_init(qbar, 1);
            asm volatile("fence.mbarrier_init.release.cluster;" ::: "memory");
            const int row = (h * SK + (SK - WIN) + c * 1024 + wu * 128) * 3;
            const uint32_t ring = sb + SM_RING + wu * 2 * TILE;
#pragma unroll
            for (int n = 0; n < 3; n++) {
                const uint32_t bar = ((IN_S1 >> n) & 1) ? rb + 8 : ((IN_S0 >> n) & 1) ? rb : xb;
                mbar_expect_tx(bar, TILE);
                tma2d(((IN_S1 >> n) & 1) ? ring + TILE : ((IN_S0 >> n) & 1) ? ring : sb + SM_B + wu * TILE, &maps.k, 0, row + 48 * n, bar, POL_EF);
                if (n == 0 && wu == 0) {
                    mbar_expect_tx(qbar, 61440);
                    tma3d(sb + SM_Q, &maps.wq, 0, 160 * c, 3 * h, qbar, POL_EF);
                }
            }
            if (wu == 1) {
                mbar_init(fbar, 1);
#pragma unroll
                for (int i = 0; i < 3; i++) mbar_init(wbar + 8 * i, 1);
                asm volatile("fence.mbarrier_init.release.cluster;" ::: "memory");
            }
            if (wu >= 2) {
                const CUtensorMap* mp = wu == 2 ? &maps.v : wu == 3 ? &maps.wo : wu == 4 ? &maps.w1 : wu == 5 ? &maps.w3 : wu == 6 ? &maps.w2 : &maps.vr;
                asm volatile("prefetch.tensormap [%0];" ::"l"(mp) : "memory");
            }
        }
        if (tid < 160) asm volatile("ld.global.nc.v2.u32 {%0,%1}, [%2];" : "=r"(xv.x), "=r"(xv.y) : "l"(x_in + 4 * tid) : "memory");
        if (tid == 96) { misc[2] = 0.f; misc[3] = 0.f; }
        if (lane == 1) *reinterpret_cast<uint2*>(smem + SM_XL + warp * XSTR) = make_uint2(0u, t_start + WO_T0);
        if (tid >= 128 && tid < 148) {
            const uint32_t v = tid < 138 ? ONES : 0u;
            reinterpret_cast<uint4*>(smem + SM_ONE)[tid - 128] = make_uint4(v, v, v, v);
        }
        if (tid < 160) { xs32[xpos(2 * tid)] = xv.x; xs32[xpos(2 * tid + 1)] = xv.y; }
        __syncthreads();
        PROF_T(14);
        if (b == 0 && tid >= 232) asm volatile("st.relaxed.gpu.global.u32 [%0], %1;" ::"l"(g_scr.ticket + tid - 232), "r"(0) : "memory");
        if (tid == 64 || (tid == 65 && b < 216 - NCTA)) st_pkt(&g_scr.acc[1][(b + NCTA * (tid - 64)) * ACC_STR], 0, 0, 0, 0);
    }

    uint32_t kq[NQ][4];
    const float SC = 0.07216878364870322f * 1.4426950408889634f;

#pragma unroll 1
    for (int ph = 0; ph < 3; ph++) {
        const int layer = ph >> 1;
        const uint32_t tag = layer + 1;
        PROF_T(1 + layer * 16);
        if (ph) {
        {
            const int tl = opq(tid), warp = tl >> 5, lane = tl & 31, g = lane >> 2, t = lane & 3, mat = lane >> 3, r8 = lane & 7;
            const int kh = warp >> 2, mg = warp & 3;
            uint32_t aq[3];
#pragma unroll
            for (int i = 0; i < 3; i++) {
                const int ch = 6 * mg + 2 * i + (mat & 1);
                aq[i] = sb + SM_Q + (80 * kh + (mat >> 1) * 8 + r8) * 128 + (ch >> 3) * 20480 + (((ch & 7) ^ r8) << 4);
            }
#define PF_K5 if (layer == 1 && PFK) tile_keep(&maps.k, (h * SK + (SK - WIN) + c * 1024 + wu * 128 + PFK * 16) * 3);
            uint2 xv = make_uint2(0u, 0u);
            mbar_wait(qbar, 0);
            uint32_t pre[6][4];
#pragma unroll
            for (int n = 0; n < 6; n++) ldsm4t(aq[n % 3] + (n / 3) * 2048, pre[n]);
            if (layer == 1) {
                __syncthreads();
                if (elect_one()) {
                    const uint32_t bar = sb + SM_BAR + wu * 16;
                    asm volatile("mbarrier.expect_tx.relaxed.cta.shared::cta.b64 [%0], 1536;" ::"r"(bar) : "memory");
#pragma unroll
                    for (int k = 0; k < 3; k++)
                        tma2d(sb + SM_Q + v1_pos(3 * wu + k), &maps.vr, 0, (h * SK + (SK - WIN) + c * 1024 + wu * 128) / 2 + 8 + 2 * k, bar, POL_EF);
                }
            }
            const uint32_t pm = opq(g == 1 ? sb + SM_ONE : sb + SM_XS + 160 * (2 * c + kh) + 16 * t), pm2 = opq(pm + 128 - (g == 1 ? 0 : 8 * t));
            const uint32_t dq = opq(sb + SM_R + 8 * (kh * 192 + 48 * mg + g)), ds = opq(sb + SM_ST + 8 * warp + (lane < 16 ? 4 : 0));
            const bool wr = t == 0, ws = (lane & 15) == 0, lo = lane < 16;
            if (wu < 5) {
                const int p0 = xpos(2 * tl), p1 = xpos(2 * tl + 1);
                if (layer == 1) {
                    uint4 v;
                    int it = 0;
                    do { v = ld_pkt(&g_scr.ay[tl]); } while (!__all_sync(0xffffffffu, v.w == 1) && ++it < SPIN_CAP);
                    xv = make_uint2(v.x, v.y);
                    xs32[p0] = xv.x; xs32[p1] = xv.y;
                } else xv = make_uint2(xs32[p0], xs32[p1]);
            }
            if (layer) PC(24);
            if (layer) __syncthreads();
            PF_K5
            if (layer) PC(25);
            PROF_T(13 + layer * 16);
            const float e0 = bf_lo(xv.x), e1 = bf_hi(xv.x), e2 = bf_lo(xv.y), e3 = bf_hi(xv.y);
            const float s1 = (e0 + e1) + (e2 + e3), s2 = (e0 * e0 + e1 * e1) + (e2 * e2 + e3 * e3);
            float sv = lo ? s1 : s2, cc[3][4];
            gemv15<2048>(cc, pre, [&](int i) { return aq[i]; }, pm, pm2, sv, lo ? s2 : s1);
            if (wr) {
#pragma unroll
                for (int i = 0; i < 3; i++) { sts64(dq + 128 * i, cc[i][0], cc[i][1]); sts64(dq + 128 * i + 64, cc[i][2], cc[i][3]); }
            }
            if (ws) sts32(ds, sv);
        }
        const uint32_t pa = opq(sb + SM_R + 32 * opq(tid)), st = opq(sb + SM_ST);
        uint4* const pq = opq(&g_scr.hx[b * 48 + opq(tid)]);
        if (layer) PC(26);
        __syncthreads();
        if (layer) PC(27);
        PROF_T(33 + layer * 16);
        if (wu < 2) {
            float mean, inv;
            ln_stats(st, mean, inv);
            const float4 a0 = lds4f(pa), a1 = lds4f(pa + 16), b0 = lds4f(pa + 1536), b1 = lds4f(pa + 1552);
            float q0 = inv * ((a0.x + b0.x) - mean * (a0.y + b0.y)), q1 = inv * ((a0.z + b0.z) - mean * (a0.w + b0.w));
            float q2 = inv * ((a1.x + b1.x) - mean * (a1.y + b1.y)), q3 = inv * ((a1.z + b1.z) - mean * (a1.w + b1.w));
            st_pktfp(pq, q0, q1, q2, q3, 1, tid < 48);
        }
        if (layer == 1 && tid >= 192 && tid < 194 && b < 108) st_pkt(&g_scr.acc[0][(2 * b + opq(tid) - 192) * ACC_STR], 0, 0, 0, 0);
        }
        if (layer) PC(28);
        if (layer == 1 && (wu & 2)) {
            idle(K5D);
#pragma unroll 1
            for (int w = wu; w >= (wu > 4 ? wu - 2 : wu); w -= 2)
                tile_load(sb + SM_Q + c_slot(w), &maps.k, (h * SK + (SK - WIN) + c * 1024 + w * 128 + 5 * 16) * 3, sb + SM_XBAR + w * 8, 0, 0);
        }

        float sc0 = -INFINITY, sc1 = -INFINITY, sc2 = 0.f, sc3 = 0.f, mw;
        uint32_t pk0, pk1;
        float acc[3][4];
        {
            const uint32_t ring = sb + SM_RING + wu * 2 * TILE, rb = sb + SM_BAR + wu * 16;
            const uint32_t xtile = sb + SM_Q + c_slot(wu), xb = sb + SM_XBAR + wu * 8;
#define V_SEQ(n) ((int)(SEQ1 >> (4 * (n))) & 7)
#define SLOT1(n) (((IN_S1 >> (n)) & 1) ? ring + TILE : ((IN_S0 >> (n)) & 1) ? ring : sb + SM_B + wu * TILE)
#define BAR1(n) (((IN_S1 >> (n)) & 1) ? rb + 8 : ((IN_S0 >> (n)) & 1) ? rb : xb)
#define PAR1(n) ((PARITY1 >> (n)) & 1)
#define PAR2(n) ((PARITY2 >> (n)) & 1)
            const int row0 = (h * SK + (SK - WIN) + c * 1024 + wu * 128) * 3;
            auto issue1 = [&](int n, uint32_t dep, bool vph = false) {
                const CUtensorMap* mp = n < 8 ? &maps.k : &maps.v;
                const int tl = V_SEQ(n), row = row0 + tl * 48;
                const uint32_t dst = SLOT1(n), bar = BAR1(n);
                if (vph && wu < L1R && tl == 7 - (wu & 1)) {
                    tile_load_l1(dst, maps.vp, row, bar, opq(tid) & 31);
                    return;
                }
                tile_load(dst, mp, row, bar, dep, maps.zero);
                if ((RT_SEL >> (tl + (n & 8))) & 1) {
                    if (n != V0_AT + 1) tile_keep(mp, row);
                    else if ((opq(tid) & 31) < 8)
                        asm volatile("cp.async.bulk.prefetch.L2.global.L2::cache_hint [%0], 256, %1;"
                                     ::"l"(static_cast<const char*>(maps.vp) + (size_t)(row + 4 + 6 * (opq(tid) & 31)) * 128), "l"(POL_EN) : "memory");
                }
            };
            auto refill1 = [&](int s, uint32_t dep, bool vph = false) { issue1(s + (!vph || s < V0_AT ? 3 : 2), dep, vph); };
#define LANE_IDS const int tl = opq(tid), lane = tl & 31, g = lane >> 2, t = lane & 3; (void)tl; (void)lane; (void)g; (void)t;
            const uint32_t xl = sb + SM_XL + wu * XSTR;
            if (layer == 0) {
#pragma unroll 1
                for (int s = ph ? Q_AT : 0; s < (ph ? 5 : Q_AT); s++) {
                    LANE_IDS
                    const uint32_t tile = SLOT1(s);
                    mbar_wait(BAR1(s), PAR1(s));
                    const uint32_t scl = s == 0 ? pack_scale(tile, lane, xl + 8) : lds32(xl + 8);
                    pack_tile<false>(tile, s, 3, scl, xl, lane, [](int, uint32_t (&)[3]) {});
#pragma unroll
                    for (int n = 0; n < 5; n++) {
                        if (s == n) {
#pragma unroll
                            for (int m = 0; m < 3; m++) {
                                const uint32_t a = tile + K_OFF(2 * m);
                                lds128(a, kq[9 * n + 3 * m][0], kq[9 * n + 3 * m][1], kq[9 * n + 3 * m][2], kq[9 * n + 3 * m][3]);
                                lds128(a ^ 64, kq[9 * n + 3 * m + 1][0], kq[9 * n + 3 * m + 1][1], kq[9 * n + 3 * m + 1][2], kq[9 * n + 3 * m + 1][3]);
                                lds128(a + 3072, kq[9 * n + 3 * m + 2][0], kq[9 * n + 3 * m + 2][1], kq[9 * n + 3 * m + 2][2], kq[9 * n + 3 * m + 2][3]);
                            }
                        }
                    }
                    __syncwarp();
                    refill1(s, lds32(tile));
                }
                if (!ph) continue;
            }
            {
                if (wu < 2) {
                    const int tl = min(opq(tid), 47);
                    const int w = 2 * tl;
                    const uint32_t pos = opq(sb + SM_QS + 4 * (((w >> 2) & 3) * 24 + 2 * (w >> 4) + ((w >> 1) & 1)));
                    uint4 v[4];
                    int it = 0;
                    bool ok;
                    do {
#pragma unroll
                        for (int k = 0; k < 4; k++) v[k] = ld_pkt(&g_scr.hx[(h * 4 + k) * 48 + tl]);
                        ok = __all_sync(0xffffffffu, ((v[0].w & v[1].w) & (v[2].w & v[3].w)) & 1);
                    } while (!ok && ++it < SPIN_CAP);
                    sts32(pos, f_(pack2((f_(v[0].x) + f_(v[1].x)) + (f_(v[2].x) + f_(v[3].x)), (f_(v[0].y) + f_(v[1].y)) + (f_(v[2].y) + f_(v[3].y)))));
                    sts32(pos + 48, f_(pack2((f_(v[0].z) + f_(v[1].z)) + (f_(v[2].z) + f_(v[3].z)), (f_(v[0].w) + f_(v[1].w)) + (f_(v[2].w) + f_(v[3].w)))));
                }
            }
            if (layer) PC(29);
            __syncthreads();
            if (layer) PC(30);
            PROF_T(2 + layer * 16);
#define V1_REST(p) ((p) < 6 ? sb + SM_Q + v1_pos(3 * wu + ((p) >> 1)) + 256 * ((p) & 1) : ((sb + SM_R + wu * 784 + 127) & ~127u) - 1536 + 256 * (p))
#define V1_LOAD(bar) if (elect_one()) tma2d(V1_REST(6), &maps.vr, 0, row0 / 6 + 14, bar, POL_EF);
#define V1_EXPECT(bar) { if ((opq(tid) & 31) == 0) asm volatile("mbarrier.expect_tx.relaxed.cta.shared::cta.b64 [%0], 512;" ::"r"(bar) : "memory"); }
            if (layer == 1 && wu < 2) tile_load(xtile, &maps.k, row0 + 5 * 48, xb, 0, 0);
            if (layer == 1 && wu >= 4) idle(STAG);
            {
                uint32_t qf[12];
                int t;
                {
                    const int lane = opq(tid) & 31;
                    t = lane & 3;
                    const uint32_t qa = sb + SM_QS + (2 * t + ((lane >> 2) & 1)) * 48;
#pragma unroll
                    for (int i = 0; i < 3; i++) lds128(qa + 16 * i, qf[4 * i], qf[4 * i + 1], qf[4 * i + 2], qf[4 * i + 3]);
                }
                const uint32_t sq = lds32(xl + 8) - 64u * 0x00800080u;
#pragma unroll
                for (int i = 0; i < 12; i++) qf[i] = bmul2(qf[i], sq);
#define KR_STEP(tau, m) \
                    _Pragma("unroll") for (int i = 2 * (m); i < 2 * (m) + 2; i++) { \
                        const int q0 = 9 * tau + 3 * (i >> 1), r = i & 1; \
                        uint32_t w[4]; \
                        unpack8(kq[q0][2 * r], kq[q0][2 * r + 1], kq[q0 + 2][r], w); \
                        mma16816(cA, w[0], w[1], w[2], w[3], qf[2 * i], qf[2 * i + 1]); \
                        unpack8(kq[q0 + 1][2 * r], kq[q0 + 1][2 * r + 1], kq[q0 + 2][2 + r], w); \
                        mma16816(cB, w[0], w[1], w[2], w[3], qf[2 * i], qf[2 * i + 1]); \
                    }
#define KR_BEGIN float cA[4] = {0.f, 0.f, 0.f, 0.f}, cB[4] = {0.f, 0.f, 0.f, 0.f};
#define KR_END(tau) \
                    const float sA = (cA[0] + cA[3]) * 18446744073709551616.f, sB = (cB[0] + cB[3]) * 18446744073709551616.f; \
                    if (t == (tau & 3)) { if (tau < 4) { sc0 = sA; sc1 = sB; } else { sc2 = sA; sc3 = sB; } }
#define KR_SCORES(tau) { KR_BEGIN KR_STEP(tau, 0) KR_STEP(tau, 1) KR_STEP(tau, 2) KR_END(tau) }
                uint32_t va[3];
                {
                    const int lane = opq(tid) & 31, g = lane >> 2, t = lane & 3;
#pragma unroll
                    for (int i = 0; i < 3; i++) va[i] = ring + V_OFF(2 * i);
                }
#define V_STG(n) _Pragma("unroll") for (int j = 3 * (n); j < 3 * (n) + 3; j++) { \
                    const int i = (j % 12) >> 1; \
                    lds128p(((i & 1) ? (va[i >> 1] ^ 16) + 128 : va[i >> 1]) + (j / 12) * TILE + (j & 1) * 3072, layer, kq[j][0], kq[j][1], kq[j][2], kq[j][3]); }
                uint32_t dep = 0;
                {
                    KR_BEGIN
                    KR_STEP(0, 0) V_STG(0) KR_STEP(0, 1) V_STG(1) KR_STEP(0, 2) V_STG(2)
                    KR_END(0)
                }
                {
                    KR_BEGIN
                    KR_STEP(1, 0) V_STG(3)
                    __syncwarp();
                    dep = lds32(ring);
                    if (layer == 1) tile_load(ring, &maps.k, row0 + 6 * 48, rb, dep, maps.zero);
                    KR_STEP(1, 1) V_STG(4) KR_STEP(1, 2) V_STG(5)
                    KR_END(1)
                }
                {
                    KR_BEGIN
                    KR_STEP(2, 0) V_STG(6) KR_STEP(2, 1) V_STG(7)
                    __syncwarp();
                    dep = lds32(ring + TILE);
                    KR_STEP(2, 2)
                    if (layer == 1) {
                        V1_EXPECT(rb + 8)
                        tile_load(ring + TILE, &maps.k, row0 + 7 * 48, rb + 8, dep, maps.zero);
                        V1_LOAD(rb + 8)
                    }
                    KR_END(2)
                }
#pragma unroll 1
                for (int s = 5; s < 8; s++) {
                    {
                        LANE_IDS
                        const uint32_t tile = !layer ? SLOT1(s) : s == 5 ? xtile : ring + (s - 6) * TILE, tb = !layer ? BAR1(s) : s == 5 ? xb : rb + (s - 6) * 8;
                        const float ur = f_((318u << 23) - (lds32(xl + 8) << 16));
                        mbar_wait(tb, layer ? PAR2(s - 5) : PAR1(s));
                        if (layer) PROF_T(29 + s);
                        float cA[4] = {0.f, 0.f, 0.f, 0.f}, cB[4] = {0.f, 0.f, 0.f, 0.f};
#pragma unroll
                        for (int i = 0; i < 6; i++) {
                            uint32_t a0, a1, a2, a3;
                            lds128(tile + K_OFF(i), a0, a1, a2, a3);
                            mma16816(cA, a0, a1, a2, a3, qf[2 * i], qf[2 * i + 1]);
                            lds128(tile + K_OFF(i) + 3072, a0, a1, a2, a3);
                            mma16816(cB, a0, a1, a2, a3, qf[2 * i], qf[2 * i + 1]);
                        }
                        __syncwarp();
                        const uint32_t last = lds32(tile);
                        if (layer) tile_load(tile, &maps.v, row0 + (s - 2) * 48, tb, last, maps.zero);
                        else refill1(s, last);
                        if (t == (s & 3)) { sc2 = (cA[0] + cA[3]) * ur; sc3 = (cB[0] + cB[3]) * ur; }
                    }
                    if (s == 5) KR_SCORES(3)
                    if (s == 6) {
                        KR_SCORES(4)
                        const int lane = opq(tid) & 31;
                        const uint32_t nx = min(lds32(xl), (uint32_t)XCAP);
#pragma unroll 1
                        for (uint32_t n = 0; n < nx; n++) {
                            const uint32_t id = lds32(xl + 16 + 4 * n);
                            const uint32_t qo = 96 * ((id >> 7) & 3) + 48 * ((id >> 1) & 1) + 16 * ((id >> 5) & 3) + (id & 12) + 2 * (id & 1);
                            const float cr = bf_hi(id) * f_(lds16(sb + SM_QS + qo) << 16);
                            const int d = (int)(16 * ((id >> 9) & 7) + 4 * ((id >> 12) & 3) + ((id >> 13) & 2) + ((id >> 4) & 1) + ((id >> 8) & 128)) - 4 * lane;
                            if (d == 0) sc0 += cr;
                            if (d == 1) sc1 += cr;
                            if (d == 2) sc2 += cr;
                            if (d == 3) sc3 += cr;
                        }
                    }
                }
#undef KR_SCORES
#undef KR_STEP
#undef KR_BEGIN
#undef KR_END
#undef V_STG
                {
                    LANE_IDS
                    if (lds32(xl) > XCAP || !__all_sync(0xffffffffu, (fabsf(sc0) + fabsf(sc1)) + (fabsf(sc2) + fabsf(sc3)) < INFINITY)) {
                        const uint32_t qa = sb + SM_QS + (2 * t + (g & 1)) * 48;
#pragma unroll
                        for (int i = 0; i < 3; i++) lds128(qa + 16 * i, qf[4 * i], qf[4 * i + 1], qf[4 * i + 2], qf[4 * i + 3]);
                        const uint4* kg = reinterpret_cast<const uint4*>(static_cast<const char*>(maps.kp) + (size_t)row0 * 128) + ((g >> 1) + 4 * (g & 1)) * 24 + t;
#pragma unroll 1
                        for (int s = 0; s < 8; s++) {
                            float cA[4] = {0.f, 0.f, 0.f, 0.f}, cB[4] = {0.f, 0.f, 0.f, 0.f};
#pragma unroll
                            for (int i = 0; i < 6; i++) {
                                uint4 u = ldg128(kg + s * 384 + 4 * i);
                                mma16816v(cA, u.x, u.y, u.z, u.w, qf[2 * i], qf[2 * i + 1]);
                                u = ldg128(kg + s * 384 + 4 * i + 192);
                                mma16816v(cB, u.x, u.y, u.z, u.w, qf[2 * i], qf[2 * i + 1]);
                            }
                            if (t == s) { sc0 = cA[0] + cA[3]; sc1 = cB[0] + cB[3]; }
                            if (t + 4 == s) { sc2 = cA[0] + cA[3]; sc3 = cB[0] + cB[3]; }
                        }
                    }
                }
            }
            mw = warp_max(fmaxf(fmaxf(sc0, sc1), fmaxf(sc2, sc3)));
            pk0 = pack2(ex2((sc0 - mw) * SC), ex2((sc1 - mw) * SC));
            pk1 = pack2(ex2((sc2 - mw) * SC), ex2((sc3 - mw) * SC));
            sc2 = (bf_lo(pk0) + bf_hi(pk0)) + (bf_lo(pk1) + bf_hi(pk1));
            sc2 = (float)__reduce_add_sync(0xffffffffu, __float2uint_rn(sc2 * 16777216.f)) * (1.0f / 16777216.f);
            if ((opq(tid) & 31) == 0) st_pkt2(&g_scr.mx[h * 32 + c * 8 + wu], __float_as_uint(mw), (__float_as_uint(sc2) & ~3u) | tag);
            auto head_factor = [&]() {
                const int lane = opq(tid) & 31;
                int it = 0;
                while (!__all_sync(0xffffffffu, (__float_as_uint(sc1) & 3u) == tag) && ++it < SPIN_CAP) {
                    const uint2 mv = ld_pkt2(&g_scr.mx[h * 32 + lane]); sc0 = f_(mv.x); sc1 = f_(mv.y);
                }
                const float e = ex2((sc0 - warp_max(sc0)) * SC);
                const uint32_t d = __reduce_add_sync(0xffffffffu, __float2uint_rn(sc1 * e * 524288.f));
                sc3 = __shfl_sync(0xffffffffu, e, c * 8 + wu) * 524288.f * rcp((float)d);
            };
#pragma unroll
            for (int s = 0; s < 3; s++) { acc[s][0] = acc[s][1] = acc[s][2] = acc[s][3] = 0.f; }
#define P_CONSTS \
                const uint32_t sel0 = g == 0 ? 0x4410u : (g == 1 ? 0x1044u : 0x4444u); \
                const uint32_t sel1 = g == 2 ? 0x4410u : (g == 3 ? 0x1044u : 0x4444u); \
                const int src00 = 4 * (t < 2 ? 4 * t : 4 * (t - 2) + 1);
#define P_FRAGS(tau) \
                const uint32_t pk = ((tau) & 4) ? pk1 : pk0; \
                const uint32_t w0 = __shfl_sync(0xffffffffu, pk, src00 + ((tau) & 3)); \
                const uint32_t w1 = __shfl_sync(0xffffffffu, pk, src00 + ((tau) & 3) + 8); \
                uint32_t pb[4][2]; \
                _Pragma("unroll") for (int j = 0; j < 4; j++) { \
                    const uint32_t src = ((j & 1) ? w1 : w0) >> ((j >> 1) * 16); \
                    pb[j][0] = __byte_perm(src, 0, sel0); pb[j][1] = __byte_perm(src, 0, sel1); \
                }
            if (layer == 0) {
#pragma unroll 1
                for (int s = 8; s < 16; s++) {
                    LANE_IDS
                    P_CONSTS
                    if (s == 13) { const uint2 mv = ld_pkt2(&g_scr.mx[h * 32 + lane]); sc0 = f_(mv.x); sc1 = f_(mv.y); }
                    P_FRAGS(V_SEQ(s))
                    mbar_wait(BAR1(s), PAR1(s));
                    const uint32_t tile = SLOT1(s);
#pragma unroll
                    for (int j = 0; j < 4; j++) {
#pragma unroll
                        for (int u = 0; u < 3; u++) {
                            uint32_t a0, a1, a2, a3;
                            lds128(tile + (j >> 1) * 3072 + V_OFF(3 * (j & 1) + u), a0, a1, a2, a3);
                            mma16816(acc[u], a0, a1, a2, a3, pb[j][0], pb[j][1]);

                        }
                    }
                    __syncwarp();
                    if (s < V0_AT || (s > V0_AT + 1 && s < 14)) refill1(s, lds32(tile), true);
                    if (s == V0_AT || s == V0_AT + 1) {
                        {
                            const uint32_t ar = sb + SM_R + wu * 784 + 32 * g + 16 * t;
                            if (t < 2) {
#pragma unroll
                                for (int u = 0; u < 3; u++) sts128(ar + 256 * u, __float_as_uint(acc[u][0]), __float_as_uint(acc[u][1]), __float_as_uint(acc[u][2]), __float_as_uint(acc[u][3]));
                            }
                        }
                        const uint32_t scl = s == V0_AT ? pack_scale(tile, lane, xl + 12) : lds32(xl + 12);
                        pack_tile<true>(tile, s + 8 - V0_AT, V0_AT + 3 - s, scl, xl, lane, [&](int m, uint32_t (&d)[3]) {
                            if (s != V0_AT && m == 0) {
#pragma unroll
                                for (int k = 0; k < 3; k++) d[k] = ring + 3072 + V_OFF(2 * k + 1);
                            }
                        });
                        if (s != V0_AT) {
                            lds128(tile + V_OFF(2), kq[45][0], kq[45][1], kq[45][2], kq[45][3]);
                            lds128(tile + V_OFF(3), kq[46][0], kq[46][1], kq[46][2], kq[46][3]);
                            lds128(tile + V_OFF(2) + 3072, kq[47][0], kq[47][1], kq[47][2], kq[47][3]);
                            __syncwarp();
                            issue1(V0_AT + 3, lds32(tile));
                        }
                        const int ln = opq(tid) & 31;
                        const uint32_t ar = sb + SM_R + wu * 784 + 8 * (ln & 28) + 16 * (ln & 1);
#pragma unroll
                        for (int u = 0; u < 3; u++) {
                            uint32_t a0, a1, a2, a3;
                            lds128(ar + 256 * u, a0, a1, a2, a3);
                            acc[u][0] = f_(a0); acc[u][1] = f_(a1); acc[u][2] = f_(a2); acc[u][3] = f_(a3);
                        }
                    }
                    if (s == 13) head_factor();
                    if (s >= 14 && elect_one()) {
                        if (atomicAdd(reinterpret_cast<unsigned*>(misc + 3), 1u) == 14u && (int)(now_ns() - lds32(xl + 4)) >= 0) {
                            PROF_X(47);
                            load_wo(maps, sb + SM_B, h, c, wbar, 6);
                            atomicAdd(reinterpret_cast<unsigned*>(misc + 3), 256u);
                        }
                    }
                }
            } else {
                LANE_IDS
                P_CONSTS
#pragma unroll
                for (int k = 0; k < 4; k++) lds128(V1_REST(t + 4 * (k >> 1)) + 16 * g + 128 * (k & 1), kq[36 + k][0], kq[36 + k][1], kq[36 + k][2], kq[36 + k][3]);
#pragma unroll 1
                for (int i = 3; i < 8; i++) {
                    const uint32_t tile = i > 3 ? ring + (i & 1) * TILE : xtile, tb = i > 3 ? rb + (i & 1) * 8 : xb;
                    if (i == 6) { const uint2 mv = ld_pkt2(&g_scr.mx[h * 32 + lane]); sc0 = f_(mv.x); sc1 = f_(mv.y); }
                    if (i == 7) head_factor();
                    if (i == PK_AT) {
                uint32_t nx, nk, ik, iv;
                lds128(xl, nx, nk, ik, iv);
                if (nx <= XCAP) {
                    const uint32_t pks = bmul2(pk0, iv);
#pragma unroll
                    for (int s = 0; s < 2; s++) {
                        const uint32_t pk1 = 0, pk0 = pks;
                        P_FRAGS(s)
#pragma unroll
                        for (int j = 0; j < 4; j++) {
#pragma unroll
                            for (int u = 0; u < 3; u++) {
                                const int i = 3 * (j & 1) + u, m = i >> 1, r = i & 1, hf = j >> 1;
                                if (s == 1 && m == 2) continue;
                                const int ql = s == 0 ? 4 * m + 2 * hf : m == 0 ? 3 + 4 * hf : 45 + hf, qc = s == 0 ? 4 * m + 1 : m == 0 ? 11 : 47;
                                uint32_t w[4];
                                unpack8(kq[ql][2 * r], kq[ql][2 * r + 1], kq[qc][2 * hf + r], w);
                                mma16816(acc[u], w[0], w[1], w[2], w[3], pb[j][0], pb[j][1]);
                            }
                        }
                    }
#pragma unroll 1
                    for (uint32_t n = 0; n < nx; n++) {
                        const uint32_t id = lds32(xl + 16 + 4 * n);
                        const int i = ((id >> 4) & 6) + ((id >> 3) & 1), key = ((id >> 6) & 6) + (i >= 3);
                        const uint32_t pw = __shfl_sync(0xffffffffu, pk0, 8 * (key & 3) + (key & 4) + ((id >> 12) & 3));
                        const float cr = bf_hi(id) * ((id & 16) ? bf_hi(pw) : bf_lo(pw));
                        const int d = (int)(64 * ((id >> 9) & 7) + 4 * (id & 4) + 4 * (i >= 3 ? i - 3 : i) + (id & 3) + ((~id >> 5) & 1024)) - 16 * lane;
#pragma unroll
                        for (int k = 0; k < 12; k++) if (d == k) acc[k >> 2][k & 3] += cr;
                    }
                } else {
                    const uint4* vg = reinterpret_cast<const uint4*>(static_cast<const char*>(maps.vp) + (size_t)row0 * 128) + 48 * t + g;
#pragma unroll 1
                    for (int s = 0; s < 2; s++) {
                        P_FRAGS(s)
#pragma unroll
                        for (int j = 0; j < 4; j++) {
#pragma unroll
                            for (int u = 0; u < 3; u++) {
                                if (s == 1 && (j & 1) && u) continue;
                                const uint4 w = ldg128(vg + 384 * s + 192 * (j >> 1) + 24 * (j & 1) + 8 * u);
                                mma16816v(acc[u], w.x, w.y, w.z, w.w, pb[j][0], pb[j][1]);
                            }
                        }
                    }
                }
#pragma unroll
                for (int s = 2; s > 0; s--) {
                    P_FRAGS(s)
#pragma unroll
                    for (int j = 0; j < 4; j++) {
#pragma unroll
                        for (int u = 0; u < 3; u++) {
                            if (s == 1 && !((j & 1) && u)) continue;
                            const int k = s == 2 ? 12 + 2 * (3 * (j & 1) + u) + (j >> 1) : 35 + (j >> 1) * 2 + u;
                            mma16816(acc[u], kq[k][0], kq[k][1], kq[k][2], kq[k][3], pb[j][0], pb[j][1]);
                        }
                    }
                }
                    }
                    P_FRAGS(i)
                    mbar_wait(tb, PAR2(i));
                    PROF_T(34 + i);
#pragma unroll
                    for (int k = 0; k < 6; k++) {
                        const uint32_t a = tile + V_OFF(k);
                        lds128(a, kq[24 + k][0], kq[24 + k][1], kq[24 + k][2], kq[24 + k][3]);
                        lds128(a + 3072, kq[30 + k][0], kq[30 + k][1], kq[30 + k][2], kq[30 + k][3]);
                    }
#pragma unroll
                    for (int j = 0; j < 4; j++) {
#pragma unroll
                        for (int u = 0; u < 3; u++) {
                            const int k = 24 + 6 * (j >> 1) + 3 * (j & 1) + u;
                            mma16816(acc[u], kq[k][0], kq[k][1], kq[k][2], kq[k][3], pb[j][0], pb[j][1]);
                        }
                    }
                    __syncwarp();
                    if (wu < L1R && i == 5 - (wu & 1)) tile_load_l1(tile, maps.vp, row0 + (i + 2) * 48, tb, lane);
                    else if (i == 4 || i == 5) tile_load(tile, &maps.v, row0 + (i + 2) * 48, tb, lds32(tile), maps.zero);
                    if (i == WO_AT1 && HAS_FFN && elect_one()) {
                        if (atomicAdd(reinterpret_cast<unsigned*>(misc + 2), 1u) == 7u) {
                            PROF_X(63);
                            load_wo(maps, sb + SM_Q, h, c, wbar, KEEP4 && __float_as_uint(misc[1]) >= DN0 ? 5 : 6);
                        }
                    }
                }
            }
#undef P_FRAGS
#undef P_CONSTS
#undef LANE_IDS
        }
        PROF_T(3 + layer * 16);
        PC(layer * 32 + 1);

        {
            const int lane = opq(tid) & 31;
            const uint32_t a = sb + SM_R + wu * 784 + 8 * (lane & 28) + 16 * (lane & 1);
#pragma unroll
            for (int u = 0; u < 3; u++) sts128p(a + 256 * u, acc[u][0] * sc3, acc[u][1] * sc3, acc[u][2] * sc3, acc[u][3] * sc3, lane & 2);
        }
        const uint32_t role1 = layer ? lds32(sb + SM_MISC + 4) : DN0 + NDN;
        const uint32_t pc = opq(sb + SM_R + 16 * opq(tid));
        uint4* const px0 = opq(&g_scr.hx[b * 48 + opq(tid)]);
        __syncthreads();
        PROF_T(4 + layer * 16);
        PC(layer * 32 + 2);
        float4 o = make_float4(0.f, 0.f, 0.f, 0.f);
        if (wu < 2) {
            float4 v[8];
#pragma unroll
            for (int w = 0; w < 8; w++) v[w] = lds4f(pc + w * 784);
            o.x = ((v[0].x + v[1].x) + (v[2].x + v[3].x)) + ((v[4].x + v[5].x) + (v[6].x + v[7].x));
            o.y = ((v[0].y + v[1].y) + (v[2].y + v[3].y)) + ((v[4].y + v[5].y) + (v[6].y + v[7].y));
            o.z = ((v[0].z + v[1].z) + (v[2].z + v[3].z)) + ((v[4].z + v[5].z) + (v[6].z + v[7].z));
            o.w = ((v[0].w + v[1].w) + (v[2].w + v[3].w)) + ((v[4].w + v[5].w) + (v[6].w + v[7].w));
            o.w = f_(__float_as_uint(o.w) & ~1u);
            st_pktp(px0, __float_as_uint(o.x), __float_as_uint(o.y), __float_as_uint(o.z), __float_as_uint(o.w), threadIdx.x < 48);
        }
        uint32_t ticket = 0;
        if (layer == 0 && tid == 224)
            asm volatile("atom.relaxed.gpu.global.inc.u32 %0, [%1], 0x7fffffff;" : "=r"(ticket) : "l"(g_scr.ticket + 8 + (b >> 3)) : "memory");
        if (layer == 0 && tid == 224 && lds32(sb + SM_MISC + 12) < 256u) {
            int it = 0;
            while ((int)(now_ns() - lds32(sb + SM_XL + 4)) < 0 && ++it < SPIN_CAP) {}
            PROF_X(47);
            load_wo(maps, sb + SM_B, h, c, wbar, 6);
        }
        uint32_t pr;
        uint4* pacc;
        {
            const int tid = opq(threadIdx.x), warp = tid >> 5, lane = tid & 31, g = lane >> 2, t = lane & 3, mat = lane >> 3, r8 = lane & 7;
            const int kg = warp >> 1, mg = warp & 1;
            const bool wo2 = role1 < DN0 + NDN;
            const uint32_t aw2 = 40960 + (wo2 && KEEP4 && role1 >= DN0 && kg >= 2 ? SM_B - SM_Q : 0);
            uint32_t aw[5];
#pragma unroll
            for (int i = 0; i < 5; i++) {
                const uint32_t lin = ((mat >> 1) * 8 + r8) * 320 + 64 * i + 32 * mg + 16 * (mat & 1);
                aw[i] = sb + (wo2 ? SM_Q : SM_B) + 5120 * kg + (lin ^ ((lin >> 3) & 48));
            }
#define CXE 1
            const uint32_t ao = pin(sb + SM_OS + 96 * kg + 16 * t), dw = pin(sb + SM_R + 16 * (16 * mg + g) + 4 * kg);
            pr = pin(sb + SM_R + 48 * tid); pacc = pin(&g_scr.acc[layer][(54 * c + tid) * ACC_STR]);
            const int w = 2 * min(tid, 47);
            const uint32_t d0 = pin(sb + SM_OS + 4 * (24 * ((w >> 3) & 3) + ((w >> 2) & 1) + (w < 64 ? 4 * (w & 3) + 2 * (w >> 5) : 16 + 2 * (w & 3))));
            const uint32_t d1 = pin(d0 + (w < 64 ? 16 : 8));
            const uint4* pp[3];
#pragma unroll
            for (int k = 0; k < 3; k++) pp[k] = pin(&g_scr.hx[(h * 4 + ((c + 1 + k) & 3)) * 48 + min(tid, 47)]);
            bool ok = true;
            if ((PRE1 & 8) && layer) {
#pragma unroll
                for (int ks = 0; ks < 3; ks++) {
                    mbar_wait(wbar + 8 * ks, wo2);
#pragma unroll
                    for (int i = 0; i < 5; i++) ldsm4t(aw[i] + (ks == 2 ? aw2 : 20480 * ks), kq[3 * i + ks]);
                    if (ks == CXE && wu < 2) {
#pragma unroll
                        for (int k = 0; k < 3; k++) { const uint4 v = ld_pkt(pp[k]); kq[20 + k][0] = v.x; kq[20 + k][1] = v.y; kq[20 + k][2] = v.z; kq[20 + k][3] = v.w; }
                    }
                }
                PROF_T(50);
                if (CXE < 3 && wu < 2) {
                    ok = __any_sync(0xffffffffu, (kq[20][3] | kq[21][3] | kq[22][3]) & 1);
                    if (!ok) {
#pragma unroll
                        for (int k = 0; k < 3; k++) { o.x += f_(kq[20 + k][0]); o.y += f_(kq[20 + k][1]); o.z += f_(kq[20 + k][2]); o.w += f_(kq[20 + k][3]); }
                    }
                }
            }
            if (wu < 2) {
                if (ok) {
                    uint4 v3[3];
                    int it = 0;
                    do {
#pragma unroll
                        for (int k = 0; k < 3; k++) v3[k] = ld_pkt(pp[k]);
                        ok = __any_sync(0xffffffffu, (v3[0].w | v3[1].w | v3[2].w) & 1);
                    } while (ok && ++it < SPIN_CAP);
#pragma unroll
                    for (int k = 0; k < 3; k++) { o.x += f_(v3[k].x); o.y += f_(v3[k].y); o.z += f_(v3[k].z); o.w += f_(v3[k].w); }
                }
                sts32p(d0, f_(pack2(o.x, o.y)), tid >= 48);
                sts32p(d1, f_(pack2(o.z, o.w)), tid >= 48);
            }
            PC(layer * 32 + 3);
            __syncthreads();
            PROF_T(5 + layer * 16);
            PC(layer * 32 + 5);
            if (tid == 224 && layer == 0) {
                if (ticket >= 6 + ((b >> 3) & 1)) ticket = DN0 + NDN;
                else asm volatile("atom.relaxed.gpu.global.inc.u32 %0, [%1], 0x7fffffff;" : "=r"(ticket) : "l"(g_scr.ticket) : "memory");
            }
            uint32_t ob[6];
            lds128(ao, ob[0], ob[1], ob[2], ob[3]);
            lds64(ao + 64 - 8 * t, ob[4], ob[5]);
            float cc[5][4];
#pragma unroll
            for (int i = 0; i < 5; i++) cc[i][0] = cc[i][1] = cc[i][2] = cc[i][3] = 0.f;
            if ((PRE1 & 8) && layer) {
#pragma unroll
                for (int ks = 0; ks < 3; ks++) {
#pragma unroll
                    for (int i = 0; i < 5; i++) mma16816(cc[i], kq[3 * i + ks][0], kq[3 * i + ks][1], kq[3 * i + ks][2], kq[3 * i + ks][3], ob[2 * ks], ob[2 * ks + 1]);
                }
            } else {
#pragma unroll
                for (int ks = 0; ks < 3; ks++) {
                    mbar_wait(wbar + 8 * ks, wo2);
                    if (ks == 2) { PC(layer * 32 + 4); PROF_T(48 + layer * 2); }
                    uint32_t a[5][4];
#pragma unroll
                    for (int i = 0; i < 5; i++) ldsm4t(aw[i] + (ks == 2 ? aw2 : 20480 * ks), a[i]);
#pragma unroll
                    for (int i = 0; i < 5; i++) mma16816(cc[i], a[i][0], a[i][1], a[i][2], a[i][3], ob[2 * ks], ob[2 * ks + 1]);
                }
            }
            if (t == 0) {
#pragma unroll
                for (int i = 0; i < 5; i++) { sts32(dw + 512 * i, cc[i][0]); sts32(dw + 512 * i + 128, cc[i][2]); }
            }
        }
        PC(layer * 32 + 6);
        __syncthreads();
        PROF_T(6 + layer * 16);
        PC(layer * 32 + 7);
        if (tid < 54) {
            const float4 v0 = lds4f(pr), v1 = lds4f(pr + 16), v2 = lds4f(pr + 32);
            const float y0 = (v0.x + v0.y) + (v0.z + v0.w), y1 = (v1.x + v1.y) + (v1.z + v1.w), y2 = (v2.x + v2.y) + (v2.z + v2.w);
            red_pkt(pacc, y0, tid == 53 ? 0.f : y1, tid == 53 ? 0.f : y2);
        }
        if (tid == 224 && layer == 0) {
            misc[1] = __uint_as_float(ticket);
            if (ticket < DN0 + NDN && (ticket < NG || !DNTH)) load_ffn(maps, ticket, sb + SM_B, fbar);
        }
        PROF_T(7 + layer * 16);
        PC(layer * 32 + 8);
        __syncthreads();
        const int role = (int)__float_as_uint(misc[1]);
        PC(layer * 32 + 9);
        const uint32_t fbase = sb + SM_B;
        const uint32_t DONE32 = 0x42000000u;
        if (role < NG) {
            const int tid = opq(threadIdx.x), warp = tid >> 5, lane = tid & 31, g = lane >> 2, t = lane & 3, mat = lane >> 3, r8 = lane & 7;
            const uint32_t ag = fbase + (80 * warp + (mat >> 1) * 8 + r8) * 96 + (((mat & 1) ^ (r8 >> 2)) << 4);
            constexpr int GI = 32, GK = 16 * 96;
            const bool on = (g & 1) == (t >> 1), isx = on && g < 2;
            const uint32_t pm = opq(isx ? sb + SM_XS + 160 * warp + 16 * t : sb + (on ? SM_ONE : SM_ZERO)), pm2 = opq(pm + 128 - (isx ? 8 * t : 0));
            const uint32_t dg = opq(sb + SM_R + 4 * (2 * (warp * 48 + g) + t)), ds = opq(sb + SM_ST + 8 * warp + (lane < 16 ? 4 : 0));
            const bool ws = (lane & 15) == 0, lo = lane < 16;
            uint32_t pre[6][4];
            float s1 = 0.f, s2 = 0.f;
            {
                bool hx = wu == 7;
                int it = 0;
                const uint4* px = &g_scr.acc[layer][min(tid, 215) * ACC_STR];
                const int cq = tid / 54, r = tid - 54 * cq, k0 = min(160 * cq + 3 * r, DM - 1);
                const uint32_t w0 = sb + SM_XS + 4 * xpos(k0 >> 1), w1 = sb + SM_XS + 4 * xpos(min((k0 >> 1) + 1, DM / 2 - 1));
                const uint32_t e0 = w0 + 2 * (k0 & 1), e1 = (k0 & 1) ? w1 : w0 + 2, e2 = w1 + 2 * (k0 & 1);
                                auto sts16 = [](uint32_t a, uint32_t x, bool on) {
                    asm volatile("{\n.reg .pred p;\nsetp.ne.u32 p, %2, 0;\n@p st.shared.u16 [%0], %1;\n}" ::"r"(a), "h"((unsigned short)x), "r"((uint32_t)on) : "memory");
                };
                const bool on0 = tid < 216, on1 = on0 && r != 53;
                const float x0 = on0 ? f_(lds16(e0) << 16) : 0.f, x1 = on1 ? f_(lds16(e1) << 16) : 0.f, x2 = on1 ? f_(lds16(e2) << 16) : 0.f;
                auto take_x = [&](const uint4 v) {
                    if (__all_sync(0xffffffffu, v.w == DONE32)) {
                        hx = true;
                        const uint32_t a = pack2(f_(v.x), f_(v.y)), p = pack2(x0 + bf_lo(a), x1 + bf_hi(a)), q = pack2(x2 + bfr(f_(v.z)), 0.f);
                        sts16(e0, p, on0); sts16(e1, p >> 16, on1); sts16(e2, q, on1);
                        const float y0 = on0 ? bf_lo(p) : 0.f, y1 = on0 ? bf_hi(p) : 0.f, y2 = on0 ? bf_lo(q) : 0.f;
                        s1 = y0 + (y1 + y2); s2 = y0 * y0 + (y1 * y1 + y2 * y2);
                    }
                };
                auto try_x = [&]() { take_x(ld_pkt(px)); };
                while (!mbar_test(fbar, 0) && ++it < SPIN_CAP) { if (!hx) try_x(); }
                uint4 v0 = make_uint4(0u, 0u, 0u, 0u);
                if ((PRE1 & 4) && !hx) v0 = ld_pkt(px);
#pragma unroll
                for (int n = 0; n < 6; n++) ldsm4t(ag + (n % 3) * GI + (n / 3) * GK, pre[n]);
                if ((PRE1 & 1) && layer) {
#pragma unroll
                    for (int n = 6; n < 15; n++) ldsm4t(ag + (n % 3) * GI + (n / 3) * GK, kq[n - 6]);
                }
                if ((PRE1 & 4) && !hx) take_x(v0);
                PC(layer * 32 + 10);
                while (!hx && ++it < SPIN_CAP) try_x();
                PC(layer * 32 + 11);
            __syncthreads();
            PC(layer * 32 + 12);
            PROF_T(9 + layer * 16);
            float sv = lo ? s1 : s2, cc[3][4];
            if ((PRE1 & 1) && layer) gemv15r(cc, pre, kq, pm, pm2, sv, lo ? s2 : s1);
            else gemv15<GK>(cc, pre, [&](int i) { return ag + i * GI; }, pm, pm2, sv, lo ? s2 : s1);
#pragma unroll
            for (int i = 0; i < 3; i++) { sts32p(dg + 128 * i, cc[i][0] + cc[i][3], t & 2); sts32p(dg + 128 * i + 64, cc[i][1] + cc[i][2], t & 2); }
            if (ws) sts32(ds, sv);
            const uint32_t pg = opq(sb + SM_R + 8 * (24 * warp + (lane < 24 ? lane : 0))), st = opq(sb + SM_ST);
            uint4* const ph = opq(lane < 24 && lane % 6 == 0 ? &g_scr.ah[role * 8 + 4 * warp + lane / 6] : nullptr);
            PC(layer * 32 + 13);
            __syncthreads();
            PC(layer * 32 + 14);
            PROF_T(43 + layer * 16);
            if (wu < 2) {
                float mean, inv;
                ln_stats(st, mean, inv);
                float2 v[8];
#pragma unroll
                for (int w = 0; w < 8; w++) v[w] = lds2f(pg + w * 384);
                const float gx = ((v[0].x + v[1].x) + (v[2].x + v[3].x)) + ((v[4].x + v[5].x) + (v[6].x + v[7].x));
                const float gs = ((v[0].y + v[1].y) + (v[2].y + v[3].y)) + ((v[4].y + v[5].y) + (v[6].y + v[7].y));
                float ga = inv * (gx - mean * gs);
                if (role < NG / 2) { ga = bfr(ga); ga *= rcp(1.0f + ex2(-1.4426950408889634f * ga)); }
                const uint32_t wd = pack2(ga, __shfl_down_sync(0xffffffffu, ga, 1));
                const uint32_t wa = __shfl_down_sync(0xffffffffu, wd, 2), wb = __shfl_down_sync(0xffffffffu, wd, 4);
                if (ph) st_pkt(ph, wd, wa, wb, tag);
            }
            if (HOLD & 2) __syncthreads();
            }
            PROF_T(10 + layer * 16);
            PC(layer * 32 + 15);
        } else if (role < DN0 + NDN) {
            const int j = role - DN0;
            const int tid = opq(threadIdx.x), warp = tid >> 5, lane = tid & 31, g = lane >> 2, t = lane & 3, mat = lane >> 3, r8 = lane & 7;
            float xres = 0.f;
            uint32_t xr0 = 0, xr1 = 0;
            if (wu == 0) {
                const int col = 16 * j + (lane & 15), cc = col / 160, r = col - 160 * cc, e = r % 3;
                const uint4* px = &g_scr.acc[layer][(54 * cc + r / 3) * ACC_STR];
                const float x0 = __bfloat162float(reinterpret_cast<const __nv_bfloat16*>(xs32)[2 * xpos(col >> 1) + (col & 1)]);
                uint4 v;
                int it = 0;
                bool ld = DNTH && layer == 0;
                do {
                    v = ld_pkt(px);
                    if (ld && f_(__shfl_sync(0xffffffffu, v.w, 0)) >= (float)DNTH) { ld = false; if (lane == 0) load_ffn(maps, role, sb + SM_B, fbar); }
                } while (!__all_sync(0xffffffffu, v.w == DONE32) && ++it < SPIN_CAP);
                if (ld && lane == 0) load_ffn(maps, role, sb + SM_B, fbar);
                xres = x0 + bfr(f_(e == 0 ? v.x : (e == 1 ? v.y : v.z)));
                const int p4 = 4 * (lane & 3);
                xr0 = pack2(__shfl_sync(0xffffffffu, xres, p4), __shfl_sync(0xffffffffu, xres, p4 + 1));
                xr1 = pack2(__shfl_sync(0xffffffffu, xres, p4 + 2), __shfl_sync(0xffffffffu, xres, p4 + 3));
            }
            PC(layer * 32 + 17);
            PROF_T(9 + layer * 16);
            const uint32_t ad = fbase + (192 * warp + (mat >> 1) * 8 + r8) * 32 + (((mat & 1) ^ (r8 >> 2)) << 4);
            uint32_t* hs = reinterpret_cast<uint32_t*>(rr) + warp * 96;
            uint32_t pre[NPRE][4];
            {
                uint32_t pos[3];
#pragma unroll
                for (int i = 0; i < 3; i++) { const int w = 3 * lane + i; pos[i] = pin(sb + SM_R + 384 * warp + 4 * ((w & ~15) + 4 * (w & 3) + ((w >> 2) & 1) + ((w >> 2) & 2))); }
                uint4 v = make_uint4(0u, 0u, 0u, 0u), u = v;
                if (layer == 0) { v = ld_pkt(&g_scr.ah[tid]); u = ld_pkt(&g_scr.ah[256 + tid]); }
                mbar_wait(fbar, 0);
#pragma unroll
                for (int n = 0; n < NPRE; n++) ldsm4t(ad + n * 512, pre[n]);
                if ((PRE1 & 2) && layer) {
#pragma unroll
                    for (int n = NPRE; n < 12; n++) ldsm4t(ad + n * 512, kq[12 + n]);
                }
                PC(layer * 32 + 18);
                int it = 0;
                while (!__all_sync(0xffffffffu, v.w == tag && u.w == tag) && ++it < SPIN_CAP) { v = ld_pkt(&g_scr.ah[tid]); u = ld_pkt(&g_scr.ah[256 + tid]); }
                PC(layer * 32 + 19);
                sts32(pos[0], f_(bmul2(v.x, u.x))); sts32(pos[1], f_(bmul2(v.y, u.y))); sts32(pos[2], f_(bmul2(v.z, u.z)));
            __syncwarp();
            PROF_T(11 + layer * 16);
            PC(layer * 32 + 20);
            float ca[4] = {0.f, 0.f, 0.f, 0.f}, cb[4] = {0.f, 0.f, 0.f, 0.f};
            if ((PRE1 & 2) && layer) {
                float cc[4] = {0.f, 0.f, 0.f, 0.f}, cd[4] = {0.f, 0.f, 0.f, 0.f};
#pragma unroll
                for (int jj = 0; jj < 6; jj++) {
                    const uint4 hv = *reinterpret_cast<const uint4*>(hs + 16 * jj + 4 * t);
                    const uint32_t (&f0)[4] = 2 * jj < NPRE ? pre[2 * jj < NPRE ? 2 * jj : 0] : kq[12 + 2 * jj];
                    const uint32_t (&f1)[4] = 2 * jj + 1 < NPRE ? pre[2 * jj + 1 < NPRE ? 2 * jj + 1 : 0] : kq[13 + 2 * jj];
                    if (jj & 1) { mma16816(cc, f0[0], f0[1], f0[2], f0[3], hv.x, hv.y); mma16816(cd, f1[0], f1[1], f1[2], f1[3], hv.z, hv.w); }
                    else { mma16816(ca, f0[0], f0[1], f0[2], f0[3], hv.x, hv.y); mma16816(cb, f1[0], f1[1], f1[2], f1[3], hv.z, hv.w); }
                }
#pragma unroll
                for (int e = 0; e < 4; e++) { ca[e] += cc[e]; cb[e] += cd[e]; }
            } else {
#pragma unroll
                for (int jj = 0; jj < 6; jj++) {
                    const uint4 hv = *reinterpret_cast<const uint4*>(hs + 16 * jj + 4 * t);
                    uint32_t a[4];
                    if (2 * jj < NPRE) { a[0] = pre[2 * jj][0]; a[1] = pre[2 * jj][1]; a[2] = pre[2 * jj][2]; a[3] = pre[2 * jj][3]; }
                    else ldsm4t(ad + 2 * jj * 512, a);
                    mma16816(ca, a[0], a[1], a[2], a[3], hv.x, hv.y);
                    if (2 * jj + 1 < NPRE) { a[0] = pre[2 * jj + 1][0]; a[1] = pre[2 * jj + 1][1]; a[2] = pre[2 * jj + 1][2]; a[3] = pre[2 * jj + 1][3]; }
                    else ldsm4t(ad + (2 * jj + 1) * 512, a);
                    mma16816(cb, a[0], a[1], a[2], a[3], hv.z, hv.w);
                }
            }
            if (t == 0) { rr[768 + warp * 16 + g] = ca[0] + cb[0]; rr[768 + warp * 16 + 8 + g] = ca[2] + cb[2]; }
            const uint32_t pd = opq(sb + SM_R + 3072 + 16 * (lane & 3));
            uint4* const py = opq(&g_scr.ay[j * 4 + lane]);
            uint2* const po = opq(reinterpret_cast<uint2*>(out + 16 * j) + lane);
            PC(layer * 32 + 21);
            __syncthreads();
            PC(layer * 32 + 22);
            if (wu == 0) {
                float4 p[8];
#pragma unroll
                for (int w = 0; w < 8; w++) p[w] = lds4f(pd + 64 * w);
                const uint32_t y0 = pack2(((p[0].x + p[1].x) + (p[2].x + p[3].x)) + ((p[4].x + p[5].x) + (p[6].x + p[7].x)),
                                          ((p[0].y + p[1].y) + (p[2].y + p[3].y)) + ((p[4].y + p[5].y) + (p[6].y + p[7].y)));
                const uint32_t y1 = pack2(((p[0].z + p[1].z) + (p[2].z + p[3].z)) + ((p[4].z + p[5].z) + (p[6].z + p[7].z)),
                                          ((p[0].w + p[1].w) + (p[2].w + p[3].w)) + ((p[4].w + p[5].w) + (p[6].w + p[7].w)));
                uint32_t wd, wn;
                asm("add.rn.bf16x2 %0, %1, %2;" : "=r"(wd) : "r"(xr0), "r"(y0));
                asm("add.rn.bf16x2 %0, %1, %2;" : "=r"(wn) : "r"(xr1), "r"(y1));
                asm volatile("{\n.reg .pred p;\nsetp.ne.u32 p, %3, 0;\n@p st.global.v2.u32 [%0], {%1,%2};\n}" ::"l"(po), "r"(wd), "r"(wn), "r"((uint32_t)(layer && tid < 4)) : "memory");
                st_pktp(py, wd, wn, 0, tag, tid < 4);
            }
            if (HOLD & 1) __syncthreads();
            }
            PROF_T(12 + layer * 16);
            PC(layer * 32 + 23);
        }
    }
}

typedef CUresult (*EncodeFn)(CUtensorMap*, CUtensorMapDataType, cuuint32_t, void*, const cuuint64_t*, const cuuint64_t*, const cuuint32_t*,
                             const cuuint32_t*, CUtensorMapInterleave, CUtensorMapSwizzle, CUtensorMapL2promotion, CUtensorMapFloatOOBfill);

void make_map(EncodeFn enc, CUtensorMap* m, const void* base, int rank, uint64_t d0, uint64_t d1, uint64_t d2, uint64_t s1, uint64_t s2,
              uint32_t b0, uint32_t b1, uint32_t b2, CUtensorMapSwizzle sw, CUtensorMapL2promotion pr = CU_TENSOR_MAP_L2_PROMOTION_NONE) {
    cuuint64_t dims[3] = {d0, d1, d2};
    cuuint64_t strides[2] = {s1, s2};
    cuuint32_t box[3] = {b0, b1, b2};
    cuuint32_t es[3] = {1, 1, 1};
    enc(m, CU_TENSOR_MAP_DATA_TYPE_BFLOAT16, rank, const_cast<void*>(base), dims, strides, box, es, CU_TENSOR_MAP_INTERLEAVE_NONE, sw,
        pr, CU_TENSOR_MAP_FLOAT_OOB_FILL_NONE);
}

}

extern "C" void kernel_launch(void* const* d_in, const int* in_sizes, int n_in, void* d_out, int out_size) {
    (void)in_sizes; (void)n_in; (void)out_size;
    static EncodeFn enc = nullptr;
    if (!enc) {
        void* fn = nullptr;
        cudaDriverEntryPointQueryResult qr;
        cudaGetDriverEntryPoint("cuTensorMapEncodeTiled", &fn, cudaEnableDefault, &qr);
        enc = reinterpret_cast<EncodeFn>(fn);
        cudaFuncSetAttribute(decode_kernel, cudaFuncAttributeMaxDynamicSharedMemorySize, SM_TOTAL);
    }
    Maps maps;
    make_map(enc, &maps.k, d_in[1], 2, 64, (uint64_t)NH * SK * 3, 1, 128, 0, 64, 48, 1, CU_TENSOR_MAP_SWIZZLE_128B);
    make_map(enc, &maps.v, d_in[2], 2, 64, (uint64_t)NH * SK * 3, 1, 128, 0, 64, 48, 1, CU_TENSOR_MAP_SWIZZLE_128B);
    make_map(enc, &maps.wq, d_in[3], 3, 64, DM, NH * DH / 64, NH * DH * 2, 128, 64, 160, 3, CU_TENSOR_MAP_SWIZZLE_128B);
    make_map(enc, &maps.wo, d_in[4], 3, 32, DM / 32, NH * DH, 64, DM * 2, 32, 5, 32, CU_TENSOR_MAP_SWIZZLE_64B);
    make_map(enc, &maps.vr, (const char*)d_in[2] + 512, 2, 128, (uint64_t)NH * SK / 2, 1, 768, 0, 128, 2, 1, CU_TENSOR_MAP_SWIZZLE_NONE);
    constexpr int GW = 48;
    make_map(enc, &maps.w1, d_in[6], 3, FF, 160, 4, FF * 2, 160 * FF * 2, GW, 160, 4, CU_TENSOR_MAP_SWIZZLE_NONE, FFN_PROMO);
    make_map(enc, &maps.w3, d_in[7], 3, FF, 160, 4, FF * 2, 160 * FF * 2, GW, 160, 4, CU_TENSOR_MAP_SWIZZLE_NONE, FFN_PROMO);
    make_map(enc, &maps.w2, d_in[8], 3, DM, 256, 6, DM * 2, 256 * DM * 2, 16, 256, 6, CU_TENSOR_MAP_SWIZZLE_32B, FFN_PROMO);
    maps.vp = d_in[2];
    maps.kp = d_in[1];
    maps.zero = 0;
    decode_kernel<<<NCTA, NT, SM_TOTAL, cudaStreamPerThread>>>(maps, (const __nv_bfloat16*)d_in[0], (__nv_bfloat16*)d_out);
}
```

```cpp
#include <cuda_runtime.h>
#include <cuda_bf16.h>
#include <cuda.h>
#include <stdint.h>
#include <math.h>

namespace {

constexpr int DM = 640;
constexpr int NH = 32;
constexpr int DH = 192;
constexpr int SK = 32768;
constexpr int WIN = 4096;
constexpr int FF = 1536;
constexpr int NCTA = 128;
constexpr int NT = 256;
constexpr int TILE = 6144;
constexpr int NG = 64;
constexpr int DN0 = 64;
constexpr int NDN = 40;

constexpr int SM_RING = 0;
constexpr int SM_B = 8 * 2 * TILE;
constexpr int SM_Q = SM_B + 61440;
__host__ __device__ constexpr int c_slot(int w) { return w < 2 ? 4096 + 10240 * w : 12288 + 6144 * w; }
__host__ __device__ constexpr int v1_pos(int n) { return 10240 * (n >> 3) + 512 * (n & 7); }
constexpr int SM_XS = SM_Q + 61440;
constexpr int SM_R = SM_XS + 1280;
constexpr int SM_ST = SM_R + 4096;
constexpr int SM_QS = SM_R + 6272;
constexpr int SM_OS = SM_QS + 384;
constexpr int SM_BAR = SM_OS + 384;
constexpr int SM_XBAR = SM_BAR + 24 * 8;
constexpr int SM_MISC = SM_XBAR + 8 * 8;
constexpr int SM_ONE = SM_MISC + 16;
constexpr int SM_ZERO = SM_ONE + 160;
constexpr int XCAP = 48;
constexpr int XSTR = 16 + 4 * XCAP;
constexpr int SM_XL = SM_ZERO + 160;
constexpr int SM_TOTAL = SM_XL + 8 * XSTR;
static_assert(SM_TOTAL <= 232448, "shared memory");

constexpr unsigned long long POL_EF = 0x12F0000000000000ull;
constexpr unsigned long long POL_EN = 0x16F0000000000000ull;

#define RT_MASK 0xF2E0u
#define RT_MASK2 0xEAE0u
#define WO_AT1 5
#define FFN_PROMO CU_TENSOR_MAP_L2_PROMOTION_NONE
#define FFN_POL POL_EF
#define HAS_FFN (__float_as_uint(misc[1]) < DN0 + NDN)
#define ACC_STR 1
#define NPRE 6

#define STAG 200
#define L1R 3
#define PRE1 13
#define HOLD 2
#define DNTH 23
constexpr int V0_AT = 8;
constexpr unsigned long long SEQ1 = 0x2765431076543210ull;
constexpr uint32_t IN_S1 = 0xAA49, IN_S0 = 0x124, PARITY1 = 0x6638, PARITY2 = 0xCE;
#define KEEP4 1
constexpr int NQ = 48;
constexpr int SPIN_CAP = 1 << 19;
constexpr uint32_t ONES = 0x3F803F80u;

struct alignas(1024) Scratch {
    uint4 hx[NCTA * 48];
    uint4 pad0[32 * 5 * 32 + 160];
    uint4 acc[2][216 * 8];
    uint4 ay[160];
    uint4 ah[NG * 8];
    uint2 mx[NH * 32];
    uint32_t ticket[32];
    uint32_t pad1[32];
};
__device__ Scratch g_scr;
#define PROF_T(i)
#define PROF_X(i)
#define PC(i)

__device__ __forceinline__ uint32_t smem_u32(const void* p) { return (uint32_t)__cvta_generic_to_shared(p); }
__device__ __forceinline__ void mbar_init(uint32_t bar, uint32_t cnt) {
    asm volatile("mbarrier.init.shared::cta.b64 [%0], %1;" ::"r"(bar), "r"(cnt) : "memory");
}
__device__ __forceinline__ void mbar_expect_tx(uint32_t bar, uint32_t bytes) {
    asm volatile("mbarrier.arrive.expect_tx.shared::cta.b64 _, [%0], %1;" ::"r"(bar), "r"(bytes) : "memory");
}
__device__ __forceinline__ bool mbar_test(uint32_t bar, uint32_t parity) {
    uint32_t done;
    asm volatile("{\n.reg .pred p;\nmbarrier.try_wait.parity.shared::cta.b64 p, [%1], %2;\nselp.u32 %0, 1, 0, p;\n}"
                 : "=r"(done) : "r"(bar), "r"(parity) : "memory");
    return done;
}
__device__ __forceinline__ void mbar_wait(uint32_t bar, uint32_t parity) {
    int it = 0;
    while (!mbar_test(bar, parity) && ++it < SPIN_CAP) {}
}
__device__ __forceinline__ void tma2d(uint32_t dst, const CUtensorMap* map, int c0, int c1, uint32_t bar, unsigned long long pol) {
    asm volatile("cp.async.bulk.tensor.2d.shared::cluster.global.mbarrier::complete_tx::bytes.L2::cache_hint [%0], [%1, {%3, %4}], [%2], %5;"
                 ::"r"(dst), "l"(map), "r"(bar), "r"(c0), "r"(c1), "l"(pol) : "memory");
}
__device__ __forceinline__ void tma3d(uint32_t dst, const CUtensorMap* map, int c0, int c1, int c2, uint32_t bar, unsigned long long pol) {
    asm volatile("cp.async.bulk.tensor.3d.shared::cluster.global.mbarrier::complete_tx::bytes.L2::cache_hint [%0], [%1, {%3, %4, %5}], [%2], %6;"
                 ::"r"(dst), "l"(map), "r"(bar), "r"(c0), "r"(c1), "r"(c2), "l"(pol) : "memory");
}
__device__ __forceinline__ void tile_load(uint32_t dst, const CUtensorMap* map, int row, uint32_t bar, uint32_t dep, uint32_t zero) {
    asm volatile("{\n.reg .pred p;\n.reg .b32 n;\nmad.lo.u32 n, %5, %6, 6144;\nelect.sync _|p, 0xffffffff;\n"
                 "@p mbarrier.arrive.expect_tx.shared::cta.b64 _, [%2], n;\n"
                 "@p cp.async.bulk.tensor.2d.shared::cluster.global.mbarrier::complete_tx::bytes.L2::cache_hint [%0], [%1, {0, %3}], [%2], %4;\n}"
                 ::"r"(dst), "l"(map), "r"(bar), "r"(row), "l"(POL_EF), "r"(dep), "r"(zero) : "memory");
}
__device__ __forceinline__ void tile_keep(const CUtensorMap* map, int row) {
    asm volatile("{\n.reg .pred p;\nelect.sync _|p, 0xffffffff;\n"
                 "@p cp.async.bulk.prefetch.tensor.2d.L2.global.L2::cache_hint [%0, {0, %1}], %2;\n}"
                 ::"l"(map), "r"(row), "l"(POL_EN) : "memory");
}
__device__ __forceinline__ void tile_load_l1(uint32_t dst, const void* base, int row, uint32_t bar, int lane) {
    const char* g = static_cast<const char*>(base) + (size_t)row * 128 + lane * 16;
    const uint32_t s0 = dst + (lane >> 3) * 128 + (((lane & 7) ^ (lane >> 3)) << 4), s1 = s0 ^ 64;
#pragma unroll
    for (int k = 0; k < 12; k++)
        asm volatile("cp.async.ca.shared.global.L2::cache_hint [%0], [%1], 16, %2;" ::"r"(((k & 1) ? s1 : s0) + k * 512), "l"(g + k * 512), "l"(POL_EF) : "memory");
    asm volatile("cp.async.mbarrier.arrive.shared::cta.b64 [%0];" ::"r"(bar) : "memory");
    __syncwarp();
    if (lane == 0) asm volatile("mbarrier.arrive.shared::cta.b64 _, [%0];" ::"r"(bar) : "memory");
}
__device__ __forceinline__ bool elect_one() {
    uint32_t p;
    asm volatile("{\n.reg .pred p;\nelect.sync _|p, 0xffffffff;\nselp.u32 %0, 1, 0, p;\n}" : "=r"(p));
    return p;
}
__device__ __forceinline__ void lds128(uint32_t addr, uint32_t& a, uint32_t& b, uint32_t& c, uint32_t& d) {
    asm volatile("ld.shared.v4.u32 {%0,%1,%2,%3}, [%4];" : "=r"(a), "=r"(b), "=r"(c), "=r"(d) : "r"(addr) : "memory");
}
__device__ __forceinline__ void lds128p(uint32_t addr, uint32_t on, uint32_t& a, uint32_t& b, uint32_t& c, uint32_t& d) {
    asm volatile("{\n.reg .pred p;\nsetp.ne.u32 p, %5, 0;\n@p ld.shared.v4.u32 {%0,%1,%2,%3}, [%4];\n}" : "+r"(a), "+r"(b), "+r"(c), "+r"(d) : "r"(addr), "r"(on) : "memory");
}
__device__ __forceinline__ void lds64(uint32_t addr, uint32_t& a, uint32_t& b) {
    asm volatile("ld.shared.v2.u32 {%0,%1}, [%2];" : "=r"(a), "=r"(b) : "r"(addr) : "memory");
}
__device__ __forceinline__ void ldsm4t(uint32_t addr, uint32_t (&a)[4]) {
    asm volatile("ldmatrix.sync.aligned.m8n8.x4.trans.shared.b16 {%0,%1,%2,%3}, [%4];" : "=r"(a[0]), "=r"(a[1]), "=r"(a[2]), "=r"(a[3]) : "r"(addr) : "memory");
}
__device__ __forceinline__ void mma16816(float (&c)[4], uint32_t a0, uint32_t a1, uint32_t a2, uint32_t a3, uint32_t b0, uint32_t b1) {
    asm("mma.sync.aligned.m16n8k16.row.col.f32.bf16.bf16.f32 {%0,%1,%2,%3}, {%4,%5,%6,%7}, {%8,%9}, {%0,%1,%2,%3};"
        : "+f"(c[0]), "+f"(c[1]), "+f"(c[2]), "+f"(c[3]) : "r"(a0), "r"(a1), "r"(a2), "r"(a3), "r"(b0), "r"(b1));
}
__device__ __forceinline__ void mma16816v(float (&c)[4], uint32_t a0, uint32_t a1, uint32_t a2, uint32_t a3, uint32_t b0, uint32_t b1) {
    asm volatile("mma.sync.aligned.m16n8k16.row.col.f32.bf16.bf16.f32 {%0,%1,%2,%3}, {%4,%5,%6,%7}, {%8,%9}, {%0,%1,%2,%3};"
        : "+f"(c[0]), "+f"(c[1]), "+f"(c[2]), "+f"(c[3]) : "r"(a0), "r"(a1), "r"(a2), "r"(a3), "r"(b0), "r"(b1));
}
__device__ __forceinline__ int xpos(int w) {
    const int seg = w / 40, r = w - 40 * seg;
    return 40 * seg + (r < 32 ? (r & 16) + 4 * (r & 3) + ((r >> 2) & 3) : 32 + 2 * (r & 3) + ((r >> 2) & 1));
}
#define NA_LD ""
#define NA_ST ""
__device__ __forceinline__ void st_pkt(uint4* p, uint32_t a, uint32_t b, uint32_t c, uint32_t d) {
    asm volatile("{\n.reg .b128 t;\n.reg .b64 lo, hi;\nmov.b64 lo, {%1,%2};\nmov.b64 hi, {%3,%4};\nmov.b128 t, {lo,hi};\nst.relaxed.gpu.global" NA_ST ".b128 [%0], t;\n}"
                 ::"l"(p), "r"(a), "r"(b), "r"(c), "r"(d) : "memory");
}
__device__ __forceinline__ void red_pkt(uint4* p, float a, float b, float c) {
    asm volatile("red.relaxed.gpu.global.add.v4.f32 [%0], {%1,%2,%3,%4};" ::"l"(p), "f"(a), "f"(b), "f"(c), "f"(1.0f) : "memory");
}
__device__ __forceinline__ void st_pktp(uint4* p, uint32_t a, uint32_t b, uint32_t c, uint32_t d, bool on) {
    asm volatile("{\n.reg .pred p;\n.reg .b128 t;\n.reg .b64 lo, hi;\nsetp.ne.u32 p, %5, 0;\nmov.b64 lo, {%1,%2};\nmov.b64 hi, {%3,%4};\nmov.b128 t, {lo,hi};\n"
                 "@p st.relaxed.gpu.global.b128 [%0], t;\n}" ::"l"(p), "r"(a), "r"(b), "r"(c), "r"(d), "r"((uint32_t)on) : "memory");
}
__device__ __forceinline__ void st_pktfp(uint4* p, float a, float b, float c, float d, uint32_t bit, bool on) {
    st_pktp(p, __float_as_uint(a), __float_as_uint(b), __float_as_uint(c), (__float_as_uint(d) & ~1u) | bit, on);
}
__device__ __forceinline__ uint4 ld_pkt(const uint4* p) {
    uint4 v;
    asm volatile("{\n.reg .b128 t;\n.reg .b64 lo, hi;\nld.relaxed.gpu.global" NA_LD ".b128 t, [%4];\nmov.b128 {lo,hi}, t;\nmov.b64 {%0,%1}, lo;\nmov.b64 {%2,%3}, hi;\n}"
                 : "=r"(v.x), "=r"(v.y), "=r"(v.z), "=r"(v.w) : "l"(p) : "memory");
    return v;
}
__device__ __forceinline__ uint2 ld_pkt2(const uint2* p) {
    unsigned long long v;
    asm volatile("ld.relaxed.gpu.global" NA_LD ".b64 %0, [%1];" : "=l"(v) : "l"(p) : "memory");
    return make_uint2((uint32_t)v, (uint32_t)(v >> 32));
}
__device__ __forceinline__ void st_pkt2(uint2* p, uint32_t a, uint32_t b) {
    asm volatile("st.relaxed.gpu.global" NA_ST ".b64 [%0], %1;" ::"l"(p), "l"((unsigned long long)a | ((unsigned long long)b << 32)) : "memory");
}
__device__ __forceinline__ float ex2(float x) { float y; asm("ex2.approx.ftz.f32 %0, %1;" : "=f"(y) : "f"(x)); return y; }
__device__ __forceinline__ float rcp(float x) { float y; asm("rcp.approx.ftz.f32 %0, %1;" : "=f"(y) : "f"(x)); return y; }
__device__ __forceinline__ uint32_t pack2(float lo, float hi) {
    uint32_t r; asm("cvt.rn.bf16x2.f32 %0, %1, %2;" : "=r"(r) : "f"(hi), "f"(lo)); return r;
}
__device__ __forceinline__ float bf_lo(uint32_t w) { return __uint_as_float(w << 16); }
__device__ __forceinline__ float bf_hi(uint32_t w) { return __uint_as_float(w & 0xffff0000u); }
__device__ __forceinline__ float bfr(float x) { return bf_lo(pack2(x, 0.f)); }
__device__ __forceinline__ float f_(uint32_t u) { return __uint_as_float(u); }

template <int SK, typename AddrF>
__device__ __forceinline__ void gemv15(float (&cc)[3][4], uint32_t (&pre)[6][4], AddrF ad, uint32_t px, uint32_t px2, float& sv, float so) {
    uint32_t x0[4], x1[4], a[3][4];
    asm volatile("ld.shared.v4.u32 {%0,%1,%2,%3}, [%20];\nld.shared.v4.u32 {%4,%5,%6,%7}, [%20+64];\n"
                 "ldmatrix.sync.aligned.m8n8.x4.trans.shared.b16 {%8,%9,%10,%11}, [%21];\n"
                 "ldmatrix.sync.aligned.m8n8.x4.trans.shared.b16 {%12,%13,%14,%15}, [%22];\n"
                 "ldmatrix.sync.aligned.m8n8.x4.trans.shared.b16 {%16,%17,%18,%19}, [%23];\nbar.warp.sync 0xffffffff;"
                 : "=r"(x0[0]), "=r"(x0[1]), "=r"(x0[2]), "=r"(x0[3]), "=r"(x1[0]), "=r"(x1[1]), "=r"(x1[2]), "=r"(x1[3]),
                   "=r"(a[0][0]), "=r"(a[0][1]), "=r"(a[0][2]), "=r"(a[0][3]), "=r"(a[1][0]), "=r"(a[1][1]), "=r"(a[1][2]), "=r"(a[1][3]),
                   "=r"(a[2][0]), "=r"(a[2][1]), "=r"(a[2][2]), "=r"(a[2][3])
                 : "r"(px), "r"(ad(0) + 2 * SK), "r"(ad(1) + 2 * SK), "r"(ad(2) + 2 * SK) : "memory");
    __syncwarp();
    sv += __shfl_xor_sync(0xffffffffu, so, 16);
#pragma unroll
    for (int i = 0; i < 3; i++) {
        cc[i][0] = cc[i][1] = cc[i][2] = cc[i][3] = 0.f;
        mma16816v(cc[i], pre[i][0], pre[i][1], pre[i][2], pre[i][3], x0[0], x0[1]);
    }
    sv += __shfl_xor_sync(0xffffffffu, sv, 8);
#pragma unroll
    for (int i = 0; i < 3; i++) {
        mma16816v(cc[i], pre[3 + i][0], pre[3 + i][1], pre[3 + i][2], pre[3 + i][3], x0[2], x0[3]);
        ldsm4t(ad(i) + 3 * SK, pre[i]);
    }
    lds64(px2, x0[0], x0[1]);
    __syncwarp();
    sv += __shfl_xor_sync(0xffffffffu, sv, 4);
#pragma unroll
    for (int i = 0; i < 3; i++) {
        mma16816v(cc[i], a[i][0], a[i][1], a[i][2], a[i][3], x1[0], x1[1]);
        ldsm4t(ad(i) + 4 * SK, pre[3 + i]);
    }
    __syncwarp();
    sv += __shfl_xor_sync(0xffffffffu, sv, 2);
#pragma unroll
    for (int i = 0; i < 3; i++) mma16816v(cc[i], pre[i][0], pre[i][1], pre[i][2], pre[i][3], x1[2], x1[3]);
    sv += __shfl_xor_sync(0xffffffffu, sv, 1);
#pragma unroll
    for (int i = 0; i < 3; i++) mma16816v(cc[i], pre[3 + i][0], pre[3 + i][1], pre[3 + i][2], pre[3 + i][3], x0[0], x0[1]);
}
__device__ __forceinline__ void gemv15r(float (&cc)[3][4], const uint32_t (&pre)[6][4], const uint32_t (&ext)[NQ][4], uint32_t px, uint32_t px2, float& sv, float so) {
    uint32_t x0[4], x1[4], x2[2];
    float cd[3][4];
    lds128(px, x0[0], x0[1], x0[2], x0[3]);
    lds128(px + 64, x1[0], x1[1], x1[2], x1[3]);
    lds64(px2, x2[0], x2[1]);
    sv += __shfl_xor_sync(0xffffffffu, so, 16);
#pragma unroll
    for (int i = 0; i < 3; i++) {
        cc[i][0] = cc[i][1] = cc[i][2] = cc[i][3] = cd[i][0] = cd[i][1] = cd[i][2] = cd[i][3] = 0.f;
        mma16816v(cc[i], pre[i][0], pre[i][1], pre[i][2], pre[i][3], x0[0], x0[1]);
        mma16816v(cd[i], pre[3 + i][0], pre[3 + i][1], pre[3 + i][2], pre[3 + i][3], x0[2], x0[3]);
    }
    sv += __shfl_xor_sync(0xffffffffu, sv, 8);
#pragma unroll
    for (int i = 0; i < 3; i++) {
        mma16816v(cc[i], ext[i][0], ext[i][1], ext[i][2], ext[i][3], x1[0], x1[1]);
        mma16816v(cd[i], ext[3 + i][0], ext[3 + i][1], ext[3 + i][2], ext[3 + i][3], x1[2], x1[3]);
    }
    sv += __shfl_xor_sync(0xffffffffu, sv, 4);
#pragma unroll
    for (int i = 0; i < 3; i++) mma16816v(cc[i], ext[6 + i][0], ext[6 + i][1], ext[6 + i][2], ext[6 + i][3], x2[0], x2[1]);
    sv += __shfl_xor_sync(0xffffffffu, sv, 2);
    sv += __shfl_xor_sync(0xffffffffu, sv, 1);
#pragma unroll
    for (int i = 0; i < 3; i++) { cc[i][0] += cd[i][0]; cc[i][1] += cd[i][1]; cc[i][2] += cd[i][2]; cc[i][3] += cd[i][3]; }
}

__device__ __forceinline__ float warp_max(float x) {
    int i = __float_as_int(x);
    i = __reduce_max_sync(0xffffffffu, i ^ ((i >> 31) & 0x7fffffff));
    return __int_as_float(i ^ ((i >> 31) & 0x7fffffff));
}
__device__ __forceinline__ void idle(uint32_t clk) {
    uint32_t t0, t;
    asm volatile("mov.u32 %0, %%clock;" : "=r"(t0) :: "memory");
    do asm volatile("mov.u32 %0, %%clock;" : "=r"(t) :: "memory"); while (t - t0 < clk);
}
__device__ __forceinline__ uint32_t now_ns() { uint32_t t; asm volatile("mov.u32 %0, %%globaltimer_lo;" : "=r"(t)); return t; }
__device__ __forceinline__ int opq(int x) { asm volatile("" : "+r"(x)); return x; }
__device__ __forceinline__ uint32_t opq(uint32_t x) { asm volatile("" : "+r"(x)); return x; }
__device__ __forceinline__ uint32_t pin(uint32_t x) { return __shfl_sync(0xffffffffu, x, threadIdx.x & 31); }
template <typename T> __device__ __forceinline__ T* pin(T* p) {
    const unsigned long long v = (unsigned long long)p;
    return (T*)((unsigned long long)pin((uint32_t)v) | (unsigned long long)pin((uint32_t)(v >> 32)) << 32);
}
template <typename T> __device__ __forceinline__ T* opq(T* p) { asm volatile("" : "+l"(p)); return p; }
__device__ __forceinline__ float4 lds4f(uint32_t a) { float4 v; asm volatile("ld.shared.v4.f32 {%0,%1,%2,%3}, [%4];" : "=f"(v.x), "=f"(v.y), "=f"(v.z), "=f"(v.w) : "r"(a) : "memory"); return v; }
__device__ __forceinline__ float2 lds2f(uint32_t a) { float2 v; asm volatile("ld.shared.v2.f32 {%0,%1}, [%2];" : "=f"(v.x), "=f"(v.y) : "r"(a) : "memory"); return v; }
__device__ __forceinline__ void ln_stats(uint32_t st, float& mean, float& inv) {
    const float4 a = lds4f(st), b = lds4f(st + 16), c = lds4f(st + 32), d = lds4f(st + 48);
    const float s2 = ((a.x + a.z) + (b.x + b.z)) + ((c.x + c.z) + (d.x + d.z));
    const float md = (((a.y + a.w) + (b.y + b.w)) + ((c.y + c.w) + (d.y + d.w))) * (1.0f / DM);
    const float var = fmaxf(s2 * (1.0f / DM) - md * md, 0.f);
    mean = bfr(md);
    asm("rsqrt.approx.ftz.f32 %0, %1;" : "=f"(inv) : "f"(var + 1e-5f));
}
__device__ __forceinline__ void sts32(uint32_t a, float v) { asm volatile("st.shared.f32 [%0], %1;" ::"r"(a), "f"(v) : "memory"); }
__device__ __forceinline__ void sts32p(uint32_t a, float v, uint32_t off) {
    asm volatile("{\n.reg .pred p;\nsetp.eq.u32 p, %2, 0;\n@p st.shared.f32 [%0], %1;\n}" ::"r"(a), "f"(v), "r"(off) : "memory");
}
__device__ __forceinline__ void sts128p(uint32_t a, float x, float y, float z, float w, uint32_t off) {
    asm volatile("{\n.reg .pred p;\nsetp.eq.u32 p, %5, 0;\n@p st.shared.v4.f32 [%0], {%1,%2,%3,%4};\n}" ::"r"(a), "f"(x), "f"(y), "f"(z), "f"(w), "r"(off) : "memory");
}
__device__ __forceinline__ void sts64(uint32_t a, float v, float w) { asm volatile("st.shared.v2.f32 [%0], {%1,%2};" ::"r"(a), "f"(v), "f"(w) : "memory"); }

__device__ __forceinline__ uint32_t prmt(uint32_t a, uint32_t b, uint32_t s) { uint32_t r; asm("prmt.b32 %0, %1, %2, %3;" : "=r"(r) : "r"(a), "r"(b), "r"(s)); return r; }
__device__ __forceinline__ uint32_t bmul2(uint32_t a, uint32_t b) { uint32_t r; asm("mul.rn.bf16x2 %0, %1, %2;" : "=r"(r) : "r"(a), "r"(b)); return r; }
__device__ __forceinline__ void sts128(uint32_t addr, uint32_t a, uint32_t b, uint32_t c, uint32_t d) {
    asm volatile("st.shared.v4.u32 [%0], {%1,%2,%3,%4};" ::"r"(addr), "r"(a), "r"(b), "r"(c), "r"(d) : "memory");
}
__device__ __forceinline__ uint4 ldg128(const uint4* p) {
    uint4 v;
    asm volatile("ld.volatile.global.v4.u32 {%0,%1,%2,%3}, [%4];" : "=r"(v.x), "=r"(v.y), "=r"(v.z), "=r"(v.w) : "l"(p) : "memory");
    return v;
}
__device__ __forceinline__ uint32_t lds32(uint32_t a) { uint32_t v; asm volatile("ld.shared.u32 %0, [%1];" : "=r"(v) : "r"(a) : "memory"); return v; }
__device__ __forceinline__ uint32_t lds16(uint32_t a) { unsigned short v; asm volatile("ld.shared.u16 %0, [%1];" : "=h"(v) : "r"(a) : "memory"); return v; }
__device__ __forceinline__ void unpack8(uint32_t la, uint32_t lb, uint32_t c, uint32_t (&w)[4]) {
    const uint32_t ha = c & 0x87878787u, hb = __funnelshift_l(c, c, 4) & 0x87878787u;
    w[0] = prmt(la, ha, 0x5140); w[1] = prmt(la, ha, 0x7362); w[2] = prmt(lb, hb, 0x5140); w[3] = prmt(lb, hb, 0x7362);
}
__device__ __forceinline__ uint32_t bdiff2(uint32_t y, uint32_t inv, uint32_t x) {
    uint32_t r;
    asm("{\n.reg .b32 n;\nneg.bf16x2 n, %3;\nfma.rn.bf16x2 %0, %1, %2, n;\n}" : "=r"(r) : "r"(y), "r"(inv), "r"(x));
    return r;
}
__device__ __forceinline__ uint32_t pack_scale(uint32_t tile, int lane, uint32_t inv_addr) {
    uint32_t m = 0;
#pragma unroll 1
    for (int k = 0; k < 12; k++) {
        uint32_t a, b, c, d;
        lds128(tile + k * 512 + lane * 16, a, b, c, d);
        asm("max.xorsign.abs.bf16x2 %0, %0, %1;" : "+r"(a) : "r"(b));
        asm("max.xorsign.abs.bf16x2 %0, %0, %1;" : "+r"(c) : "r"(d));
        asm("max.xorsign.abs.bf16x2 %0, %0, %1;" : "+r"(a) : "r"(c));
        asm("max.xorsign.abs.bf16x2 %0, %0, %1;" : "+r"(m) : "r"(a));
    }
    m = __reduce_max_sync(0xffffffffu, max(m & 0x7fffu, (m >> 16) & 0x7fffu));
    const uint32_t inv = (112u + min((m + 0x28u) >> 7, 141u)) * 0x00800080u;
    if (lane == 0) asm volatile("st.shared.u32 [%0], %1;" ::"r"(inv_addr), "r"(inv) : "memory");
    return inv;
}

#define K_OFF(i) ((uint32_t)((3 * ((g >> 1) + 4 * (g & 1)) + ((i) >> 1)) * 128 + ((t ^ ((3 * ((g >> 1) + 4 * (g & 1)) + ((i) >> 1)) & 7) ^ (((i) & 1) << 2)) << 4)))
#define V_OFF(i) ((uint32_t)((6 * t + (i)) * 128 + ((g ^ ((6 * t + (i)) & 7)) << 4)))
template <bool ISV, typename DST>
__device__ __forceinline__ void pack_tile(uint32_t tile, int tau, int nm, uint32_t inv, uint32_t xl, int lane, DST dst) {
    const int g = lane >> 2, t = lane & 3;
    const uint32_t scl = 254u * 0x00800080u - inv;
#pragma unroll 1
    for (int m = 0; m < nm; m++) {
        const int row = ISV ? 6 * t + 2 * m : 3 * ((g >> 1) + 4 * (g & 1)) + m;
        const uint32_t a0 = tile + row * 128 + (((ISV ? g : t) ^ (row & 7)) << 4), a1 = ISV ? (a0 ^ 16) + 128 : a0 ^ 64;
        uint32_t l[8], cw[4], ck = 0, cd = 0;
#pragma unroll
        for (int r = 0; r < 4; r++) {
            uint32_t w0, w1, w2, w3;
            lds128(((r & 1) ? a1 : a0) + (r >> 1) * 3072, w0, w1, w2, w3);
            const uint32_t y0 = bmul2(w0, scl), y1 = bmul2(w1, scl), y2 = bmul2(w2, scl), y3 = bmul2(w3, scl);
            cd |= bdiff2(y0, inv, w0) | bdiff2(y1, inv, w1);
            cd |= bdiff2(y2, inv, w2) | bdiff2(y3, inv, w3);
            const uint32_t ha = prmt(y0, y1, 0x7531), hb = prmt(y2, y3, 0x7531);
            l[2 * r] = prmt(y0, y1, 0x6420); l[2 * r + 1] = prmt(y2, y3, 0x6420);
            asm("lop3.b32 %0, %1, 0x87878787, %2, 0xe2;" : "=r"(cw[r]) : "r"(ha), "r"(__funnelshift_r(hb, hb, 4)));
            ck |= ha | hb;
        }
        const uint32_t bad = __ballot_sync(0xffffffffu, (ck & 0x78787878u) | cd);
        if (bad) {
            const int src = __ffs(bad) - 1;
            const uint32_t b0 = __shfl_sync(0xffffffffu, a0, src), b1 = __shfl_sync(0xffffffffu, a1, src), n0 = lds32(xl);
            const uint32_t ax = ((lane & 8) ? b1 : b0) + (lane >> 4) * 3072 + 2 * (lane & 7), x = lds16(ax), y = bmul2(x, scl);
            const bool out = (y & 0x7800u) | bdiff2(y, inv, x);
            const uint32_t n = n0 + __popc(__ballot_sync(0xffffffffu, out) << (31 - lane)) - 1;
            if (out) {
                asm volatile("st.shared.u16 [%0], %1;" ::"r"(ax), "h"((unsigned short)0) : "memory");
                if (n < XCAP) sts32(xl + 16 + 4 * n, f_(x << 16 | tau << 12 | src << 7 | m << 5 | lane));
            }
            if (lane == 31) sts32(xl, f_(n + 1));
            __syncwarp();
            if (n0 <= XCAP) { m--; continue; }
        }
        uint32_t d[3] = {a0, a1, a0 + 3072};
        dst(m, d);
        sts128(d[0], l[0], l[1], l[2], l[3]);
        sts128(d[1], l[4], l[5], l[6], l[7]);
        sts128(d[2], cw[0], cw[1], cw[2], cw[3]);
    }
}

struct Maps { CUtensorMap k, v, wq, wo, w1, w3, w2, vr; const void* vp; const void* kp; uint32_t zero; };
#define RT_SEL ((wu & 1) ? RT_MASK2 : RT_MASK)
#define PFK 5
#define Q_AT 3
#define WO_T0 33200
#define K5D 370
#define PK_AT 6

__device__ __forceinline__ void load_ffn(const Maps& maps, int b, uint32_t dst, uint32_t bar) {
    const bool gu = b < NG;
    mbar_expect_tx(bar, gu ? 61440 : 49152);
    tma3d(dst, gu ? (b < NG / 2 ? &maps.w1 : &maps.w3) : &maps.w2, gu ? 48 * (b & (NG / 2 - 1)) : 16 * (b - DN0), 0, 0, bar, FFN_POL);
}

__device__ __forceinline__ void load_wo(const Maps& maps, uint32_t dst, int h, int c, uint32_t bar, int nbox) {
#pragma unroll 1
    for (int i = 0; i < nbox; i++) {
        if (!(i & 1)) mbar_expect_tx(bar + 4 * i, i + 1 < nbox ? 20480 : 10240);
        tma3d(dst + i * 10240, &maps.wo, 0, 5 * c, h * DH + 32 * i, bar + 4 * (i & 6), POL_EF);
    }
}

__global__ void __launch_bounds__(NT, 1)
decode_kernel(const __grid_constant__ Maps maps, const __nv_bfloat16* __restrict__ x_in, __nv_bfloat16* __restrict__ out) {
    extern __shared__ __align__(1024) unsigned char smem[];
    const int tid = threadIdx.x, warp = tid >> 5, lane = tid & 31;
    const int wu = __shfl_sync(0xffffffffu, tid >> 5, 0);
    const int b = blockIdx.x, h = b >> 2, c = b & 3;
    const uint32_t sb = smem_u32(smem);
    const uint32_t qbar = sb + SM_BAR + 16 * 8, fbar = qbar + 8, wbar = qbar + 16;
    uint32_t* xs32 = reinterpret_cast<uint32_t*>(smem + SM_XS);
    float* rr = reinterpret_cast<float*>(smem + SM_R);
    float* misc = reinterpret_cast<float*>(smem + SM_MISC);

    PROF_T(0);
    {
        uint2 xv = make_uint2(0u, 0u);
        const uint32_t t_start = now_ns();
        if (elect_one()) {
            const uint32_t rb = sb + SM_BAR + wu * 16, xb = sb + SM_XBAR + wu * 8;
            mbar_init(rb, 1); mbar_init(rb + 8, 1); mbar_init(xb, 1);
            if (wu == 0) mbar_init(qbar, 1);
            asm volatile("fence.mbarrier_init.release.cluster;" ::: "memory");
            const int row = (h * SK + (SK - WIN) + c * 1024 + wu * 128) * 3;
            const uint32_t ring = sb + SM_RING + wu * 2 * TILE;
#pragma unroll
            for (int n = 0; n < 3; n++) {
                const uint32_t bar = ((IN_S1 >> n) & 1) ? rb + 8 : ((IN_S0 >> n) & 1) ? rb : xb;
                mbar_expect_tx(bar, TILE);
                tma2d(((IN_S1 >> n) & 1) ? ring + TILE : ((IN_S0 >> n) & 1) ? ring : sb + SM_B + wu * TILE, &maps.k, 0, row + 48 * n, bar, POL_EF);
                if (n == 0 && wu == 0) {
                    mbar_expect_tx(qbar, 61440);
                    tma3d(sb + SM_Q, &maps.wq, 0, 160 * c, 3 * h, qbar, POL_EF);
                }
            }
            if (wu == 1) {
                mbar_init(fbar, 1);
#pragma unroll
                for (int i = 0; i < 3; i++) mbar_init(wbar + 8 * i, 1);
                asm volatile("fence.mbarrier_init.release.cluster;" ::: "memory");
            }
            if (wu >= 2) {
                const CUtensorMap* mp = wu == 2 ? &maps.v : wu == 3 ? &maps.wo : wu == 4 ? &maps.w1 : wu == 5 ? &maps.w3 : wu == 6 ? &maps.w2 : &maps.vr;
                asm volatile("prefetch.tensormap [%0];" ::"l"(mp) : "memory");
            }
        }
        if (tid < 160) asm volatile("ld.global.nc.v2.u32 {%0,%1}, [%2];" : "=r"(xv.x), "=r"(xv.y) : "l"(x_in + 4 * tid) : "memory");
        if (tid == 96) { misc[2] = 0.f; misc[3] = 0.f; }
        if (lane == 1) *reinterpret_cast<uint2*>(smem + SM_XL + warp * XSTR) = make_uint2(0u, t_start + WO_T0);
        if (tid >= 128 && tid < 148) {
            const uint32_t v = tid < 138 ? ONES : 0u;
            reinterpret_cast<uint4*>(smem + SM_ONE)[tid - 128] = make_uint4(v, v, v, v);
        }
        if (tid < 160) { xs32[xpos(2 * tid)] = xv.x; xs32[xpos(2 * tid + 1)] = xv.y; }
        __syncthreads();
        PROF_T(14);
        if (b == 0 && tid >= 232) asm volatile("st.relaxed.gpu.global.u32 [%0], %1;" ::"l"(g_scr.ticket + tid - 232), "r"(0) : "memory");
        if (tid == 64 || (tid == 65 && b < 216 - NCTA)) st_pkt(&g_scr.acc[1][(b + NCTA * (tid - 64)) * ACC_STR], 0, 0, 0, 0);
    }

    uint32_t kq[NQ][4];
    const float SC = 0.07216878364870322f * 1.4426950408889634f;

#pragma unroll 1
    for (int ph = 0; ph < 3; ph++) {
        const int layer = ph >> 1;
        const uint32_t tag = layer + 1;
        PROF_T(1 + layer * 16);
        if (ph) {
        {
            const int tl = opq(tid), warp = tl >> 5, lane = tl & 31, g = lane >> 2, t = lane & 3, mat = lane >> 3, r8 = lane & 7;
            const int kh = warp >> 2, mg = warp & 3;
            uint32_t aq[3];
#pragma unroll
            for (int i = 0; i < 3; i++) {
                const int ch = 6 * mg + 2 * i + (mat & 1);
                aq[i] = sb + SM_Q + (80 * kh + (mat >> 1) * 8 + r8) * 128 + (ch >> 3) * 20480 + (((ch & 7) ^ r8) << 4);
            }
#define PF_K5 if (layer == 1 && PFK) tile_keep(&maps.k, (h * SK + (SK - WIN) + c * 1024 + wu * 128 + PFK * 16) * 3);
            uint2 xv = make_uint2(0u, 0u);
            mbar_wait(qbar, 0);
            uint32_t pre[6][4];
#pragma unroll
            for (int n = 0; n < 6; n++) ldsm4t(aq[n % 3] + (n / 3) * 2048, pre[n]);
            if (layer == 1) {
                __syncthreads();
                if (elect_one()) {
                    const uint32_t bar = sb + SM_BAR + wu * 16;
                    asm volatile("mbarrier.expect_tx.relaxed.cta.shared::cta.b64 [%0], 1536;" ::"r"(bar) : "memory");
#pragma unroll
                    for (int k = 0; k < 3; k++)
                        tma2d(sb + SM_Q + v1_pos(3 * wu + k), &maps.vr, 0, (h * SK + (SK - WIN) + c * 1024 + wu * 128) / 2 + 8 + 2 * k, bar, POL_EF);
                }
            }
            const uint32_t pm = opq(g == 1 ? sb + SM_ONE : sb + SM_XS + 160 * (2 * c + kh) + 16 * t), pm2 = opq(pm + 128 - (g == 1 ? 0 : 8 * t));
            const uint32_t dq = opq(sb + SM_R + 8 * (kh * 192 + 48 * mg + g)), ds = opq(sb + SM_ST + 8 * warp + (lane < 16 ? 4 : 0));
            const bool wr = t == 0, ws = (lane & 15) == 0, lo = lane < 16;
            if (wu < 5) {
                const int p0 = xpos(2 * tl), p1 = xpos(2 * tl + 1);
                if (layer == 1) {
                    uint4 v;
                    for (int it = 0; it < SPIN_CAP; it++) { v = ld_pkt(&g_scr.ay[tl]); if (__all_sync(0xffffffffu, v.w == 1)) break; }
                    xv = make_uint2(v.x, v.y);
                    xs32[p0] = xv.x; xs32[p1] = xv.y;
                } else xv = make_uint2(xs32[p0], xs32[p1]);
            }
            if (layer) PC(24);
            __syncthreads();
            PF_K5
            if (layer) PC(25);
            PROF_T(13 + layer * 16);
            const float e0 = bf_lo(xv.x), e1 = bf_hi(xv.x), e2 = bf_lo(xv.y), e3 = bf_hi(xv.y);
            const float s1 = (e0 + e1) + (e2 + e3), s2 = (e0 * e0 + e1 * e1) + (e2 * e2 + e3 * e3);
            float sv = lo ? s1 : s2, cc[3][4];
            gemv15<2048>(cc, pre, [&](int i) { return aq[i]; }, pm, pm2, sv, lo ? s2 : s1);
            if (wr) {
#pragma unroll
                for (int i = 0; i < 3; i++) { sts64(dq + 128 * i, cc[i][0], cc[i][1]); sts64(dq + 128 * i + 64, cc[i][2], cc[i][3]); }
            }
            if (ws) sts32(ds, sv);
        }
        const uint32_t pa = opq(sb + SM_R + 32 * opq(tid)), st = opq(sb + SM_ST);
        uint4* const pq = opq(&g_scr.hx[b * 48 + opq(tid)]);
        if (layer) PC(26);
        __syncthreads();
        if (layer) PC(27);
        PROF_T(33 + layer * 16);
        if (wu < 2) {
            float mean, inv;
            ln_stats(st, mean, inv);
            const float4 a0 = lds4f(pa), a1 = lds4f(pa + 16), b0 = lds4f(pa + 1536), b1 = lds4f(pa + 1552);
            float q0 = inv * ((a0.x + b0.x) - mean * (a0.y + b0.y)), q1 = inv * ((a0.z + b0.z) - mean * (a0.w + b0.w));
            float q2 = inv * ((a1.x + b1.x) - mean * (a1.y + b1.y)), q3 = inv * ((a1.z + b1.z) - mean * (a1.w + b1.w));
            st_pktfp(pq, q0, q1, q2, q3, 1, tid < 48);
        }
        if (layer == 1 && tid >= 192 && tid < 194 && b < 108) st_pkt(&g_scr.acc[0][(2 * b + opq(tid) - 192) * ACC_STR], 0, 0, 0, 0);
        }
        if (layer) PC(28);
        if (layer == 1 && (wu & 2)) {
            idle(K5D);
#pragma unroll 1
            for (int w = wu; w >= (wu > 4 ? wu - 2 : wu); w -= 2)
                tile_load(sb + SM_Q + c_slot(w), &maps.k, (h * SK + (SK - WIN) + c * 1024 + w * 128 + 5 * 16) * 3, sb + SM_XBAR + w * 8, 0, 0);
        }

        float sc0 = -INFINITY, sc1 = -INFINITY, sc2 = 0.f, sc3 = 0.f, mw;
        uint32_t pk0, pk1;
        float acc[3][4];
        {
            const uint32_t ring = sb + SM_RING + wu * 2 * TILE, rb = sb + SM_BAR + wu * 16;
            const uint32_t xtile = sb + SM_Q + c_slot(wu), xb = sb + SM_XBAR + wu * 8;
#define V_SEQ(n) ((int)(SEQ1 >> (4 * (n))) & 7)
#define SLOT1(n) (((IN_S1 >> (n)) & 1) ? ring + TILE : ((IN_S0 >> (n)) & 1) ? ring : sb + SM_B + wu * TILE)
#define BAR1(n) (((IN_S1 >> (n)) & 1) ? rb + 8 : ((IN_S0 >> (n)) & 1) ? rb : xb)
#define PAR1(n) ((PARITY1 >> (n)) & 1)
#define PAR2(n) ((PARITY2 >> (n)) & 1)
            const int row0 = (h * SK + (SK - WIN) + c * 1024 + wu * 128) * 3;
            auto issue1 = [&](int n, uint32_t dep, bool vph = false) {
                const CUtensorMap* mp = n < 8 ? &maps.k : &maps.v;
                const int tl = V_SEQ(n), row = row0 + tl * 48;
                const uint32_t dst = SLOT1(n), bar = BAR1(n);
                if (vph && wu < L1R && tl == 7 - (wu & 1)) {
                    tile_load_l1(dst, maps.vp, row, bar, opq(tid) & 31);
                    return;
                }
                tile_load(dst, mp, row, bar, dep, maps.zero);
                if ((RT_SEL >> (tl + (n & 8))) & 1) {
                    if (n != V0_AT + 1) tile_keep(mp, row);
                    else if ((opq(tid) & 31) < 8)
                        asm volatile("cp.async.bulk.prefetch.L2.global.L2::cache_hint [%0], 256, %1;"
                                     ::"l"(static_cast<const char*>(maps.vp) + (size_t)(row + 4 + 6 * (opq(tid) & 31)) * 128), "l"(POL_EN) : "memory");
                }
            };
            auto refill1 = [&](int s, uint32_t dep, bool vph = false) { issue1(s + (!vph || s < V0_AT ? 3 : 2), dep, vph); };
#define LANE_IDS const int tl = opq(tid), lane = tl & 31, g = lane >> 2, t = lane & 3; (void)tl; (void)lane; (void)g; (void)t;
            const uint32_t xl = sb + SM_XL + wu * XSTR;
            if (layer == 0) {
#pragma unroll 1
                for (int s = ph ? Q_AT : 0; s < (ph ? 5 : Q_AT); s++) {
                    LANE_IDS
                    const uint32_t tile = SLOT1(s);
                    mbar_wait(BAR1(s), PAR1(s));
                    const uint32_t scl = s == 0 ? pack_scale(tile, lane, xl + 8) : lds32(xl + 8);
                    pack_tile<false>(tile, s, 3, scl, xl, lane, [](int, uint32_t (&)[3]) {});
#pragma unroll
                    for (int n = 0; n < 5; n++) {
                        if (s == n) {
#pragma unroll
                            for (int m = 0; m < 3; m++) {
                                const uint32_t a = tile + K_OFF(2 * m);
                                lds128(a, kq[9 * n + 3 * m][0], kq[9 * n + 3 * m][1], kq[9 * n + 3 * m][2], kq[9 * n + 3 * m][3]);
                                lds128(a ^ 64, kq[9 * n + 3 * m + 1][0], kq[9 * n + 3 * m + 1][1], kq[9 * n + 3 * m + 1][2], kq[9 * n + 3 * m + 1][3]);
                                lds128(a + 3072, kq[9 * n + 3 * m + 2][0], kq[9 * n + 3 * m + 2][1], kq[9 * n + 3 * m + 2][2], kq[9 * n + 3 * m + 2][3]);
                            }
                        }
                    }
                    __syncwarp();
                    refill1(s, lds32(tile));
                }
                if (!ph) continue;
            }
            {
                if (wu < 2) {
                    const int tl = min(opq(tid), 47);
                    const int w = 2 * tl;
                    const uint32_t pos = opq(sb + SM_QS + 4 * (((w >> 2) & 3) * 24 + 2 * (w >> 4) + ((w >> 1) & 1)));
                    uint4 v[4];
                    for (int it = 0; it < SPIN_CAP; it++) {
#pragma unroll
                        for (int k = 0; k < 4; k++) v[k] = ld_pkt(&g_scr.hx[(h * 4 + k) * 48 + tl]);
                        if (__all_sync(0xffffffffu, ((v[0].w & v[1].w) & (v[2].w & v[3].w)) & 1)) break;
                    }
                    sts32(pos, f_(pack2((f_(v[0].x) + f_(v[1].x)) + (f_(v[2].x) + f_(v[3].x)), (f_(v[0].y) + f_(v[1].y)) + (f_(v[2].y) + f_(v[3].y)))));
                    sts32(pos + 48, f_(pack2((f_(v[0].z) + f_(v[1].z)) + (f_(v[2].z) + f_(v[3].z)), (f_(v[0].w) + f_(v[1].w)) + (f_(v[2].w) + f_(v[3].w)))));
                }
            }
            if (layer) PC(29);
            __syncthreads();
            if (layer) PC(30);
            PROF_T(2 + layer * 16);
#define V1_REST(p) ((p) < 6 ? sb + SM_Q + v1_pos(3 * wu + ((p) >> 1)) + 256 * ((p) & 1) : ((sb + SM_R + wu * 784 + 127) & ~127u) - 1536 + 256 * (p))
#define V1_LOAD(bar) if (elect_one()) tma2d(V1_REST(6), &maps.vr, 0, row0 / 6 + 14, bar, POL_EF);
#define V1_EXPECT(bar) { if ((opq(tid) & 31) == 0) asm volatile("mbarrier.expect_tx.relaxed.cta.shared::cta.b64 [%0], 512;" ::"r"(bar) : "memory"); }
            if (layer == 1 && wu < 2) tile_load(xtile, &maps.k, row0 + 5 * 48, xb, 0, 0);
            if (layer == 1 && wu >= 4) idle(STAG);
            {
                uint32_t qf[12];
                int t;
                {
                    const int lane = opq(tid) & 31;
                    t = lane & 3;
                    const uint32_t qa = sb + SM_QS + (2 * t + ((lane >> 2) & 1)) * 48;
#pragma unroll
                    for (int i = 0; i < 3; i++) lds128(qa + 16 * i, qf[4 * i], qf[4 * i + 1], qf[4 * i + 2], qf[4 * i + 3]);
                }
                const uint32_t sq = lds32(xl + 8) - 64u * 0x00800080u;
#pragma unroll
                for (int i = 0; i < 12; i++) qf[i] = bmul2(qf[i], sq);
#define KR_STEP(tau, m) \
                    _Pragma("unroll") for (int i = 2 * (m); i < 2 * (m) + 2; i++) { \
                        const int q0 = 9 * tau + 3 * (i >> 1), r = i & 1; \
                        uint32_t w[4]; \
                        unpack8(kq[q0][2 * r], kq[q0][2 * r + 1], kq[q0 + 2][r], w); \
                        mma16816(cA, w[0], w[1], w[2], w[3], qf[2 * i], qf[2 * i + 1]); \
                        unpack8(kq[q0 + 1][2 * r], kq[q0 + 1][2 * r + 1], kq[q0 + 2][2 + r], w); \
                        mma16816(cB, w[0], w[1], w[2], w[3], qf[2 * i], qf[2 * i + 1]); \
                    }
#define KR_BEGIN float cA[4] = {0.f, 0.f, 0.f, 0.f}, cB[4] = {0.f, 0.f, 0.f, 0.f};
#define KR_END(tau) \
                    const float sA = (cA[0] + cA[3]) * 18446744073709551616.f, sB = (cB[0] + cB[3]) * 18446744073709551616.f; \
                    if (t == (tau & 3)) { if (tau < 4) { sc0 = sA; sc1 = sB; } else { sc2 = sA; sc3 = sB; } }
#define KR_SCORES(tau) { KR_BEGIN KR_STEP(tau, 0) KR_STEP(tau, 1) KR_STEP(tau, 2) KR_END(tau) }
                uint32_t va[3];
                {
                    const int lane = opq(tid) & 31, g = lane >> 2, t = lane & 3;
#pragma unroll
                    for (int i = 0; i < 3; i++) va[i] = ring + V_OFF(2 * i);
                }
#define V_STG(n) _Pragma("unroll") for (int j = 3 * (n); j < 3 * (n) + 3; j++) { \
                    const int i = (j % 12) >> 1; \
                    lds128p(((i & 1) ? (va[i >> 1] ^ 16) + 128 : va[i >> 1]) + (j / 12) * TILE + (j & 1) * 3072, layer, kq[j][0], kq[j][1], kq[j][2], kq[j][3]); }
                uint32_t dep = 0;
                {
                    KR_BEGIN
                    KR_STEP(0, 0) V_STG(0) KR_STEP(0, 1) V_STG(1) KR_STEP(0, 2) V_STG(2)
                    KR_END(0)
                }
                {
                    KR_BEGIN
                    KR_STEP(1, 0) V_STG(3)
                    __syncwarp();
                    dep = lds32(ring);
                    if (layer == 1) tile_load(ring, &maps.k, row0 + 6 * 48, rb, dep, maps.zero);
                    KR_STEP(1, 1) V_STG(4) KR_STEP(1, 2) V_STG(5)
                    KR_END(1)
                }
                {
                    KR_BEGIN
                    KR_STEP(2, 0) V_STG(6) KR_STEP(2, 1) V_STG(7)
                    __syncwarp();
                    dep = lds32(ring + TILE);
                    KR_STEP(2, 2)
                    if (layer == 1) {
                        V1_EXPECT(rb + 8)
                        tile_load(ring + TILE, &maps.k, row0 + 7 * 48, rb + 8, dep, maps.zero);
                        V1_LOAD(rb + 8)
                    }
                    KR_END(2)
                }
#pragma unroll 1
                for (int s = 5; s < 8; s++) {
                    {
                        LANE_IDS
                        const uint32_t tile = !layer ? SLOT1(s) : s == 5 ? xtile : ring + (s - 6) * TILE, tb = !layer ? BAR1(s) : s == 5 ? xb : rb + (s - 6) * 8;
                        const float ur = f_((318u << 23) - (lds32(xl + 8) << 16));
                        mbar_wait(tb, layer ? PAR2(s - 5) : PAR1(s));
                        if (layer) PROF_T(29 + s);
                        float cA[4] = {0.f, 0.f, 0.f, 0.f}, cB[4] = {0.f, 0.f, 0.f, 0.f};
#pragma unroll
                        for (int i = 0; i < 6; i++) {
                            uint32_t a0, a1, a2, a3;
                            lds128(tile + K_OFF(i), a0, a1, a2, a3);
                            mma16816(cA, a0, a1, a2, a3, qf[2 * i], qf[2 * i + 1]);
                            lds128(tile + K_OFF(i) + 3072, a0, a1, a2, a3);
                            mma16816(cB, a0, a1, a2, a3, qf[2 * i], qf[2 * i + 1]);
                        }
                        __syncwarp();
                        const uint32_t last = lds32(tile);
                        if (layer) tile_load(tile, &maps.v, row0 + (s - 2) * 48, tb, last, maps.zero);
                        else refill1(s, last);
                        if (t == (s & 3)) { sc2 = (cA[0] + cA[3]) * ur; sc3 = (cB[0] + cB[3]) * ur; }
                    }
                    if (s == 5) KR_SCORES(3)
                    if (s == 6) {
                        KR_SCORES(4)
                        const int lane = opq(tid) & 31;
                        const uint32_t nx = min(lds32(xl), (uint32_t)XCAP);
#pragma unroll 1
                        for (uint32_t n = 0; n < nx; n++) {
                            const uint32_t id = lds32(xl + 16 + 4 * n);
                            const uint32_t qo = 96 * ((id >> 7) & 3) + 48 * ((id >> 1) & 1) + 16 * ((id >> 5) & 3) + (id & 12) + 2 * (id & 1);
                            const float cr = bf_hi(id) * f_(lds16(sb + SM_QS + qo) << 16);
                            const int d = (int)(16 * ((id >> 9) & 7) + 4 * ((id >> 12) & 3) + ((id >> 13) & 2) + ((id >> 4) & 1) + ((id >> 8) & 128)) - 4 * lane;
                            if (d == 0) sc0 += cr;
                            if (d == 1) sc1 += cr;
                            if (d == 2) sc2 += cr;
                            if (d == 3) sc3 += cr;
                        }
                    }
                }
#undef KR_SCORES
#undef KR_STEP
#undef KR_BEGIN
#undef KR_END
#undef V_STG
                {
                    LANE_IDS
                    if (lds32(xl) > XCAP || !__all_sync(0xffffffffu, (fabsf(sc0) + fabsf(sc1)) + (fabsf(sc2) + fabsf(sc3)) < INFINITY)) {
                        const uint32_t qa = sb + SM_QS + (2 * t + (g & 1)) * 48;
#pragma unroll
                        for (int i = 0; i < 3; i++) lds128(qa + 16 * i, qf[4 * i], qf[4 * i + 1], qf[4 * i + 2], qf[4 * i + 3]);
                        const uint4* kg = reinterpret_cast<const uint4*>(static_cast<const char*>(maps.kp) + (size_t)row0 * 128) + ((g >> 1) + 4 * (g & 1)) * 24 + t;
#pragma unroll 1
                        for (int s = 0; s < 8; s++) {
                            float cA[4] = {0.f, 0.f, 0.f, 0.f}, cB[4] = {0.f, 0.f, 0.f, 0.f};
#pragma unroll
                            for (int i = 0; i < 6; i++) {
                                uint4 u = ldg128(kg + s * 384 + 4 * i);
                                mma16816v(cA, u.x, u.y, u.z, u.w, qf[2 * i], qf[2 * i + 1]);
                                u = ldg128(kg + s * 384 + 4 * i + 192);
                                mma16816v(cB, u.x, u.y, u.z, u.w, qf[2 * i], qf[2 * i + 1]);
                            }
                            if (t == s) { sc0 = cA[0] + cA[3]; sc1 = cB[0] + cB[3]; }
                            if (t + 4 == s) { sc2 = cA[0] + cA[3]; sc3 = cB[0] + cB[3]; }
                        }
                    }
                }
            }
            mw = warp_max(fmaxf(fmaxf(sc0, sc1), fmaxf(sc2, sc3)));
            pk0 = pack2(ex2((sc0 - mw) * SC), ex2((sc1 - mw) * SC));
            pk1 = pack2(ex2((sc2 - mw) * SC), ex2((sc3 - mw) * SC));
            sc2 = (bf_lo(pk0) + bf_hi(pk0)) + (bf_lo(pk1) + bf_hi(pk1));
            sc2 = (float)__reduce_add_sync(0xffffffffu, __float2uint_rn(sc2 * 16777216.f)) * (1.0f / 16777216.f);
            if ((opq(tid) & 31) == 0) st_pkt2(&g_scr.mx[h * 32 + c * 8 + wu], __float_as_uint(mw), (__float_as_uint(sc2) & ~3u) | tag);
            auto head_factor = [&]() {
                const int lane = opq(tid) & 31;
                int it = 0;
                while (!__all_sync(0xffffffffu, (__float_as_uint(sc1) & 3u) == tag) && ++it < SPIN_CAP) {
                    const uint2 mv = ld_pkt2(&g_scr.mx[h * 32 + lane]); sc0 = f_(mv.x); sc1 = f_(mv.y);
                }
                const float e = ex2((sc0 - warp_max(sc0)) * SC);
                const uint32_t d = __reduce_add_sync(0xffffffffu, __float2uint_rn(sc1 * e * 524288.f));
                sc3 = __shfl_sync(0xffffffffu, e, c * 8 + wu) * 524288.f * rcp((float)d);
            };
#pragma unroll
            for (int s = 0; s < 3; s++) { acc[s][0] = acc[s][1] = acc[s][2] = acc[s][3] = 0.f; }
#define P_CONSTS \
                const uint32_t sel0 = g == 0 ? 0x4410u : (g == 1 ? 0x1044u : 0x4444u); \
                const uint32_t sel1 = g == 2 ? 0x4410u : (g == 3 ? 0x1044u : 0x4444u); \
                const int src00 = 4 * (t < 2 ? 4 * t : 4 * (t - 2) + 1);
#define P_FRAGS(tau) \
                const uint32_t pk = ((tau) & 4) ? pk1 : pk0; \
                const uint32_t w0 = __shfl_sync(0xffffffffu, pk, src00 + ((tau) & 3)); \
                const uint32_t w1 = __shfl_sync(0xffffffffu, pk, src00 + ((tau) & 3) + 8); \
                uint32_t pb[4][2]; \
                _Pragma("unroll") for (int j = 0; j < 4; j++) { \
                    const uint32_t src = ((j & 1) ? w1 : w0) >> ((j >> 1) * 16); \
                    pb[j][0] = __byte_perm(src, 0, sel0); pb[j][1] = __byte_perm(src, 0, sel1); \
                }
            if (layer == 0) {
#pragma unroll 1
                for (int s = 8; s < 16; s++) {
                    LANE_IDS
                    P_CONSTS
                    if (s == 13) { const uint2 mv = ld_pkt2(&g_scr.mx[h * 32 + lane]); sc0 = f_(mv.x); sc1 = f_(mv.y); }
                    P_FRAGS(V_SEQ(s))
                    mbar_wait(BAR1(s), PAR1(s));
                    const uint32_t tile = SLOT1(s);
#pragma unroll
                    for (int j = 0; j < 4; j++) {
#pragma unroll
                        for (int u = 0; u < 3; u++) {
                            uint32_t a0, a1, a2, a3;
                            lds128(tile + (j >> 1) * 3072 + V_OFF(3 * (j & 1) + u), a0, a1, a2, a3);
                            mma16816(acc[u], a0, a1, a2, a3, pb[j][0], pb[j][1]);

                        }
                    }
                    __syncwarp();
                    if (s < V0_AT || (s > V0_AT + 1 && s < 14)) refill1(s, lds32(tile), true);
                    if (s == V0_AT || s == V0_AT + 1) {
                        {
                            const uint32_t ar = sb + SM_R + wu * 784 + 32 * g + 16 * t;
                            if (t < 2) {
#pragma unroll
                                for (int u = 0; u < 3; u++) sts128(ar + 256 * u, __float_as_uint(acc[u][0]), __float_as_uint(acc[u][1]), __float_as_uint(acc[u][2]), __float_as_uint(acc[u][3]));
                            }
                        }
                        const uint32_t scl = s == V0_AT ? pack_scale(tile, lane, xl + 12) : lds32(xl + 12);
                        pack_tile<true>(tile, s + 8 - V0_AT, V0_AT + 3 - s, scl, xl, lane, [&](int m, uint32_t (&d)[3]) {
                            if (s != V0_AT && m == 0) {
#pragma unroll
                                for (int k = 0; k < 3; k++) d[k] = ring + 3072 + V_OFF(2 * k + 1);
                            }
                        });
                        if (s != V0_AT) {
                            lds128(tile + V_OFF(2), kq[45][0], kq[45][1], kq[45][2], kq[45][3]);
                            lds128(tile + V_OFF(3), kq[46][0], kq[46][1], kq[46][2], kq[46][3]);
                            lds128(tile + V_OFF(2) + 3072, kq[47][0], kq[47][1], kq[47][2], kq[47][3]);
                            __syncwarp();
                            issue1(V0_AT + 3, lds32(tile));
                        }
                        const int ln = opq(tid) & 31;
                        const uint32_t ar = sb + SM_R + wu * 784 + 8 * (ln & 28) + 16 * (ln & 1);
#pragma unroll
                        for (int u = 0; u < 3; u++) {
                            uint32_t a0, a1, a2, a3;
                            lds128(ar + 256 * u, a0, a1, a2, a3);
                            acc[u][0] = f_(a0); acc[u][1] = f_(a1); acc[u][2] = f_(a2); acc[u][3] = f_(a3);
                        }
                    }
                    if (s == 13) head_factor();
                    if (s >= 14 && elect_one()) {
                        if (atomicAdd(reinterpret_cast<unsigned*>(misc + 3), 1u) == 14u && (int)(now_ns() - lds32(xl + 4)) >= 0) {
                            PROF_X(47);
                            load_wo(maps, sb + SM_B, h, c, wbar, 6);
                            atomicAdd(reinterpret_cast<unsigned*>(misc + 3), 256u);
                        }
                    }
                }
            } else {
                LANE_IDS
                P_CONSTS
#pragma unroll
                for (int k = 0; k < 4; k++) lds128(V1_REST(t + 4 * (k >> 1)) + 16 * g + 128 * (k & 1), kq[36 + k][0], kq[36 + k][1], kq[36 + k][2], kq[36 + k][3]);
#pragma unroll 1
                for (int i = 3; i < 8; i++) {
                    const uint32_t tile = i > 3 ? ring + (i & 1) * TILE : xtile, tb = i > 3 ? rb + (i & 1) * 8 : xb;
                    if (i == 6) { const uint2 mv = ld_pkt2(&g_scr.mx[h * 32 + lane]); sc0 = f_(mv.x); sc1 = f_(mv.y); }
                    if (i == 7) head_factor();
                    if (i == PK_AT) {
                uint32_t nx, nk, ik, iv;
                lds128(xl, nx, nk, ik, iv);
                if (nx <= XCAP) {
                    const uint32_t pks = bmul2(pk0, iv);
#pragma unroll
                    for (int s = 0; s < 2; s++) {
                        const uint32_t pk1 = 0, pk0 = pks;
                        P_FRAGS(s)
#pragma unroll
                        for (int j = 0; j < 4; j++) {
#pragma unroll
                            for (int u = 0; u < 3; u++) {
                                const int i = 3 * (j & 1) + u, m = i >> 1, r = i & 1, hf = j >> 1;
                                if (s == 1 && m == 2) continue;
                                const int ql = s == 0 ? 4 * m + 2 * hf : m == 0 ? 3 + 4 * hf : 45 + hf, qc = s == 0 ? 4 * m + 1 : m == 0 ? 11 : 47;
                                uint32_t w[4];
                                unpack8(kq[ql][2 * r], kq[ql][2 * r + 1], kq[qc][2 * hf + r], w);
                                mma16816(acc[u], w[0], w[1], w[2], w[3], pb[j][0], pb[j][1]);
                            }
                        }
                    }
#pragma unroll 1
                    for (uint32_t n = 0; n < nx; n++) {
                        const uint32_t id = lds32(xl + 16 + 4 * n);
                        const int i = ((id >> 4) & 6) + ((id >> 3) & 1), key = ((id >> 6) & 6) + (i >= 3);
                        const uint32_t pw = __shfl_sync(0xffffffffu, pk0, 8 * (key & 3) + (key & 4) + ((id >> 12) & 3));
                        const float cr = bf_hi(id) * ((id & 16) ? bf_hi(pw) : bf_lo(pw));
                        const int d = (int)(64 * ((id >> 9) & 7) + 4 * (id & 4) + 4 * (i >= 3 ? i - 3 : i) + (id & 3) + ((~id >> 5) & 1024)) - 16 * lane;
#pragma unroll
                        for (int k = 0; k < 12; k++) if (d == k) acc[k >> 2][k & 3] += cr;
                    }
                } else {
                    const uint4* vg = reinterpret_cast<const uint4*>(static_cast<const char*>(maps.vp) + (size_t)row0 * 128) + 48 * t + g;
#pragma unroll 1
                    for (int s = 0; s < 2; s++) {
                        P_FRAGS(s)
#pragma unroll
                        for (int j = 0; j < 4; j++) {
#pragma unroll
                            for (int u = 0; u < 3; u++) {
                                if (s == 1 && (j & 1) && u) continue;
                                const uint4 w = ldg128(vg + 384 * s + 192 * (j >> 1) + 24 * (j & 1) + 8 * u);
                                mma16816v(acc[u], w.x, w.y, w.z, w.w, pb[j][0], pb[j][1]);
                            }
                        }
                    }
                }
#pragma unroll
                for (int s = 2; s > 0; s--) {
                    P_FRAGS(s)
#pragma unroll
                    for (int j = 0; j < 4; j++) {
#pragma unroll
                        for (int u = 0; u < 3; u++) {
                            if (s == 1 && !((j & 1) && u)) continue;
                            const int k = s == 2 ? 12 + 2 * (3 * (j & 1) + u) + (j >> 1) : 35 + (j >> 1) * 2 + u;
                            mma16816(acc[u], kq[k][0], kq[k][1], kq[k][2], kq[k][3], pb[j][0], pb[j][1]);
                        }
                    }
                }
                    }
                    P_FRAGS(i)
                    mbar_wait(tb, PAR2(i));
                    PROF_T(34 + i);
#pragma unroll
                    for (int k = 0; k < 6; k++) {
                        const uint32_t a = tile + V_OFF(k);
                        lds128(a, kq[24 + k][0], kq[24 + k][1], kq[24 + k][2], kq[24 + k][3]);
                        lds128(a + 3072, kq[30 + k][0], kq[30 + k][1], kq[30 + k][2], kq[30 + k][3]);
                    }
#pragma unroll
                    for (int j = 0; j < 4; j++) {
#pragma unroll
                        for (int u = 0; u < 3; u++) {
                            const int k = 24 + 6 * (j >> 1) + 3 * (j & 1) + u;
                            mma16816(acc[u], kq[k][0], kq[k][1], kq[k][2], kq[k][3], pb[j][0], pb[j][1]);
                        }
                    }
                    __syncwarp();
                    if (wu < L1R && i == 5 - (wu & 1)) tile_load_l1(tile, maps.vp, row0 + (i + 2) * 48, tb, lane);
                    else if (i == 4 || i == 5) tile_load(tile, &maps.v, row0 + (i + 2) * 48, tb, lds32(tile), maps.zero);
                    if (i == WO_AT1 && HAS_FFN && elect_one()) {
                        if (atomicAdd(reinterpret_cast<unsigned*>(misc + 2), 1u) == 7u) {
                            PROF_X(63);
                            load_wo(maps, sb + SM_Q, h, c, wbar, KEEP4 && __float_as_uint(misc[1]) >= DN0 ? 5 : 6);
                        }
                    }
                }
            }
#undef P_FRAGS
#undef P_CONSTS
#undef LANE_IDS
        }
        PROF_T(3 + layer * 16);
        PC(layer * 32 + 1);

        {
            const int lane = opq(tid) & 31;
            const uint32_t a = sb + SM_R + wu * 784 + 8 * (lane & 28) + 16 * (lane & 1);
#pragma unroll
            for (int u = 0; u < 3; u++) sts128p(a + 256 * u, acc[u][0] * sc3, acc[u][1] * sc3, acc[u][2] * sc3, acc[u][3] * sc3, lane & 2);
        }
        const uint32_t role1 = layer ? lds32(sb + SM_MISC + 4) : DN0 + NDN;
        const uint32_t pc = opq(sb + SM_R + 16 * opq(tid));
        uint4* const px0 = opq(&g_scr.hx[b * 48 + opq(tid)]);
        __syncthreads();
        PROF_T(4 + layer * 16);
        PC(layer * 32 + 2);
        float4 o = make_float4(0.f, 0.f, 0.f, 0.f);
        if (wu < 2) {
            float4 v[8];
#pragma unroll
            for (int w = 0; w < 8; w++) v[w] = lds4f(pc + w * 784);
            o.x = ((v[0].x + v[1].x) + (v[2].x + v[3].x)) + ((v[4].x + v[5].x) + (v[6].x + v[7].x));
            o.y = ((v[0].y + v[1].y) + (v[2].y + v[3].y)) + ((v[4].y + v[5].y) + (v[6].y + v[7].y));
            o.z = ((v[0].z + v[1].z) + (v[2].z + v[3].z)) + ((v[4].z + v[5].z) + (v[6].z + v[7].z));
            o.w = ((v[0].w + v[1].w) + (v[2].w + v[3].w)) + ((v[4].w + v[5].w) + (v[6].w + v[7].w));
            o.w = f_(__float_as_uint(o.w) & ~1u);
            st_pktp(px0, __float_as_uint(o.x), __float_as_uint(o.y), __float_as_uint(o.z), __float_as_uint(o.w), threadIdx.x < 48);
        }
        uint32_t ticket = 0;
        if (layer == 0 && tid == 224)
            asm volatile("atom.relaxed.gpu.global.inc.u32 %0, [%1], 0x7fffffff;" : "=r"(ticket) : "l"(g_scr.ticket + 8 + (b >> 3)) : "memory");
        if (layer == 0 && tid == 224 && lds32(sb + SM_MISC + 12) < 256u) {
            int it = 0;
            while ((int)(now_ns() - lds32(sb + SM_XL + 4)) < 0 && ++it < SPIN_CAP) {}
            PROF_X(47);
            load_wo(maps, sb + SM_B, h, c, wbar, 6);
        }
        uint32_t pr;
        uint4* pacc;
        {
            const int tid = opq(threadIdx.x), warp = tid >> 5, lane = tid & 31, g = lane >> 2, t = lane & 3, mat = lane >> 3, r8 = lane & 7;
            const int kg = warp >> 1, mg = warp & 1;
            const bool wo2 = role1 < DN0 + NDN;
            const uint32_t aw2 = 40960 + (wo2 && KEEP4 && role1 >= DN0 && kg >= 2 ? SM_B - SM_Q : 0);
            uint32_t aw[5];
#pragma unroll
            for (int i = 0; i < 5; i++) {
                const uint32_t lin = ((mat >> 1) * 8 + r8) * 320 + 64 * i + 32 * mg + 16 * (mat & 1);
                aw[i] = sb + (wo2 ? SM_Q : SM_B) + 5120 * kg + (lin ^ ((lin >> 3) & 48));
            }
#define CXE 0
            const uint32_t ao = pin(sb + SM_OS + 96 * kg + 16 * t), dw = pin(sb + SM_R + 16 * (16 * mg + g) + 4 * kg);
            pr = pin(sb + SM_R + 48 * tid); pacc = pin(&g_scr.acc[layer][(54 * c + tid) * ACC_STR]);
            const int w = 2 * min(tid, 47);
            const uint32_t d0 = pin(sb + SM_OS + 4 * (24 * ((w >> 3) & 3) + ((w >> 2) & 1) + (w < 64 ? 4 * (w & 3) + 2 * (w >> 5) : 16 + 2 * (w & 3))));
            const uint32_t d1 = pin(d0 + (w < 64 ? 16 : 8));
            const uint4* pp[3];
#pragma unroll
            for (int k = 0; k < 3; k++) pp[k] = pin(&g_scr.hx[(h * 4 + ((c + 1 + k) & 3)) * 48 + min(tid, 47)]);
            bool ok = true;
            if ((PRE1 & 8) && layer) {
#pragma unroll
                for (int ks = 0; ks < 3; ks++) {
                    mbar_wait(wbar + 8 * ks, wo2);
#pragma unroll
                    for (int i = 0; i < 5; i++) ldsm4t(aw[i] + (ks == 2 ? aw2 : 20480 * ks), kq[3 * i + ks]);
                    if (ks == CXE && wu < 2) {
#pragma unroll
                        for (int k = 0; k < 3; k++) { const uint4 v = ld_pkt(pp[k]); kq[20 + k][0] = v.x; kq[20 + k][1] = v.y; kq[20 + k][2] = v.z; kq[20 + k][3] = v.w; }
                    }
                }
                PROF_T(50);
                if (CXE < 3 && wu < 2) {
                    ok = __any_sync(0xffffffffu, (kq[20][3] | kq[21][3] | kq[22][3]) & 1);
                    if (!ok) {
#pragma unroll
                        for (int k = 0; k < 3; k++) { o.x += f_(kq[20 + k][0]); o.y += f_(kq[20 + k][1]); o.z += f_(kq[20 + k][2]); o.w += f_(kq[20 + k][3]); }
                    }
                }
            }
            if (wu < 2) {
                if (ok) {
                    uint4 v3[3];
                    int it = 0;
                    do {
#pragma unroll
                        for (int k = 0; k < 3; k++) v3[k] = ld_pkt(pp[k]);
                        ok = __any_sync(0xffffffffu, (v3[0].w | v3[1].w | v3[2].w) & 1);
                    } while (ok && ++it < SPIN_CAP);
#pragma unroll
                    for (int k = 0; k < 3; k++) { o.x += f_(v3[k].x); o.y += f_(v3[k].y); o.z += f_(v3[k].z); o.w += f_(v3[k].w); }
                }
                sts32p(d0, f_(pack2(o.x, o.y)), tid >= 48);
                sts32p(d1, f_(pack2(o.z, o.w)), tid >= 48);
            }
            PC(layer * 32 + 3);
            __syncthreads();
            PROF_T(5 + layer * 16);
            PC(layer * 32 + 5);
            if (tid == 224 && layer == 0) {
                if (ticket >= 6 + ((b >> 3) & 1)) ticket = DN0 + NDN;
                else asm volatile("atom.relaxed.gpu.global.inc.u32 %0, [%1], 0x7fffffff;" : "=r"(ticket) : "l"(g_scr.ticket) : "memory");
            }
            uint32_t ob[6];
            lds128(ao, ob[0], ob[1], ob[2], ob[3]);
            lds64(ao + 64 - 8 * t, ob[4], ob[5]);
            float cc[5][4];
#pragma unroll
            for (int i = 0; i < 5; i++) cc[i][0] = cc[i][1] = cc[i][2] = cc[i][3] = 0.f;
            if ((PRE1 & 8) && layer) {
#pragma unroll
                for (int ks = 0; ks < 3; ks++) {
#pragma unroll
                    for (int i = 0; i < 5; i++) mma16816(cc[i], kq[3 * i + ks][0], kq[3 * i + ks][1], kq[3 * i + ks][2], kq[3 * i + ks][3], ob[2 * ks], ob[2 * ks + 1]);
                }
            } else {
#pragma unroll
                for (int ks = 0; ks < 3; ks++) {
                    mbar_wait(wbar + 8 * ks, wo2);
                    if (ks == 2) { PC(layer * 32 + 4); PROF_T(48 + layer * 2); }
                    uint32_t a[5][4];
#pragma unroll
                    for (int i = 0; i < 5; i++) ldsm4t(aw[i] + (ks == 2 ? aw2 : 20480 * ks), a[i]);
#pragma unroll
                    for (int i = 0; i < 5; i++) mma16816(cc[i], a[i][0], a[i][1], a[i][2], a[i][3], ob[2 * ks], ob[2 * ks + 1]);
                }
            }
            if (t == 0) {
#pragma unroll
                for (int i = 0; i < 5; i++) { sts32(dw + 512 * i, cc[i][0]); sts32(dw + 512 * i + 128, cc[i][2]); }
            }
        }
        PC(layer * 32 + 6);
        __syncthreads();
        PROF_T(6 + layer * 16);
        PC(layer * 32 + 7);
        if (tid < 54) {
            const float4 v0 = lds4f(pr), v1 = lds4f(pr + 16), v2 = lds4f(pr + 32);
            const float y0 = (v0.x + v0.y) + (v0.z + v0.w), y1 = (v1.x + v1.y) + (v1.z + v1.w), y2 = (v2.x + v2.y) + (v2.z + v2.w);
            red_pkt(pacc, y0, tid == 53 ? 0.f : y1, tid == 53 ? 0.f : y2);
        }
        if (tid == 224 && layer == 0) {
            misc[1] = __uint_as_float(ticket);
            if (ticket < DN0 + NDN && (ticket < NG || !DNTH)) load_ffn(maps, ticket, sb + SM_B, fbar);
        }
        PROF_T(7 + layer * 16);
        PC(layer * 32 + 8);
        __syncthreads();
        const int role = (int)__float_as_uint(misc[1]);
        PC(layer * 32 + 9);
        const uint32_t fbase = sb + SM_B;
        const uint32_t DONE32 = 0x42000000u;
        if (role < NG) {
            const int tid = opq(threadIdx.x), warp = tid >> 5, lane = tid & 31, g = lane >> 2, t = lane & 3, mat = lane >> 3, r8 = lane & 7;
            const uint32_t ag = fbase + (80 * warp + (mat >> 1) * 8 + r8) * 96 + (((mat & 1) ^ (r8 >> 2)) << 4);
            constexpr int GI = 32, GK = 16 * 96;
            const bool on = (g & 1) == (t >> 1), isx = on && g < 2;
            const uint32_t pm = opq(isx ? sb + SM_XS + 160 * warp + 16 * t : sb + (on ? SM_ONE : SM_ZERO)), pm2 = opq(pm + 128 - (isx ? 8 * t : 0));
            const uint32_t dg = opq(sb + SM_R + 4 * (2 * (warp * 48 + g) + t)), ds = opq(sb + SM_ST + 8 * warp + (lane < 16 ? 4 : 0));
            const bool ws = (lane & 15) == 0, lo = lane < 16;
            uint32_t pre[6][4];
            float s1 = 0.f, s2 = 0.f;
            {
                bool hx = wu == 7;
                int it = 0;
                const uint4* px = &g_scr.acc[layer][min(tid, 215) * ACC_STR];
                const int cq = tid / 54, r = tid - 54 * cq, k0 = min(160 * cq + 3 * r, DM - 1);
                const uint32_t w0 = sb + SM_XS + 4 * xpos(k0 >> 1), w1 = sb + SM_XS + 4 * xpos(min((k0 >> 1) + 1, DM / 2 - 1));
                const uint32_t e0 = w0 + 2 * (k0 & 1), e1 = (k0 & 1) ? w1 : w0 + 2, e2 = w1 + 2 * (k0 & 1);
                                auto sts16 = [](uint32_t a, uint32_t x, bool on) {
                    asm volatile("{\n.reg .pred p;\nsetp.ne.u32 p, %2, 0;\n@p st.shared.u16 [%0], %1;\n}" ::"r"(a), "h"((unsigned short)x), "r"((uint32_t)on) : "memory");
                };
                const bool on0 = tid < 216, on1 = on0 && r != 53;
                const float x0 = on0 ? f_(lds16(e0) << 16) : 0.f, x1 = on1 ? f_(lds16(e1) << 16) : 0.f, x2 = on1 ? f_(lds16(e2) << 16) : 0.f;
                auto take_x = [&](const uint4 v) {
                    if (__all_sync(0xffffffffu, v.w == DONE32)) {
                        hx = true;
                        const uint32_t a = pack2(f_(v.x), f_(v.y)), p = pack2(x0 + bf_lo(a), x1 + bf_hi(a)), q = pack2(x2 + bfr(f_(v.z)), 0.f);
                        sts16(e0, p, on0); sts16(e1, p >> 16, on1); sts16(e2, q, on1);
                        const float y0 = on0 ? bf_lo(p) : 0.f, y1 = on0 ? bf_hi(p) : 0.f, y2 = on0 ? bf_lo(q) : 0.f;
                        s1 = y0 + (y1 + y2); s2 = y0 * y0 + (y1 * y1 + y2 * y2);
                    }
                };
                auto try_x = [&]() { take_x(ld_pkt(px)); };
                while (!mbar_test(fbar, 0) && ++it < SPIN_CAP) { if (!hx) try_x(); }
                uint4 v0 = make_uint4(0u, 0u, 0u, 0u);
                if ((PRE1 & 4) && !hx) v0 = ld_pkt(px);
#pragma unroll
                for (int n = 0; n < 6; n++) ldsm4t(ag + (n % 3) * GI + (n / 3) * GK, pre[n]);
                if ((PRE1 & 1) && layer) {
#pragma unroll
                    for (int n = 6; n < 15; n++) ldsm4t(ag + (n % 3) * GI + (n / 3) * GK, kq[n - 6]);
                }
                if ((PRE1 & 4) && !hx) take_x(v0);
                PC(layer * 32 + 10);
                while (!hx && ++it < SPIN_CAP) try_x();
                PC(layer * 32 + 11);
            __syncthreads();
            PC(layer * 32 + 12);
            PROF_T(9 + layer * 16);
            float sv = lo ? s1 : s2, cc[3][4];
            if ((PRE1 & 1) && layer) gemv15r(cc, pre, kq, pm, pm2, sv, lo ? s2 : s1);
            else gemv15<GK>(cc, pre, [&](int i) { return ag + i * GI; }, pm, pm2, sv, lo ? s2 : s1);
#pragma unroll
            for (int i = 0; i < 3; i++) { sts32p(dg + 128 * i, cc[i][0] + cc[i][3], t & 2); sts32p(dg + 128 * i + 64, cc[i][1] + cc[i][2], t & 2); }
            if (ws) sts32(ds, sv);
            const uint32_t pg = opq(sb + SM_R + 8 * (24 * warp + (lane < 24 ? lane : 0))), st = opq(sb + SM_ST);
            uint4* const ph = opq(lane < 24 && lane % 6 == 0 ? &g_scr.ah[role * 8 + 4 * warp + lane / 6] : nullptr);
            PC(layer * 32 + 13);
            __syncthreads();
            PC(layer * 32 + 14);
            PROF_T(43 + layer * 16);
            if (wu < 2) {
                float mean, inv;
                ln_stats(st, mean, inv);
                float2 v[8];
#pragma unroll
                for (int w = 0; w < 8; w++) v[w] = lds2f(pg + w * 384);
                const float gx = ((v[0].x + v[1].x) + (v[2].x + v[3].x)) + ((v[4].x + v[5].x) + (v[6].x + v[7].x));
                const float gs = ((v[0].y + v[1].y) + (v[2].y + v[3].y)) + ((v[4].y + v[5].y) + (v[6].y + v[7].y));
                float ga = inv * (gx - mean * gs);
                if (role < NG / 2) { ga = bfr(ga); ga *= rcp(1.0f + ex2(-1.4426950408889634f * ga)); }
                const uint32_t wd = pack2(ga, __shfl_down_sync(0xffffffffu, ga, 1));
                const uint32_t wa = __shfl_down_sync(0xffffffffu, wd, 2), wb = __shfl_down_sync(0xffffffffu, wd, 4);
                if (ph) st_pkt(ph, wd, wa, wb, tag);
            }
            if (HOLD & 2) __syncthreads();
            }
            PROF_T(10 + layer * 16);
            PC(layer * 32 + 15);
        } else if (role < DN0 + NDN) {
            const int j = role - DN0;
            const int tid = opq(threadIdx.x), warp = tid >> 5, lane = tid & 31, g = lane >> 2, t = lane & 3, mat = lane >> 3, r8 = lane & 7;
            float xres = 0.f;
            uint32_t xr0 = 0, xr1 = 0;
            if (wu == 0) {
                const int col = 16 * j + (lane & 15), cc = col / 160, r = col - 160 * cc, e = r % 3;
                const uint4* px = &g_scr.acc[layer][(54 * cc + r / 3) * ACC_STR];
                const float x0 = __bfloat162float(reinterpret_cast<const __nv_bfloat16*>(xs32)[2 * xpos(col >> 1) + (col & 1)]);
                uint4 v;
                int it = 0;
                bool ld = DNTH && layer == 0;
                do {
                    v = ld_pkt(px);
                    if (ld && f_(__shfl_sync(0xffffffffu, v.w, 0)) >= (float)DNTH) { ld = false; if (lane == 0) load_ffn(maps, role, sb + SM_B, fbar); }
                } while (!__all_sync(0xffffffffu, v.w == DONE32) && ++it < SPIN_CAP);
                if (ld && lane == 0) load_ffn(maps, role, sb + SM_B, fbar);
                xres = x0 + bfr(f_(e == 0 ? v.x : (e == 1 ? v.y : v.z)));
                const int p4 = 4 * (lane & 3);
                xr0 = pack2(__shfl_sync(0xffffffffu, xres, p4), __shfl_sync(0xffffffffu, xres, p4 + 1));
                xr1 = pack2(__shfl_sync(0xffffffffu, xres, p4 + 2), __shfl_sync(0xffffffffu, xres, p4 + 3));
            }
            PC(layer * 32 + 17);
            PROF_T(9 + layer * 16);
            const uint32_t ad = fbase + (192 * warp + (mat >> 1) * 8 + r8) * 32 + (((mat & 1) ^ (r8 >> 2)) << 4);
            uint32_t* hs = reinterpret_cast<uint32_t*>(rr) + warp * 96;
            uint32_t pre[NPRE][4];
            {
                uint32_t pos[3];
#pragma unroll
                for (int i = 0; i < 3; i++) { const int w = 3 * lane + i; pos[i] = pin(sb + SM_R + 384 * warp + 4 * ((w & ~15) + 4 * (w & 3) + ((w >> 2) & 1) + ((w >> 2) & 2))); }
                uint4 v = make_uint4(0u, 0u, 0u, 0u), u = v;
                if (layer == 0) { v = ld_pkt(&g_scr.ah[tid]); u = ld_pkt(&g_scr.ah[256 + tid]); }
                mbar_wait(fbar, 0);
#pragma unroll
                for (int n = 0; n < NPRE; n++) ldsm4t(ad + n * 512, pre[n]);
                if ((PRE1 & 2) && layer) {
#pragma unroll
                    for (int n = NPRE; n < 12; n++) ldsm4t(ad + n * 512, kq[12 + n]);
                }
                PC(layer * 32 + 18);
                int it = 0;
                while (!__all_sync(0xffffffffu, v.w == tag && u.w == tag) && ++it < SPIN_CAP) { v = ld_pkt(&g_scr.ah[tid]); u = ld_pkt(&g_scr.ah[256 + tid]); }
                PC(layer * 32 + 19);
                sts32(pos[0], f_(bmul2(v.x, u.x))); sts32(pos[1], f_(bmul2(v.y, u.y))); sts32(pos[2], f_(bmul2(v.z, u.z)));
            __syncwarp();
            PROF_T(11 + layer * 16);
            PC(layer * 32 + 20);
            float ca[4] = {0.f, 0.f, 0.f, 0.f}, cb[4] = {0.f, 0.f, 0.f, 0.f};
            if ((PRE1 & 2) && layer) {
                float cc[4] = {0.f, 0.f, 0.f, 0.f}, cd[4] = {0.f, 0.f, 0.f, 0.f};
#pragma unroll
                for (int jj = 0; jj < 6; jj++) {
                    const uint4 hv = *reinterpret_cast<const uint4*>(hs + 16 * jj + 4 * t);
                    const uint32_t (&f0)[4] = 2 * jj < NPRE ? pre[2 * jj < NPRE ? 2 * jj : 0] : kq[12 + 2 * jj];
                    const uint32_t (&f1)[4] = 2 * jj + 1 < NPRE ? pre[2 * jj + 1 < NPRE ? 2 * jj + 1 : 0] : kq[13 + 2 * jj];
                    if (jj & 1) { mma16816(cc, f0[0], f0[1], f0[2], f0[3], hv.x, hv.y); mma16816(cd, f1[0], f1[1], f1[2], f1[3], hv.z, hv.w); }
                    else { mma16816(ca, f0[0], f0[1], f0[2], f0[3], hv.x, hv.y); mma16816(cb, f1[0], f1[1], f1[2], f1[3], hv.z, hv.w); }
                }
#pragma unroll
                for (int e = 0; e < 4; e++) { ca[e] += cc[e]; cb[e] += cd[e]; }
            } else {
#pragma unroll
                for (int jj = 0; jj < 6; jj++) {
                    const uint4 hv = *reinterpret_cast<const uint4*>(hs + 16 * jj + 4 * t);
                    uint32_t a[4];
                    if (2 * jj < NPRE) { a[0] = pre[2 * jj][0]; a[1] = pre[2 * jj][1]; a[2] = pre[2 * jj][2]; a[3] = pre[2 * jj][3]; }
                    else ldsm4t(ad + 2 * jj * 512, a);
                    mma16816(ca, a[0], a[1], a[2], a[3], hv.x, hv.y);
                    if (2 * jj + 1 < NPRE) { a[0] = pre[2 * jj + 1][0]; a[1] = pre[2 * jj + 1][1]; a[2] = pre[2 * jj + 1][2]; a[3] = pre[2 * jj + 1][3]; }
                    else ldsm4t(ad + (2 * jj + 1) * 512, a);
                    mma16816(cb, a[0], a[1], a[2], a[3], hv.z, hv.w);
                }
            }
            if (t == 0) { rr[768 + warp * 16 + g] = ca[0] + cb[0]; rr[768 + warp * 16 + 8 + g] = ca[2] + cb[2]; }
            const uint32_t pd = opq(sb + SM_R + 3072 + 16 * (lane & 3));
            uint4* const py = opq(&g_scr.ay[j * 4 + lane]);
            uint2* const po = opq(reinterpret_cast<uint2*>(out + 16 * j) + lane);
            PC(layer * 32 + 21);
            __syncthreads();
            PC(layer * 32 + 22);
            if (wu == 0) {
                float4 p[8];
#pragma unroll
                for (int w = 0; w < 8; w++) p[w] = lds4f(pd + 64 * w);
                const uint32_t y0 = pack2(((p[0].x + p[1].x) + (p[2].x + p[3].x)) + ((p[4].x + p[5].x) + (p[6].x + p[7].x)),
                                          ((p[0].y + p[1].y) + (p[2].y + p[3].y)) + ((p[4].y + p[5].y) + (p[6].y + p[7].y)));
                const uint32_t y1 = pack2(((p[0].z + p[1].z) + (p[2].z + p[3].z)) + ((p[4].z + p[5].z) + (p[6].z + p[7].z)),
                                          ((p[0].w + p[1].w) + (p[2].w + p[3].w)) + ((p[4].w + p[5].w) + (p[6].w + p[7].w)));
                uint32_t wd, wn;
                asm("add.rn.bf16x2 %0, %1, %2;" : "=r"(wd) : "r"(xr0), "r"(y0));
                asm("add.rn.bf16x2 %0, %1, %2;" : "=r"(wn) : "r"(xr1), "r"(y1));
                asm volatile("{\n.reg .pred p;\nsetp.ne.u32 p, %3, 0;\n@p st.global.v2.u32 [%0], {%1,%2};\n}" ::"l"(po), "r"(wd), "r"(wn), "r"((uint32_t)(layer && tid < 4)) : "memory");
                st_pktp(py, wd, wn, 0, tag, tid < 4);
            }
            if (HOLD & 1) __syncthreads();
            }
            PROF_T(12 + layer * 16);
            PC(layer * 32 + 23);
        }
    }
}

typedef CUresult (*EncodeFn)(CUtensorMap*, CUtensorMapDataType, cuuint32_t, void*, const cuuint64_t*, const cuuint64_t*, const cuuint32_t*,
                             const cuuint32_t*, CUtensorMapInterleave, CUtensorMapSwizzle, CUtensorMapL2promotion, CUtensorMapFloatOOBfill);

void make_map(EncodeFn enc, CUtensorMap* m, const void* base, int rank, uint64_t d0, uint64_t d1, uint64_t d2, uint64_t s1, uint64_t s2,
              uint32_t b0, uint32_t b1, uint32_t b2, CUtensorMapSwizzle sw, CUtensorMapL2promotion pr = CU_TENSOR_MAP_L2_PROMOTION_NONE) {
    cuuint64_t dims[3] = {d0, d1, d2};
    cuuint64_t strides[2] = {s1, s2};
    cuuint32_t box[3] = {b0, b1, b2};
    cuuint32_t es[3] = {1, 1, 1};
    enc(m, CU_TENSOR_MAP_DATA_TYPE_BFLOAT16, rank, const_cast<void*>(base), dims, strides, box, es, CU_TENSOR_MAP_INTERLEAVE_NONE, sw,
        pr, CU_TENSOR_MAP_FLOAT_OOB_FILL_NONE);
}

}

extern "C" void kernel_launch(void* const* d_in, const int* in_sizes, int n_in, void* d_out, int out_size) {
    (void)in_sizes; (void)n_in; (void)out_size;
    static EncodeFn enc = nullptr;
    if (!enc) {
        void* fn = nullptr;
        cudaDriverEntryPointQueryResult qr;
        cudaGetDriverEntryPoint("cuTensorMapEncodeTiled", &fn, cudaEnableDefault, &qr);
        enc = reinterpret_cast<EncodeFn>(fn);
        cudaFuncSetAttribute(decode_kernel, cudaFuncAttributeMaxDynamicSharedMemorySize, SM_TOTAL);
    }
    Maps maps;
    make_map(enc, &maps.k, d_in[1], 2, 64, (uint64_t)NH * SK * 3, 1, 128, 0, 64, 48, 1, CU_TENSOR_MAP_SWIZZLE_128B);
    make_map(enc, &maps.v, d_in[2], 2, 64, (uint64_t)NH * SK * 3, 1, 128, 0, 64, 48, 1, CU_TENSOR_MAP_SWIZZLE_128B);
    make_map(enc, &maps.wq, d_in[3], 3, 64, DM, NH * DH / 64, NH * DH * 2, 128, 64, 160, 3, CU_TENSOR_MAP_SWIZZLE_128B);
    make_map(enc, &maps.wo, d_in[4], 3, 32, DM / 32, NH * DH, 64, DM * 2, 32, 5, 32, CU_TENSOR_MAP_SWIZZLE_64B);
    make_map(enc, &maps.vr, (const char*)d_in[2] + 512, 2, 128, (uint64_t)NH * SK / 2, 1, 768, 0, 128, 2, 1, CU_TENSOR_MAP_SWIZZLE_NONE);
    constexpr int GW = 48;
    make_map(enc, &maps.w1, d_in[6], 3, FF, 160, 4, FF * 2, 160 * FF * 2, GW, 160, 4, CU_TENSOR_MAP_SWIZZLE_NONE, FFN_PROMO);
    make_map(enc, &maps.w3, d_in[7], 3, FF, 160, 4, FF * 2, 160 * FF * 2, GW, 160, 4, CU_TENSOR_MAP_SWIZZLE_NONE, FFN_PROMO);
    make_map(enc, &maps.w2, d_in[8], 3, DM, 256, 6, DM * 2, 256 * DM * 2, 16, 256, 6, CU_TENSOR_MAP_SWIZZLE_32B, FFN_PROMO);
    maps.vp = d_in[2];
    maps.kp = d_in[1];
    maps.zero = 0;
    decode_kernel<<<NCTA, NT, SM_TOTAL, cudaStreamPerThread>>>(maps, (const __nv_bfloat16*)d_in[0], (__nv_bfloat16*)d_out);
}
```

```cpp
#include <cuda_runtime.h>
#include <cuda_bf16.h>
#include <cuda.h>
#include <stdint.h>
#include <math.h>

namespace {

constexpr int DM = 640;
constexpr int NH = 32;
constexpr int DH = 192;
constexpr int SK = 32768;
constexpr int WIN = 4096;
constexpr int FF = 1536;
constexpr int NCTA = 128;
constexpr int NT = 256;
constexpr int TILE = 6144;
constexpr int NG = 64;
constexpr int DN0 = 64;
constexpr int NDN = 40;

constexpr int SM_RING = 0;
constexpr int SM_B = 8 * 2 * TILE;
constexpr int SM_Q = SM_B + 61440;
__host__ __device__ constexpr int c_slot(int w) { return w < 2 ? 4096 + 10240 * w : 12288 + 6144 * w; }
__host__ __device__ constexpr int v1_pos(int n) { return 10240 * (n >> 3) + 512 * (n & 7); }
constexpr int SM_XS = SM_Q + 61440;
constexpr int SM_R = SM_XS + 1280;
constexpr int SM_ST = SM_R + 4096;
constexpr int SM_QS = SM_R + 6272;
constexpr int SM_OS = SM_QS + 384;
constexpr int SM_BAR = SM_OS + 384;
constexpr int SM_XBAR = SM_BAR + 24 * 8;
constexpr int SM_MISC = SM_XBAR + 8 * 8;
constexpr int SM_ONE = SM_MISC + 16;
constexpr int SM_ZERO = SM_ONE + 160;
constexpr int XCAP = 48;
constexpr int XSTR = 16 + 4 * XCAP;
constexpr int SM_XL = SM_ZERO + 160;
constexpr int SM_TOTAL = SM_XL + 8 * XSTR;
static_assert(SM_TOTAL <= 232448, "shared memory");

constexpr unsigned long long POL_EF = 0x12F0000000000000ull;
constexpr unsigned long long POL_EN = 0x16F0000000000000ull;

#define RT_MASK 0xF2E0u
#define RT_MASK2 0xEAE0u
#define WO_AT1 5
#define FFN_PROMO CU_TENSOR_MAP_L2_PROMOTION_NONE
#define FFN_POL POL_EF
#define HAS_FFN (__float_as_uint(misc[1]) < DN0 + NDN)
#define ACC_STR 1
#define NPRE 6

#define STAG 200
#define L1R 3
#define PRE1 13
#define HOLD 2
#define DNTH 23
constexpr int V0_AT = 8;
constexpr unsigned long long SEQ1 = 0x2765431076543210ull;
constexpr uint32_t IN_S1 = 0xAA49, IN_S0 = 0x124, PARITY1 = 0x6638, PARITY2 = 0xCE;
#define KEEP4 1
constexpr int NQ = 48;
constexpr int SPIN_CAP = 1 << 19;
constexpr uint32_t ONES = 0x3F803F80u;

struct alignas(1024) Scratch {
    uint4 hx[NCTA * 48];
    uint4 pad0[32 * 5 * 32 + 160];
    uint4 acc[2][216 * 8];
    uint4 ay[160];
    uint4 ah[NG * 8];
    uint2 mx[NH * 32];
    uint32_t ticket[32];
    uint32_t pad1[32];
};
__device__ Scratch g_scr;
#define PROF_T(i)
#define PROF_X(i)
#define PC(i)

__device__ __forceinline__ uint32_t smem_u32(const void* p) { return (uint32_t)__cvta_generic_to_shared(p); }
__device__ __forceinline__ void mbar_init(uint32_t bar, uint32_t cnt) {
    asm volatile("mbarrier.init.shared::cta.b64 [%0], %1;" ::"r"(bar), "r"(cnt) : "memory");
}
__device__ __forceinline__ void mbar_expect_tx(uint32_t bar, uint32_t bytes) {
    asm volatile("mbarrier.arrive.expect_tx.shared::cta.b64 _, [%0], %1;" ::"r"(bar), "r"(bytes) : "memory");
}
__device__ __forceinline__ bool mbar_test(uint32_t bar, uint32_t parity) {
    uint32_t done;
    asm volatile("{\n.reg .pred p;\nmbarrier.try_wait.parity.shared::cta.b64 p, [%1], %2;\nselp.u32 %0, 1, 0, p;\n}"
                 : "=r"(done) : "r"(bar), "r"(parity) : "memory");
    return done;
}
__device__ __forceinline__ void mbar_wait(uint32_t bar, uint32_t parity) {
    int it = 0;
    while (!mbar_test(bar, parity) && ++it < SPIN_CAP) {}
}
__device__ __forceinline__ void tma2d(uint32_t dst, const CUtensorMap* map, int c0, int c1, uint32_t bar, unsigned long long pol) {
    asm volatile("cp.async.bulk.tensor.2d.shared::cluster.global.mbarrier::complete_tx::bytes.L2::cache_hint [%0], [%1, {%3, %4}], [%2], %5;"
                 ::"r"(dst), "l"(map), "r"(bar), "r"(c0), "r"(c1), "l"(pol) : "memory");
}
__device__ __forceinline__ void tma3d(uint32_t dst, const CUtensorMap* map, int c0, int c1, int c2, uint32_t bar, unsigned long long pol) {
    asm volatile("cp.async.bulk.tensor.3d.shared::cluster.global.mbarrier::complete_tx::bytes.L2::cache_hint [%0], [%1, {%3, %4, %5}], [%2], %6;"
                 ::"r"(dst), "l"(map), "r"(bar), "r"(c0), "r"(c1), "r"(c2), "l"(pol) : "memory");
}
__device__ __forceinline__ void tile_load(uint32_t dst, const CUtensorMap* map, int row, uint32_t bar, uint32_t dep, uint32_t zero) {
    asm volatile("{\n.reg .pred p;\n.reg .b32 n;\nmad.lo.u32 n, %5, %6, 6144;\nelect.sync _|p, 0xffffffff;\n"
                 "@p mbarrier.arrive.expect_tx.shared::cta.b64 _, [%2], n;\n"
                 "@p cp.async.bulk.tensor.2d.shared::cluster.global.mbarrier::complete_tx::bytes.L2::cache_hint [%0], [%1, {0, %3}], [%2], %4;\n}"
                 ::"r"(dst), "l"(map), "r"(bar), "r"(row), "l"(POL_EF), "r"(dep), "r"(zero) : "memory");
}
__device__ __forceinline__ void tile_keep(const CUtensorMap* map, int row) {
    asm volatile("{\n.reg .pred p;\nelect.sync _|p, 0xffffffff;\n"
                 "@p cp.async.bulk.prefetch.tensor.2d.L2.global.L2::cache_hint [%0, {0, %1}], %2;\n}"
                 ::"l"(map), "r"(row), "l"(POL_EN) : "memory");
}
__device__ __forceinline__ void tile_load_l1(uint32_t dst, const void* base, int row, uint32_t bar, int lane) {
    const char* g = static_cast<const char*>(base) + (size_t)row * 128 + lane * 16;
    const uint32_t s0 = dst + (lane >> 3) * 128 + (((lane & 7) ^ (lane >> 3)) << 4), s1 = s0 ^ 64;
#pragma unroll
    for (int k = 0; k < 12; k++)
        asm volatile("cp.async.ca.shared.global.L2::cache_hint [%0], [%1], 16, %2;" ::"r"(((k & 1) ? s1 : s0) + k * 512), "l"(g + k * 512), "l"(POL_EF) : "memory");
    asm volatile("cp.async.mbarrier.arrive.shared::cta.b64 [%0];" ::"r"(bar) : "memory");
    __syncwarp();
    if (lane == 0) asm volatile("mbarrier.arrive.shared::cta.b64 _, [%0];" ::"r"(bar) : "memory");
}
__device__ __forceinline__ bool elect_one() {
    uint32_t p;
    asm volatile("{\n.reg .pred p;\nelect.sync _|p, 0xffffffff;\nselp.u32 %0, 1, 0, p;\n}" : "=r"(p));
    return p;
}
__device__ __forceinline__ void lds128(uint32_t addr, uint32_t& a, uint32_t& b, uint32_t& c, uint32_t& d) {
    asm volatile("ld.shared.v4.u32 {%0,%1,%2,%3}, [%4];" : "=r"(a), "=r"(b), "=r"(c), "=r"(d) : "r"(addr) : "memory");
}
__device__ __forceinline__ void lds128p(uint32_t addr, uint32_t on, uint32_t& a, uint32_t& b, uint32_t& c, uint32_t& d) {
    asm volatile("{\n.reg .pred p;\nsetp.ne.u32 p, %5, 0;\n@p ld.shared.v4.u32 {%0,%1,%2,%3}, [%4];\n}" : "+r"(a), "+r"(b), "+r"(c), "+r"(d) : "r"(addr), "r"(on) : "memory");
}
__device__ __forceinline__ void lds64(uint32_t addr, uint32_t& a, uint32_t& b) {
    asm volatile("ld.shared.v2.u32 {%0,%1}, [%2];" : "=r"(a), "=r"(b) : "r"(addr) : "memory");
}
__device__ __forceinline__ void ldsm4t(uint32_t addr, uint32_t (&a)[4]) {
    asm volatile("ldmatrix.sync.aligned.m8n8.x4.trans.shared.b16 {%0,%1,%2,%3}, [%4];" : "=r"(a[0]), "=r"(a[1]), "=r"(a[2]), "=r"(a[3]) : "r"(addr) : "memory");
}
__device__ __forceinline__ void mma16816(float (&c)[4], uint32_t a0, uint32_t a1, uint32_t a2, uint32_t a3, uint32_t b0, uint32_t b1) {
    asm("mma.sync.aligned.m16n8k16.row.col.f32.bf16.bf16.f32 {%0,%1,%2,%3}, {%4,%5,%6,%7}, {%8,%9}, {%0,%1,%2,%3};"
        : "+f"(c[0]), "+f"(c[1]), "+f"(c[2]), "+f"(c[3]) : "r"(a0), "r"(a1), "r"(a2), "r"(a3), "r"(b0), "r"(b1));
}
__device__ __forceinline__ void mma16816v(float (&c)[4], uint32_t a0, uint32_t a1, uint32_t a2, uint32_t a3, uint32_t b0, uint32_t b1) {
    asm volatile("mma.sync.aligned.m16n8k16.row.col.f32.bf16.bf16.f32 {%0,%1,%2,%3}, {%4,%5,%6,%7}, {%8,%9}, {%0,%1,%2,%3};"
        : "+f"(c[0]), "+f"(c[1]), "+f"(c[2]), "+f"(c[3]) : "r"(a0), "r"(a1), "r"(a2), "r"(a3), "r"(b0), "r"(b1));
}
__device__ __forceinline__ int xpos(int w) {
    const int seg = w / 40, r = w - 40 * seg;
    return 40 * seg + (r < 32 ? (r & 16) + 4 * (r & 3) + ((r >> 2) & 3) : 32 + 2 * (r & 3) + ((r >> 2) & 1));
}
#define NA_LD ""
#define NA_ST ""
__device__ __forceinline__ void st_pkt(uint4* p, uint32_t a, uint32_t b, uint32_t c, uint32_t d) {
    asm volatile("{\n.reg .b128 t;\n.reg .b64 lo, hi;\nmov.b64 lo, {%1,%2};\nmov.b64 hi, {%3,%4};\nmov.b128 t, {lo,hi};\nst.relaxed.gpu.global" NA_ST ".b128 [%0], t;\n}"
                 ::"l"(p), "r"(a), "r"(b), "r"(c), "r"(d) : "memory");
}
__device__ __forceinline__ void red_pkt(uint4* p, float a, float b, float c) {
    asm volatile("red.relaxed.gpu.global.add.v4.f32 [%0], {%1,%2,%3,%4};" ::"l"(p), "f"(a), "f"(b), "f"(c), "f"(1.0f) : "memory");
}
__device__ __forceinline__ void st_pktp(uint4* p, uint32_t a, uint32_t b, uint32_t c, uint32_t d, bool on) {
    asm volatile("{\n.reg .pred p;\n.reg .b128 t;\n.reg .b64 lo, hi;\nsetp.ne.u32 p, %5, 0;\nmov.b64 lo, {%1,%2};\nmov.b64 hi, {%3,%4};\nmov.b128 t, {lo,hi};\n"
                 "@p st.relaxed.gpu.global.b128 [%0], t;\n}" ::"l"(p), "r"(a), "r"(b), "r"(c), "r"(d), "r"((uint32_t)on) : "memory");
}
__device__ __forceinline__ void st_pktfp(uint4* p, float a, float b, float c, float d, uint32_t bit, bool on) {
    st_pktp(p, __float_as_uint(a), __float_as_uint(b), __float_as_uint(c), (__float_as_uint(d) & ~1u) | bit, on);
}
__device__ __forceinline__ uint4 ld_pkt(const uint4* p) {
    uint4 v;
    asm volatile("{\n.reg .b128 t;\n.reg .b64 lo, hi;\nld.relaxed.gpu.global" NA_LD ".b128 t, [%4];\nmov.b128 {lo,hi}, t;\nmov.b64 {%0,%1}, lo;\nmov.b64 {%2,%3}, hi;\n}"
                 : "=r"(v.x), "=r"(v.y), "=r"(v.z), "=r"(v.w) : "l"(p) : "memory");
    return v;
}
__device__ __forceinline__ bool all_odd(uint32_t a, uint32_t b, uint32_t c, uint32_t d) {
    uint32_t r;
    asm volatile("{\n.reg .pred p, q, t;\n.reg .b32 x;\nsetp.eq.b32 t, 0, 0;\nlop3.b32 x, %1, %2, %3, 0x80;\nlop3.and.b32 _|p, x, %4, 1, 0x80, t;\n"
                 "vote.sync.all.pred q, p, 0xffffffff;\nselp.u32 %0, 1, 0, q;\n}" : "=r"(r) : "r"(a), "r"(b), "r"(c), "r"(d));
    return r;
}
__device__ __forceinline__ bool any_odd(uint32_t a, uint32_t b, uint32_t c) {
    uint32_t r;
    asm volatile("{\n.reg .pred p, q, t;\n.reg .b32 x;\nsetp.eq.b32 t, 0, 0;\nlop3.b32 x, %1, %2, %3, 0xFE;\nlop3.and.b32 _|p, x, 1, 0, 0xC0, t;\n"
                 "vote.sync.any.pred q, p, 0xffffffff;\nselp.u32 %0, 1, 0, q;\n}" : "=r"(r) : "r"(a), "r"(b), "r"(c));
    return r;
}
__device__ __forceinline__ bool any_ne(uint32_t a, uint32_t b, uint32_t c) {
    uint32_t r;
    asm volatile("{\n.reg .pred p, q, t;\nsetp.eq.b32 t, 0, 0;\nlop3.and.b32 _|p, %1, %2, %3, 0x7E, t;\n"
                 "vote.sync.any.pred q, p, 0xffffffff;\nselp.u32 %0, 1, 0, q;\n}" : "=r"(r) : "r"(a), "r"(b), "r"(c));
    return r;
}
__device__ __forceinline__ uint2 ld_pkt2(const uint2* p) {
    unsigned long long v;
    asm volatile("ld.relaxed.gpu.global" NA_LD ".b64 %0, [%1];" : "=l"(v) : "l"(p) : "memory");
    return make_uint2((uint32_t)v, (uint32_t)(v >> 32));
}
__device__ __forceinline__ void st_pkt2(uint2* p, uint32_t a, uint32_t b) {
    asm volatile("st.relaxed.gpu.global" NA_ST ".b64 [%0], %1;" ::"l"(p), "l"((unsigned long long)a | ((unsigned long long)b << 32)) : "memory");
}
__device__ __forceinline__ float ex2(float x) { float y; asm("ex2.approx.ftz.f32 %0, %1;" : "=f"(y) : "f"(x)); return y; }
__device__ __forceinline__ float rcp(float x) { float y; asm("rcp.approx.ftz.f32 %0, %1;" : "=f"(y) : "f"(x)); return y; }
__device__ __forceinline__ uint32_t pack2(float lo, float hi) {
    uint32_t r; asm("cvt.rn.bf16x2.f32 %0, %1, %2;" : "=r"(r) : "f"(hi), "f"(lo)); return r;
}
__device__ __forceinline__ float bf_lo(uint32_t w) { return __uint_as_float(w << 16); }
__device__ __forceinline__ float bf_hi(uint32_t w) { return __uint_as_float(w & 0xffff0000u); }
__device__ __forceinline__ float bfr(float x) { return bf_lo(pack2(x, 0.f)); }
__device__ __forceinline__ float f_(uint32_t u) { return __uint_as_float(u); }

template <int SK, typename AddrF>
__device__ __forceinline__ void gemv15(float (&cc)[3][4], uint32_t (&pre)[6][4], AddrF ad, uint32_t px, uint32_t px2, float& sv, float so) {
    uint32_t x0[4], x1[4], a[3][4];
    asm volatile("ld.shared.v4.u32 {%0,%1,%2,%3}, [%20];\nld.shared.v4.u32 {%4,%5,%6,%7}, [%20+64];\n"
                 "ldmatrix.sync.aligned.m8n8.x4.trans.shared.b16 {%8,%9,%10,%11}, [%21];\n"
                 "ldmatrix.sync.aligned.m8n8.x4.trans.shared.b16 {%12,%13,%14,%15}, [%22];\n"
                 "ldmatrix.sync.aligned.m8n8.x4.trans.shared.b16 {%16,%17,%18,%19}, [%23];\nbar.warp.sync 0xffffffff;"
                 : "=r"(x0[0]), "=r"(x0[1]), "=r"(x0[2]), "=r"(x0[3]), "=r"(x1[0]), "=r"(x1[1]), "=r"(x1[2]), "=r"(x1[3]),
                   "=r"(a[0][0]), "=r"(a[0][1]), "=r"(a[0][2]), "=r"(a[0][3]), "=r"(a[1][0]), "=r"(a[1][1]), "=r"(a[1][2]), "=r"(a[1][3]),
                   "=r"(a[2][0]), "=r"(a[2][1]), "=r"(a[2][2]), "=r"(a[2][3])
                 : "r"(px), "r"(ad(0) + 2 * SK), "r"(ad(1) + 2 * SK), "r"(ad(2) + 2 * SK) : "memory");
    __syncwarp();
    sv += __shfl_xor_sync(0xffffffffu, so, 16);
#pragma unroll
    for (int i = 0; i < 3; i++) {
        cc[i][0] = cc[i][1] = cc[i][2] = cc[i][3] = 0.f;
        mma16816v(cc[i], pre[i][0], pre[i][1], pre[i][2], pre[i][3], x0[0], x0[1]);
    }
    sv += __shfl_xor_sync(0xffffffffu, sv, 8);
#pragma unroll
    for (int i = 0; i < 3; i++) {
        mma16816v(cc[i], pre[3 + i][0], pre[3 + i][1], pre[3 + i][2], pre[3 + i][3], x0[2], x0[3]);
        ldsm4t(ad(i) + 3 * SK, pre[i]);
    }
    lds64(px2, x0[0], x0[1]);
    __syncwarp();
    sv += __shfl_xor_sync(0xffffffffu, sv, 4);
#pragma unroll
    for (int i = 0; i < 3; i++) {
        mma16816v(cc[i], a[i][0], a[i][1], a[i][2], a[i][3], x1[0], x1[1]);
        ldsm4t(ad(i) + 4 * SK, pre[3 + i]);
    }
    __syncwarp();
    sv += __shfl_xor_sync(0xffffffffu, sv, 2);
#pragma unroll
    for (int i = 0; i < 3; i++) mma16816v(cc[i], pre[i][0], pre[i][1], pre[i][2], pre[i][3], x1[2], x1[3]);
    sv += __shfl_xor_sync(0xffffffffu, sv, 1);
#pragma unroll
    for (int i = 0; i < 3; i++) mma16816v(cc[i], pre[3 + i][0], pre[3 + i][1], pre[3 + i][2], pre[3 + i][3], x0[0], x0[1]);
}
__device__ __forceinline__ void gemv15r(float (&cc)[3][4], const uint32_t (&pre)[6][4], const uint32_t (&ext)[NQ][4], uint32_t px, uint32_t px2, float& sv, float so) {
    uint32_t x0[4], x1[4], x2[2];
    float cd[3][4];
    lds128(px, x0[0], x0[1], x0[2], x0[3]);
    lds128(px + 64, x1[0], x1[1], x1[2], x1[3]);
    lds64(px2, x2[0], x2[1]);
    sv += __shfl_xor_sync(0xffffffffu, so, 16);
#pragma unroll
    for (int i = 0; i < 3; i++) {
        cc[i][0] = cc[i][1] = cc[i][2] = cc[i][3] = cd[i][0] = cd[i][1] = cd[i][2] = cd[i][3] = 0.f;
        mma16816v(cc[i], pre[i][0], pre[i][1], pre[i][2], pre[i][3], x0[0], x0[1]);
        mma16816v(cd[i], pre[3 + i][0], pre[3 + i][1], pre[3 + i][2], pre[3 + i][3], x0[2], x0[3]);
    }
    sv += __shfl_xor_sync(0xffffffffu, sv, 8);
#pragma unroll
    for (int i = 0; i < 3; i++) {
        mma16816v(cc[i], ext[i][0], ext[i][1], ext[i][2], ext[i][3], x1[0], x1[1]);
        mma16816v(cd[i], ext[3 + i][0], ext[3 + i][1], ext[3 + i][2], ext[3 + i][3], x1[2], x1[3]);
    }
    sv += __shfl_xor_sync(0xffffffffu, sv, 4);
#pragma unroll
    for (int i = 0; i < 3; i++) mma16816v(cc[i], ext[6 + i][0], ext[6 + i][1], ext[6 + i][2], ext[6 + i][3], x2[0], x2[1]);
    sv += __shfl_xor_sync(0xffffffffu, sv, 2);
    sv += __shfl_xor_sync(0xffffffffu, sv, 1);
#pragma unroll
    for (int i = 0; i < 3; i++) { cc[i][0] += cd[i][0]; cc[i][1] += cd[i][1]; cc[i][2] += cd[i][2]; cc[i][3] += cd[i][3]; }
}

__device__ __forceinline__ float warp_max(float x) {
    int i = __float_as_int(x);
    i = __reduce_max_sync(0xffffffffu, i ^ ((i >> 31) & 0x7fffffff));
    return __int_as_float(i ^ ((i >> 31) & 0x7fffffff));
}
__device__ __forceinline__ void idle(uint32_t clk) {
    uint32_t t0, t;
    asm volatile("mov.u32 %0, %%clock;" : "=r"(t0) :: "memory");
    do asm volatile("mov.u32 %0, %%clock;" : "=r"(t) :: "memory"); while (t - t0 < clk);
}
__device__ __forceinline__ uint32_t now_ns() { uint32_t t; asm volatile("mov.u32 %0, %%globaltimer_lo;" : "=r"(t)); return t; }
__device__ __forceinline__ int opq(int x) { asm volatile("" : "+r"(x)); return x; }
__device__ __forceinline__ uint32_t opq(uint32_t x) { asm volatile("" : "+r"(x)); return x; }
__device__ __forceinline__ uint32_t pin(uint32_t x) { return __shfl_sync(0xffffffffu, x, threadIdx.x & 31); }
template <typename T> __device__ __forceinline__ T* pin(T* p) {
    const unsigned long long v = (unsigned long long)p;
    return (T*)((unsigned long long)pin((uint32_t)v) | (unsigned long long)pin((uint32_t)(v >> 32)) << 32);
}
template <typename T> __device__ __forceinline__ T* opq(T* p) { asm volatile("" : "+l"(p)); return p; }
__device__ __forceinline__ float4 lds4f(uint32_t a) { float4 v; asm volatile("ld.shared.v4.f32 {%0,%1,%2,%3}, [%4];" : "=f"(v.x), "=f"(v.y), "=f"(v.z), "=f"(v.w) : "r"(a) : "memory"); return v; }
__device__ __forceinline__ float2 lds2f(uint32_t a) { float2 v; asm volatile("ld.shared.v2.f32 {%0,%1}, [%2];" : "=f"(v.x), "=f"(v.y) : "r"(a) : "memory"); return v; }
__device__ __forceinline__ void ln_stats(uint32_t st, float& mean, float& inv) {
    const float4 a = lds4f(st), b = lds4f(st + 16), c = lds4f(st + 32), d = lds4f(st + 48);
    const float s2 = ((a.x + a.z) + (b.x + b.z)) + ((c.x + c.z) + (d.x + d.z));
    const float md = (((a.y + a.w) + (b.y + b.w)) + ((c.y + c.w) + (d.y + d.w))) * (1.0f / DM);
    const float var = fmaxf(s2 * (1.0f / DM) - md * md, 0.f);
    mean = bfr(md);
    asm("rsqrt.approx.ftz.f32 %0, %1;" : "=f"(inv) : "f"(var + 1e-5f));
}
__device__ __forceinline__ void sts32(uint32_t a, float v) { asm volatile("st.shared.f32 [%0], %1;" ::"r"(a), "f"(v) : "memory"); }
__device__ __forceinline__ void sts32p(uint32_t a, float v, uint32_t off) {
    asm volatile("{\n.reg .pred p;\nsetp.eq.u32 p, %2, 0;\n@p st.shared.f32 [%0], %1;\n}" ::"r"(a), "f"(v), "r"(off) : "memory");
}
__device__ __forceinline__ void sts128p(uint32_t a, float x, float y, float z, float w, uint32_t off) {
    asm volatile("{\n.reg .pred p;\nsetp.eq.u32 p, %5, 0;\n@p st.shared.v4.f32 [%0], {%1,%2,%3,%4};\n}" ::"r"(a), "f"(x), "f"(y), "f"(z), "f"(w), "r"(off) : "memory");
}
__device__ __forceinline__ void sts64(uint32_t a, float v, float w) { asm volatile("st.shared.v2.f32 [%0], {%1,%2};" ::"r"(a), "f"(v), "f"(w) : "memory"); }

__device__ __forceinline__ uint32_t prmt(uint32_t a, uint32_t b, uint32_t s) { uint32_t r; asm("prmt.b32 %0, %1, %2, %3;" : "=r"(r) : "r"(a), "r"(b), "r"(s)); return r; }
__device__ __forceinline__ uint32_t bmul2(uint32_t a, uint32_t b) { uint32_t r; asm("mul.rn.bf16x2 %0, %1, %2;" : "=r"(r) : "r"(a), "r"(b)); return r; }
__device__ __forceinline__ void sts128(uint32_t addr, uint32_t a, uint32_t b, uint32_t c, uint32_t d) {
    asm volatile("st.shared.v4.u32 [%0], {%1,%2,%3,%4};" ::"r"(addr), "r"(a), "r"(b), "r"(c), "r"(d) : "memory");
}
__device__ __forceinline__ uint4 ldg128(const uint4* p) {
    uint4 v;
    asm volatile("ld.volatile.global.v4.u32 {%0,%1,%2,%3}, [%4];" : "=r"(v.x), "=r"(v.y), "=r"(v.z), "=r"(v.w) : "l"(p) : "memory");
    return v;
}
__device__ __forceinline__ uint32_t lds32(uint32_t a) { uint32_t v; asm volatile("ld.shared.u32 %0, [%1];" : "=r"(v) : "r"(a) : "memory"); return v; }
__device__ __forceinline__ uint32_t lds16(uint32_t a) { unsigned short v; asm volatile("ld.shared.u16 %0, [%1];" : "=h"(v) : "r"(a) : "memory"); return v; }
__device__ __forceinline__ void unpack8(uint32_t la, uint32_t lb, uint32_t c, uint32_t (&w)[4]) {
    const uint32_t ha = c & 0x87878787u, hb = __funnelshift_l(c, c, 4) & 0x87878787u;
    w[0] = prmt(la, ha, 0x5140); w[1] = prmt(la, ha, 0x7362); w[2] = prmt(lb, hb, 0x5140); w[3] = prmt(lb, hb, 0x7362);
}
__device__ __forceinline__ uint32_t bdiff2(uint32_t y, uint32_t inv, uint32_t x) {
    uint32_t r;
    asm("{\n.reg .b32 n;\nneg.bf16x2 n, %3;\nfma.rn.bf16x2 %0, %1, %2, n;\n}" : "=r"(r) : "r"(y), "r"(inv), "r"(x));
    return r;
}
__device__ __forceinline__ uint32_t pack_scale(uint32_t tile, int lane, uint32_t inv_addr) {
    uint32_t m = 0;
#pragma unroll 1
    for (int k = 0; k < 12; k++) {
        uint32_t a, b, c, d;
        lds128(tile + k * 512 + lane * 16, a, b, c, d);
        asm("max.xorsign.abs.bf16x2 %0, %0, %1;" : "+r"(a) : "r"(b));
        asm("max.xorsign.abs.bf16x2 %0, %0, %1;" : "+r"(c) : "r"(d));
        asm("max.xorsign.abs.bf16x2 %0, %0, %1;" : "+r"(a) : "r"(c));
        asm("max.xorsign.abs.bf16x2 %0, %0, %1;" : "+r"(m) : "r"(a));
    }
    m = __reduce_max_sync(0xffffffffu, max(m & 0x7fffu, (m >> 16) & 0x7fffu));
    const uint32_t inv = (112u + min((m + 0x28u) >> 7, 141u)) * 0x00800080u;
    if (lane == 0) asm volatile("st.shared.u32 [%0], %1;" ::"r"(inv_addr), "r"(inv) : "memory");
    return inv;
}

#define K_OFF(i) ((uint32_t)((3 * ((g >> 1) + 4 * (g & 1)) + ((i) >> 1)) * 128 + ((t ^ ((3 * ((g >> 1) + 4 * (g & 1)) + ((i) >> 1)) & 7) ^ (((i) & 1) << 2)) << 4)))
#define V_OFF(i) ((uint32_t)((6 * t + (i)) * 128 + ((g ^ ((6 * t + (i)) & 7)) << 4)))
template <bool ISV, typename DST>
__device__ __forceinline__ void pack_tile(uint32_t tile, int tau, int nm, uint32_t inv, uint32_t xl, int lane, DST dst) {
    const int g = lane >> 2, t = lane & 3;
    const uint32_t scl = 254u * 0x00800080u - inv;
#pragma unroll 1
    for (int m = 0; m < nm; m++) {
        const int row = ISV ? 6 * t + 2 * m : 3 * ((g >> 1) + 4 * (g & 1)) + m;
        const uint32_t a0 = tile + row * 128 + (((ISV ? g : t) ^ (row & 7)) << 4), a1 = ISV ? (a0 ^ 16) + 128 : a0 ^ 64;
        uint32_t l[8], cw[4], ck = 0, cd = 0;
#pragma unroll
        for (int r = 0; r < 4; r++) {
            uint32_t w0, w1, w2, w3;
            lds128(((r & 1) ? a1 : a0) + (r >> 1) * 3072, w0, w1, w2, w3);
            const uint32_t y0 = bmul2(w0, scl), y1 = bmul2(w1, scl), y2 = bmul2(w2, scl), y3 = bmul2(w3, scl);
            cd |= bdiff2(y0, inv, w0) | bdiff2(y1, inv, w1);
            cd |= bdiff2(y2, inv, w2) | bdiff2(y3, inv, w3);
            const uint32_t ha = prmt(y0, y1, 0x7531), hb = prmt(y2, y3, 0x7531);
            l[2 * r] = prmt(y0, y1, 0x6420); l[2 * r + 1] = prmt(y2, y3, 0x6420);
            asm("lop3.b32 %0, %1, 0x87878787, %2, 0xe2;" : "=r"(cw[r]) : "r"(ha), "r"(__funnelshift_r(hb, hb, 4)));
            ck |= ha | hb;
        }
        const uint32_t bad = __ballot_sync(0xffffffffu, (ck & 0x78787878u) | cd);
        if (bad) {
            const int src = __ffs(bad) - 1;
            const uint32_t b0 = __shfl_sync(0xffffffffu, a0, src), b1 = __shfl_sync(0xffffffffu, a1, src), n0 = lds32(xl);
            const uint32_t ax = ((lane & 8) ? b1 : b0) + (lane >> 4) * 3072 + 2 * (lane & 7), x = lds16(ax), y = bmul2(x, scl);
            const bool out = (y & 0x7800u) | bdiff2(y, inv, x);
            const uint32_t n = n0 + __popc(__ballot_sync(0xffffffffu, out) << (31 - lane)) - 1;
            if (out) {
                asm volatile("st.shared.u16 [%0], %1;" ::"r"(ax), "h"((unsigned short)0) : "memory");
                if (n < XCAP) sts32(xl + 16 + 4 * n, f_(x << 16 | tau << 12 | src << 7 | m << 5 | lane));
            }
            if (lane == 31) sts32(xl, f_(n + 1));
            __syncwarp();
            if (n0 <= XCAP) { m--; continue; }
        }
        uint32_t d[3] = {a0, a1, a0 + 3072};
        dst(m, d);
        sts128(d[0], l[0], l[1], l[2], l[3]);
        sts128(d[1], l[4], l[5], l[6], l[7]);
        sts128(d[2], cw[0], cw[1], cw[2], cw[3]);
    }
}

struct Maps { CUtensorMap k, v, wq, wo, w1, w3, w2, vr; const void* vp; const void* kp; uint32_t zero; };
#define RT_SEL ((wu & 1) ? RT_MASK2 : RT_MASK)
#define PFK 5
#define Q_AT 3
#define WO_T0 33200
#define K5D 370
#define PK_AT 6

__device__ __forceinline__ void load_ffn(const Maps& maps, int b, uint32_t dst, uint32_t bar) {
    const bool gu = b < NG;
    mbar_expect_tx(bar, gu ? 61440 : 49152);
    tma3d(dst, gu ? (b < NG / 2 ? &maps.w1 : &maps.w3) : &maps.w2, gu ? 48 * (b & (NG / 2 - 1)) : 16 * (b - DN0), 0, 0, bar, FFN_POL);
}

__device__ __forceinline__ void load_wo(const Maps& maps, uint32_t dst, int h, int c, uint32_t bar, int nbox) {
#pragma unroll 1
    for (int i = 0; i < nbox; i++) {
        if (!(i & 1)) mbar_expect_tx(bar + 4 * i, i + 1 < nbox ? 20480 : 10240);
        tma3d(dst + i * 10240, &maps.wo, 0, 5 * c, h * DH + 32 * i, bar + 4 * (i & 6), POL_EF);
    }
}

__global__ void __launch_bounds__(NT, 1)
decode_kernel(const __grid_constant__ Maps maps, const __nv_bfloat16* __restrict__ x_in, __nv_bfloat16* __restrict__ out) {
    extern __shared__ __align__(1024) unsigned char smem[];
    const int tid = threadIdx.x, warp = tid >> 5, lane = tid & 31;
    const int wu = __shfl_sync(0xffffffffu, tid >> 5, 0);
    const int b = blockIdx.x, h = b >> 2, c = b & 3;
    const uint32_t sb = smem_u32(smem);
    const uint32_t qbar = sb + SM_BAR + 16 * 8, fbar = qbar + 8, wbar = qbar + 16;
    uint32_t* xs32 = reinterpret_cast<uint32_t*>(smem + SM_XS);
    float* rr = reinterpret_cast<float*>(smem + SM_R);
    float* misc = reinterpret_cast<float*>(smem + SM_MISC);

    PROF_T(0);
    {
        uint2 xv = make_uint2(0u, 0u);
        const uint32_t t_start = now_ns();
        if (elect_one()) {
            const uint32_t rb = sb + SM_BAR + wu * 16, xb = sb + SM_XBAR + wu * 8;
            mbar_init(rb, 1); mbar_init(rb + 8, 1); mbar_init(xb, 1);
            if (wu == 0) mbar_init(qbar, 1);
            asm volatile("fence.mbarrier_init.release.cluster;" ::: "memory");
            const int row = (h * SK + (SK - WIN) + c * 1024 + wu * 128) * 3;
            const uint32_t ring = sb + SM_RING + wu * 2 * TILE;
#pragma unroll
            for (int n = 0; n < 3; n++) {
                const uint32_t bar = ((IN_S1 >> n) & 1) ? rb + 8 : ((IN_S0 >> n) & 1) ? rb : xb;
                mbar_expect_tx(bar, TILE);
                tma2d(((IN_S1 >> n) & 1) ? ring + TILE : ((IN_S0 >> n) & 1) ? ring : sb + SM_B + wu * TILE, &maps.k, 0, row + 48 * n, bar, POL_EF);
                if (n == 0 && wu == 0) {
                    mbar_expect_tx(qbar, 61440);
                    tma3d(sb + SM_Q, &maps.wq, 0, 160 * c, 3 * h, qbar, POL_EF);
                }
            }
            if (wu == 1) {
                mbar_init(fbar, 1);
#pragma unroll
                for (int i = 0; i < 3; i++) mbar_init(wbar + 8 * i, 1);
                asm volatile("fence.mbarrier_init.release.cluster;" ::: "memory");
            }
            if (wu >= 2) {
                const CUtensorMap* mp = wu == 2 ? &maps.v : wu == 3 ? &maps.wo : wu == 4 ? &maps.w1 : wu == 5 ? &maps.w3 : wu == 6 ? &maps.w2 : &maps.vr;
                asm volatile("prefetch.tensormap [%0];" ::"l"(mp) : "memory");
            }
        }
        if (tid < 160) asm volatile("ld.global.nc.v2.u32 {%0,%1}, [%2];" : "=r"(xv.x), "=r"(xv.y) : "l"(x_in + 4 * tid) : "memory");
        if (tid == 96) { misc[2] = 0.f; misc[3] = 0.f; }
        if (lane == 1) *reinterpret_cast<uint2*>(smem + SM_XL + warp * XSTR) = make_uint2(0u, t_start + WO_T0);
        if (tid >= 128 && tid < 148) {
            const uint32_t v = tid < 138 ? ONES : 0u;
            reinterpret_cast<uint4*>(smem + SM_ONE)[tid - 128] = make_uint4(v, v, v, v);
        }
        if (tid < 160) { xs32[xpos(2 * tid)] = xv.x; xs32[xpos(2 * tid + 1)] = xv.y; }
        __syncthreads();
        PROF_T(14);
        if (b == 0 && tid >= 232) asm volatile("st.relaxed.gpu.global.u32 [%0], %1;" ::"l"(g_scr.ticket + tid - 232), "r"(0) : "memory");
        if (tid == 64 || (tid == 65 && b < 216 - NCTA)) st_pkt(&g_scr.acc[1][(b + NCTA * (tid - 64)) * ACC_STR], 0, 0, 0, 0);
    }

    uint32_t kq[NQ][4];
    const float SC = 0.07216878364870322f * 1.4426950408889634f;

#pragma unroll 1
    for (int ph = 0; ph < 3; ph++) {
        const int layer = ph >> 1;
        const uint32_t tag = layer + 1;
        PROF_T(1 + layer * 16);
        if (ph) {
        {
            const int tl = opq(tid), warp = tl >> 5, lane = tl & 31, g = lane >> 2, t = lane & 3, mat = lane >> 3, r8 = lane & 7;
            const int kh = warp >> 2, mg = warp & 3;
            uint32_t aq[3];
#pragma unroll
            for (int i = 0; i < 3; i++) {
                const int ch = 6 * mg + 2 * i + (mat & 1);
                aq[i] = sb + SM_Q + (80 * kh + (mat >> 1) * 8 + r8) * 128 + (ch >> 3) * 20480 + (((ch & 7) ^ r8) << 4);
            }
#define PF_K5 if (layer == 1 && PFK) tile_keep(&maps.k, (h * SK + (SK - WIN) + c * 1024 + wu * 128 + PFK * 16) * 3);
            uint2 xv = make_uint2(0u, 0u);
            mbar_wait(qbar, 0);
            uint32_t pre[6][4];
#pragma unroll
            for (int n = 0; n < 6; n++) ldsm4t(aq[n % 3] + (n / 3) * 2048, pre[n]);
            if (layer == 1) {
                __syncthreads();
                if (elect_one()) {
                    const uint32_t bar = sb + SM_BAR + wu * 16;
                    asm volatile("mbarrier.expect_tx.relaxed.cta.shared::cta.b64 [%0], 1536;" ::"r"(bar) : "memory");
#pragma unroll
                    for (int k = 0; k < 3; k++)
                        tma2d(sb + SM_Q + v1_pos(3 * wu + k), &maps.vr, 0, (h * SK + (SK - WIN) + c * 1024 + wu * 128) / 2 + 8 + 2 * k, bar, POL_EF);
                }
            }
            const uint32_t pm = opq(g == 1 ? sb + SM_ONE : sb + SM_XS + 160 * (2 * c + kh) + 16 * t), pm2 = opq(pm + 128 - (g == 1 ? 0 : 8 * t));
            const uint32_t dq = opq(sb + SM_R + 8 * (kh * 192 + 48 * mg + g)), ds = opq(sb + SM_ST + 8 * warp + (lane < 16 ? 4 : 0));
            const bool wr = t == 0, ws = (lane & 15) == 0, lo = lane < 16;
            if (wu < 5) {
                const int p0 = xpos(2 * tl), p1 = xpos(2 * tl + 1);
                if (layer == 1) {
                    uint4 v;
                    for (int it = 0; it < SPIN_CAP; it++) { v = ld_pkt(&g_scr.ay[tl]); if (__all_sync(0xffffffffu, v.w == 1)) break; }
                    xv = make_uint2(v.x, v.y);
                    xs32[p0] = xv.x; xs32[p1] = xv.y;
                } else xv = make_uint2(xs32[p0], xs32[p1]);
            }
            if (layer) PC(24);
            __syncthreads();
            PF_K5
            if (layer) PC(25);
            PROF_T(13 + layer * 16);
            const float e0 = bf_lo(xv.x), e1 = bf_hi(xv.x), e2 = bf_lo(xv.y), e3 = bf_hi(xv.y);
            const float s1 = (e0 + e1) + (e2 + e3), s2 = (e0 * e0 + e1 * e1) + (e2 * e2 + e3 * e3);
            float sv = lo ? s1 : s2, cc[3][4];
            gemv15<2048>(cc, pre, [&](int i) { return aq[i]; }, pm, pm2, sv, lo ? s2 : s1);
            if (wr) {
#pragma unroll
                for (int i = 0; i < 3; i++) { sts64(dq + 128 * i, cc[i][0], cc[i][1]); sts64(dq + 128 * i + 64, cc[i][2], cc[i][3]); }
            }
            if (ws) sts32(ds, sv);
        }
        const uint32_t pa = opq(sb + SM_R + 32 * opq(tid)), st = opq(sb + SM_ST);
        uint4* const pq = opq(&g_scr.hx[b * 48 + opq(tid)]);
        if (layer) PC(26);
        __syncthreads();
        if (layer) PC(27);
        PROF_T(33 + layer * 16);
        if (wu < 2) {
            float mean, inv;
            ln_stats(st, mean, inv);
            const float4 a0 = lds4f(pa), a1 = lds4f(pa + 16), b0 = lds4f(pa + 1536), b1 = lds4f(pa + 1552);
            float q0 = inv * ((a0.x + b0.x) - mean * (a0.y + b0.y)), q1 = inv * ((a0.z + b0.z) - mean * (a0.w + b0.w));
            float q2 = inv * ((a1.x + b1.x) - mean * (a1.y + b1.y)), q3 = inv * ((a1.z + b1.z) - mean * (a1.w + b1.w));
            st_pktfp(pq, q0, q1, q2, q3, 1, tid < 48);
        }
        if (layer == 1 && tid >= 192 && tid < 194 && b < 108) st_pkt(&g_scr.acc[0][(2 * b + opq(tid) - 192) * ACC_STR], 0, 0, 0, 0);
        }
        if (layer) PC(28);
        if (layer == 1 && (wu & 2)) {
            idle(K5D);
#pragma unroll 1
            for (int w = wu; w >= (wu > 4 ? wu - 2 : wu); w -= 2)
                tile_load(sb + SM_Q + c_slot(w), &maps.k, (h * SK + (SK - WIN) + c * 1024 + w * 128 + 5 * 16) * 3, sb + SM_XBAR + w * 8, 0, 0);
        }

        float sc0 = -INFINITY, sc1 = -INFINITY, sc2 = 0.f, sc3 = 0.f, mw;
        uint32_t pk0, pk1;
        float acc[3][4];
        {
            const uint32_t ring = sb + SM_RING + wu * 2 * TILE, rb = sb + SM_BAR + wu * 16;
            const uint32_t xtile = sb + SM_Q + c_slot(wu), xb = sb + SM_XBAR + wu * 8;
#define V_SEQ(n) ((int)(SEQ1 >> (4 * (n))) & 7)
#define SLOT1(n) (((IN_S1 >> (n)) & 1) ? ring + TILE : ((IN_S0 >> (n)) & 1) ? ring : sb + SM_B + wu * TILE)
#define BAR1(n) (((IN_S1 >> (n)) & 1) ? rb + 8 : ((IN_S0 >> (n)) & 1) ? rb : xb)
#define PAR1(n) ((PARITY1 >> (n)) & 1)
#define PAR2(n) ((PARITY2 >> (n)) & 1)
            const int row0 = (h * SK + (SK - WIN) + c * 1024 + wu * 128) * 3;
            auto issue1 = [&](int n, uint32_t dep, bool vph = false) {
                const CUtensorMap* mp = n < 8 ? &maps.k : &maps.v;
                const int tl = V_SEQ(n), row = row0 + tl * 48;
                const uint32_t dst = SLOT1(n), bar = BAR1(n);
                if (vph && wu < L1R && tl == 7 - (wu & 1)) {
                    tile_load_l1(dst, maps.vp, row, bar, opq(tid) & 31);
                    return;
                }
                tile_load(dst, mp, row, bar, dep, maps.zero);
                if ((RT_SEL >> (tl + (n & 8))) & 1) {
                    if (n != V0_AT + 1) tile_keep(mp, row);
                    else if ((opq(tid) & 31) < 8)
                        asm volatile("cp.async.bulk.prefetch.L2.global.L2::cache_hint [%0], 256, %1;"
                                     ::"l"(static_cast<const char*>(maps.vp) + (size_t)(row + 4 + 6 * (opq(tid) & 31)) * 128), "l"(POL_EN) : "memory");
                }
            };
            auto refill1 = [&](int s, uint32_t dep, bool vph = false) { issue1(s + (!vph || s < V0_AT ? 3 : 2), dep, vph); };
#define LANE_IDS const int tl = opq(tid), lane = tl & 31, g = lane >> 2, t = lane & 3; (void)tl; (void)lane; (void)g; (void)t;
            const uint32_t xl = sb + SM_XL + wu * XSTR;
            if (layer == 0) {
#pragma unroll 1
                for (int s = ph ? Q_AT : 0; s < (ph ? 5 : Q_AT); s++) {
                    LANE_IDS
                    const uint32_t tile = SLOT1(s);
                    mbar_wait(BAR1(s), PAR1(s));
                    const uint32_t scl = s == 0 ? pack_scale(tile, lane, xl + 8) : lds32(xl + 8);
                    pack_tile<false>(tile, s, 3, scl, xl, lane, [](int, uint32_t (&)[3]) {});
#pragma unroll
                    for (int n = 0; n < 5; n++) {
                        if (s == n) {
#pragma unroll
                            for (int m = 0; m < 3; m++) {
                                const uint32_t a = tile + K_OFF(2 * m);
                                lds128(a, kq[9 * n + 3 * m][0], kq[9 * n + 3 * m][1], kq[9 * n + 3 * m][2], kq[9 * n + 3 * m][3]);
                                lds128(a ^ 64, kq[9 * n + 3 * m + 1][0], kq[9 * n + 3 * m + 1][1], kq[9 * n + 3 * m + 1][2], kq[9 * n + 3 * m + 1][3]);
                                lds128(a + 3072, kq[9 * n + 3 * m + 2][0], kq[9 * n + 3 * m + 2][1], kq[9 * n + 3 * m + 2][2], kq[9 * n + 3 * m + 2][3]);
                            }
                        }
                    }
                    __syncwarp();
                    refill1(s, lds32(tile));
                }
                if (!ph) continue;
            }
            {
                if (wu < 2) {
                    const int tl = min(opq(tid), 47);
                    const int w = 2 * tl;
                    const uint32_t pos = opq(sb + SM_QS + 4 * (((w >> 2) & 3) * 24 + 2 * (w >> 4) + ((w >> 1) & 1)));
                    uint4 v[4];
                    for (int it = 0; it < SPIN_CAP; it++) {
#pragma unroll
                        for (int k = 0; k < 4; k++) v[k] = ld_pkt(&g_scr.hx[(h * 4 + k) * 48 + tl]);
                        if (all_odd(v[0].w, v[1].w, v[2].w, v[3].w)) break;
                    }
                    sts32(pos, f_(pack2((f_(v[0].x) + f_(v[1].x)) + (f_(v[2].x) + f_(v[3].x)), (f_(v[0].y) + f_(v[1].y)) + (f_(v[2].y) + f_(v[3].y)))));
                    sts32(pos + 48, f_(pack2((f_(v[0].z) + f_(v[1].z)) + (f_(v[2].z) + f_(v[3].z)), (f_(v[0].w) + f_(v[1].w)) + (f_(v[2].w) + f_(v[3].w)))));
                }
            }
            if (layer) PC(29);
            __syncthreads();
            if (layer) PC(30);
            PROF_T(2 + layer * 16);
#define V1_REST(p) ((p) < 6 ? sb + SM_Q + v1_pos(3 * wu + ((p) >> 1)) + 256 * ((p) & 1) : ((sb + SM_R + wu * 784 + 127) & ~127u) - 1536 + 256 * (p))
#define V1_LOAD(bar) if (elect_one()) tma2d(V1_REST(6), &maps.vr, 0, row0 / 6 + 14, bar, POL_EF);
#define V1_EXPECT(bar) { if ((opq(tid) & 31) == 0) asm volatile("mbarrier.expect_tx.relaxed.cta.shared::cta.b64 [%0], 512;" ::"r"(bar) : "memory"); }
            if (layer == 1 && wu < 2) tile_load(xtile, &maps.k, row0 + 5 * 48, xb, 0, 0);
            if (layer == 1 && wu >= 4) idle(STAG);
            {
                uint32_t qf[12];
                int t;
                {
                    const int lane = opq(tid) & 31;
                    t = lane & 3;
                    const uint32_t qa = sb + SM_QS + (2 * t + ((lane >> 2) & 1)) * 48;
#pragma unroll
                    for (int i = 0; i < 3; i++) lds128(qa + 16 * i, qf[4 * i], qf[4 * i + 1], qf[4 * i + 2], qf[4 * i + 3]);
                }
                const uint32_t sq = lds32(xl + 8) - 64u * 0x00800080u;
#pragma unroll
                for (int i = 0; i < 12; i++) qf[i] = bmul2(qf[i], sq);
#define KR_STEP(tau, m) \
                    _Pragma("unroll") for (int i = 2 * (m); i < 2 * (m) + 2; i++) { \
                        const int q0 = 9 * tau + 3 * (i >> 1), r = i & 1; \
                        uint32_t w[4]; \
                        unpack8(kq[q0][2 * r], kq[q0][2 * r + 1], kq[q0 + 2][r], w); \
                        mma16816(cA, w[0], w[1], w[2], w[3], qf[2 * i], qf[2 * i + 1]); \
                        unpack8(kq[q0 + 1][2 * r], kq[q0 + 1][2 * r + 1], kq[q0 + 2][2 + r], w); \
                        mma16816(cB, w[0], w[1], w[2], w[3], qf[2 * i], qf[2 * i + 1]); \
                    }
#define KR_BEGIN float cA[4] = {0.f, 0.f, 0.f, 0.f}, cB[4] = {0.f, 0.f, 0.f, 0.f};
#define KR_END(tau) \
                    const float sA = (cA[0] + cA[3]) * 18446744073709551616.f, sB = (cB[0] + cB[3]) * 18446744073709551616.f; \
                    if (t == (tau & 3)) { if (tau < 4) { sc0 = sA; sc1 = sB; } else { sc2 = sA; sc3 = sB; } }
#define KR_SCORES(tau) { KR_BEGIN KR_STEP(tau, 0) KR_STEP(tau, 1) KR_STEP(tau, 2) KR_END(tau) }
                uint32_t va[3];
                {
                    const int lane = opq(tid) & 31, g = lane >> 2, t = lane & 3;
#pragma unroll
                    for (int i = 0; i < 3; i++) va[i] = ring + V_OFF(2 * i);
                }
#define V_STG(n) _Pragma("unroll") for (int j = 3 * (n); j < 3 * (n) + 3; j++) { \
                    const int i = (j % 12) >> 1; \
                    lds128p(((i & 1) ? (va[i >> 1] ^ 16) + 128 : va[i >> 1]) + (j / 12) * TILE + (j & 1) * 3072, layer, kq[j][0], kq[j][1], kq[j][2], kq[j][3]); }
                uint32_t dep = 0;
                {
                    KR_BEGIN
                    KR_STEP(0, 0) V_STG(0) KR_STEP(0, 1) V_STG(1) KR_STEP(0, 2) V_STG(2)
                    KR_END(0)
                }
                {
                    KR_BEGIN
                    KR_STEP(1, 0) V_STG(3)
                    __syncwarp();
                    dep = lds32(ring);
                    if (layer == 1) tile_load(ring, &maps.k, row0 + 6 * 48, rb, dep, maps.zero);
                    KR_STEP(1, 1) V_STG(4) KR_STEP(1, 2) V_STG(5)
                    KR_END(1)
                }
                {
                    KR_BEGIN
                    KR_STEP(2, 0) V_STG(6) KR_STEP(2, 1) V_STG(7)
                    __syncwarp();
                    dep = lds32(ring + TILE);
                    KR_STEP(2, 2)
                    if (layer == 1) {
                        V1_EXPECT(rb + 8)
                        tile_load(ring + TILE, &maps.k, row0 + 7 * 48, rb + 8, dep, maps.zero);
                        V1_LOAD(rb + 8)
                    }
                    KR_END(2)
                }
#pragma unroll 1
                for (int s = 5; s < 8; s++) {
                    {
                        LANE_IDS
                        const uint32_t tile = !layer ? SLOT1(s) : s == 5 ? xtile : ring + (s - 6) * TILE, tb = !layer ? BAR1(s) : s == 5 ? xb : rb + (s - 6) * 8;
                        const float ur = f_((318u << 23) - (lds32(xl + 8) << 16));
                        mbar_wait(tb, layer ? PAR2(s - 5) : PAR1(s));
                        if (layer) PROF_T(29 + s);
                        float cA[4] = {0.f, 0.f, 0.f, 0.f}, cB[4] = {0.f, 0.f, 0.f, 0.f};
#pragma unroll
                        for (int i = 0; i < 6; i++) {
                            uint32_t a0, a1, a2, a3;
                            lds128(tile + K_OFF(i), a0, a1, a2, a3);
                            mma16816(cA, a0, a1, a2, a3, qf[2 * i], qf[2 * i + 1]);
                            lds128(tile + K_OFF(i) + 3072, a0, a1, a2, a3);
                            mma16816(cB, a0, a1, a2, a3, qf[2 * i], qf[2 * i + 1]);
                        }
                        __syncwarp();
                        const uint32_t last = lds32(tile);
                        if (layer) tile_load(tile, &maps.v, row0 + (s - 2) * 48, tb, last, maps.zero);
                        else refill1(s, last);
                        if (t == (s & 3)) { sc2 = (cA[0] + cA[3]) * ur; sc3 = (cB[0] + cB[3]) * ur; }
                    }
                    if (s == 5) KR_SCORES(3)
                    if (s == 6) {
                        KR_SCORES(4)
                        const int lane = opq(tid) & 31;
                        const uint32_t nx = min(lds32(xl), (uint32_t)XCAP);
#pragma unroll 1
                        for (uint32_t n = 0; n < nx; n++) {
                            const uint32_t id = lds32(xl + 16 + 4 * n);
                            const uint32_t qo = 96 * ((id >> 7) & 3) + 48 * ((id >> 1) & 1) + 16 * ((id >> 5) & 3) + (id & 12) + 2 * (id & 1);
                            const float cr = bf_hi(id) * f_(lds16(sb + SM_QS + qo) << 16);
                            const int d = (int)(16 * ((id >> 9) & 7) + 4 * ((id >> 12) & 3) + ((id >> 13) & 2) + ((id >> 4) & 1) + ((id >> 8) & 128)) - 4 * lane;
                            if (d == 0) sc0 += cr;
                            if (d == 1) sc1 += cr;
                            if (d == 2) sc2 += cr;
                            if (d == 3) sc3 += cr;
                        }
                    }
                }
#undef KR_SCORES
#undef KR_STEP
#undef KR_BEGIN
#undef KR_END
#undef V_STG
                {
                    LANE_IDS
                    if (lds32(xl) > XCAP || !__all_sync(0xffffffffu, (fabsf(sc0) + fabsf(sc1)) + (fabsf(sc2) + fabsf(sc3)) < INFINITY)) {
                        const uint32_t qa = sb + SM_QS + (2 * t + (g & 1)) * 48;
#pragma unroll
                        for (int i = 0; i < 3; i++) lds128(qa + 16 * i, qf[4 * i], qf[4 * i + 1], qf[4 * i + 2], qf[4 * i + 3]);
                        const uint4* kg = reinterpret_cast<const uint4*>(static_cast<const char*>(maps.kp) + (size_t)row0 * 128) + ((g >> 1) + 4 * (g & 1)) * 24 + t;
#pragma unroll 1
                        for (int s = 0; s < 8; s++) {
                            float cA[4] = {0.f, 0.f, 0.f, 0.f}, cB[4] = {0.f, 0.f, 0.f, 0.f};
#pragma unroll
                            for (int i = 0; i < 6; i++) {
                                uint4 u = ldg128(kg + s * 384 + 4 * i);
                                mma16816v(cA, u.x, u.y, u.z, u.w, qf[2 * i], qf[2 * i + 1]);
                                u = ldg128(kg + s * 384 + 4 * i + 192);
                                mma16816v(cB, u.x, u.y, u.z, u.w, qf[2 * i], qf[2 * i + 1]);
                            }
                            if (t == s) { sc0 = cA[0] + cA[3]; sc1 = cB[0] + cB[3]; }
                            if (t + 4 == s) { sc2 = cA[0] + cA[3]; sc3 = cB[0] + cB[3]; }
                        }
                    }
                }
            }
            mw = warp_max(fmaxf(fmaxf(sc0, sc1), fmaxf(sc2, sc3)));
            pk0 = pack2(ex2((sc0 - mw) * SC), ex2((sc1 - mw) * SC));
            pk1 = pack2(ex2((sc2 - mw) * SC), ex2((sc3 - mw) * SC));
            sc2 = (bf_lo(pk0) + bf_hi(pk0)) + (bf_lo(pk1) + bf_hi(pk1));
            sc2 = (float)__reduce_add_sync(0xffffffffu, __float2uint_rn(sc2 * 16777216.f)) * (1.0f / 16777216.f);
            if ((opq(tid) & 31) == 0) st_pkt2(&g_scr.mx[h * 32 + c * 8 + wu], __float_as_uint(mw), (__float_as_uint(sc2) & ~3u) | tag);
            auto head_factor = [&]() {
                const int lane = opq(tid) & 31;
                int it = 0;
                while (!__all_sync(0xffffffffu, (__float_as_uint(sc1) & 3u) == tag) && ++it < SPIN_CAP) {
                    const uint2 mv = ld_pkt2(&g_scr.mx[h * 32 + lane]); sc0 = f_(mv.x); sc1 = f_(mv.y);
                }
                const float e = ex2((sc0 - warp_max(sc0)) * SC);
                const uint32_t d = __reduce_add_sync(0xffffffffu, __float2uint_rn(sc1 * e * 524288.f));
                sc3 = __shfl_sync(0xffffffffu, e, c * 8 + wu) * 524288.f * rcp((float)d);
            };
#pragma unroll
            for (int s = 0; s < 3; s++) { acc[s][0] = acc[s][1] = acc[s][2] = acc[s][3] = 0.f; }
#define P_CONSTS \
                const uint32_t sel0 = g == 0 ? 0x4410u : (g == 1 ? 0x1044u : 0x4444u); \
                const uint32_t sel1 = g == 2 ? 0x4410u : (g == 3 ? 0x1044u : 0x4444u); \
                const int src00 = 4 * (t < 2 ? 4 * t : 4 * (t - 2) + 1);
#define P_FRAGS(tau) \
                const uint32_t pk = ((tau) & 4) ? pk1 : pk0; \
                const uint32_t w0 = __shfl_sync(0xffffffffu, pk, src00 + ((tau) & 3)); \
                const uint32_t w1 = __shfl_sync(0xffffffffu, pk, src00 + ((tau) & 3) + 8); \
                uint32_t pb[4][2]; \
                _Pragma("unroll") for (int j = 0; j < 4; j++) { \
                    const uint32_t src = ((j & 1) ? w1 : w0) >> ((j >> 1) * 16); \
                    pb[j][0] = __byte_perm(src, 0, sel0); pb[j][1] = __byte_perm(src, 0, sel1); \
                }
            if (layer == 0) {
#pragma unroll 1
                for (int s = 8; s < 16; s++) {
                    LANE_IDS
                    P_CONSTS
                    if (s == 13) { const uint2 mv = ld_pkt2(&g_scr.mx[h * 32 + lane]); sc0 = f_(mv.x); sc1 = f_(mv.y); }
                    P_FRAGS(V_SEQ(s))
                    mbar_wait(BAR1(s), PAR1(s));
                    const uint32_t tile = SLOT1(s);
#pragma unroll
                    for (int j = 0; j < 4; j++) {
#pragma unroll
                        for (int u = 0; u < 3; u++) {
                            uint32_t a0, a1, a2, a3;
                            lds128(tile + (j >> 1) * 3072 + V_OFF(3 * (j & 1) + u), a0, a1, a2, a3);
                            mma16816(acc[u], a0, a1, a2, a3, pb[j][0], pb[j][1]);

                        }
                    }
                    __syncwarp();
                    if (s < V0_AT || (s > V0_AT + 1 && s < 14)) refill1(s, lds32(tile), true);
                    if (s == V0_AT || s == V0_AT + 1) {
                        {
                            const uint32_t ar = sb + SM_R + wu * 784 + 32 * g + 16 * t;
                            if (t < 2) {
#pragma unroll
                                for (int u = 0; u < 3; u++) sts128(ar + 256 * u, __float_as_uint(acc[u][0]), __float_as_uint(acc[u][1]), __float_as_uint(acc[u][2]), __float_as_uint(acc[u][3]));
                            }
                        }
                        const uint32_t scl = s == V0_AT ? pack_scale(tile, lane, xl + 12) : lds32(xl + 12);
                        pack_tile<true>(tile, s + 8 - V0_AT, V0_AT + 3 - s, scl, xl, lane, [&](int m, uint32_t (&d)[3]) {
                            if (s != V0_AT && m == 0) {
#pragma unroll
                                for (int k = 0; k < 3; k++) d[k] = ring + 3072 + V_OFF(2 * k + 1);
                            }
                        });
                        if (s != V0_AT) {
                            lds128(tile + V_OFF(2), kq[45][0], kq[45][1], kq[45][2], kq[45][3]);
                            lds128(tile + V_OFF(3), kq[46][0], kq[46][1], kq[46][2], kq[46][3]);
                            lds128(tile + V_OFF(2) + 3072, kq[47][0], kq[47][1], kq[47][2], kq[47][3]);
                            __syncwarp();
                            issue1(V0_AT + 3, lds32(tile));
                        }
                        const int ln = opq(tid) & 31;
                        const uint32_t ar = sb + SM_R + wu * 784 + 8 * (ln & 28) + 16 * (ln & 1);
#pragma unroll
                        for (int u = 0; u < 3; u++) {
                            uint32_t a0, a1, a2, a3;
                            lds128(ar + 256 * u, a0, a1, a2, a3);
                            acc[u][0] = f_(a0); acc[u][1] = f_(a1); acc[u][2] = f_(a2); acc[u][3] = f_(a3);
                        }
                    }
                    if (s == 13) head_factor();
                    if (s >= 14 && elect_one()) {
                        if (atomicAdd(reinterpret_cast<unsigned*>(misc + 3), 1u) == 14u && (int)(now_ns() - lds32(xl + 4)) >= 0) {
                            PROF_X(47);
                            load_wo(maps, sb + SM_B, h, c, wbar, 6);
                            atomicAdd(reinterpret_cast<unsigned*>(misc + 3), 256u);
                        }
                    }
                }
            } else {
                LANE_IDS
                P_CONSTS
#pragma unroll
                for (int k = 0; k < 4; k++) lds128(V1_REST(t + 4 * (k >> 1)) + 16 * g + 128 * (k & 1), kq[36 + k][0], kq[36 + k][1], kq[36 + k][2], kq[36 + k][3]);
#pragma unroll 1
                for (int i = 3; i < 8; i++) {
                    const uint32_t tile = i > 3 ? ring + (i & 1) * TILE : xtile, tb = i > 3 ? rb + (i & 1) * 8 : xb;
                    if (i == 6) { const uint2 mv = ld_pkt2(&g_scr.mx[h * 32 + lane]); sc0 = f_(mv.x); sc1 = f_(mv.y); }
                    if (i == 7) head_factor();
                    if (i == PK_AT) {
                uint32_t nx, nk, ik, iv;
                lds128(xl, nx, nk, ik, iv);
                if (nx <= XCAP) {
                    const uint32_t pks = bmul2(pk0, iv);
#pragma unroll
                    for (int s = 0; s < 2; s++) {
                        const uint32_t pk1 = 0, pk0 = pks;
                        P_FRAGS(s)
#pragma unroll
                        for (int j = 0; j < 4; j++) {
#pragma unroll
                            for (int u = 0; u < 3; u++) {
                                const int i = 3 * (j & 1) + u, m = i >> 1, r = i & 1, hf = j >> 1;
                                if (s == 1 && m == 2) continue;
                                const int ql = s == 0 ? 4 * m + 2 * hf : m == 0 ? 3 + 4 * hf : 45 + hf, qc = s == 0 ? 4 * m + 1 : m == 0 ? 11 : 47;
                                uint32_t w[4];
                                unpack8(kq[ql][2 * r], kq[ql][2 * r + 1], kq[qc][2 * hf + r], w);
                                mma16816(acc[u], w[0], w[1], w[2], w[3], pb[j][0], pb[j][1]);
                            }
                        }
                    }
#pragma unroll 1
                    for (uint32_t n = 0; n < nx; n++) {
                        const uint32_t id = lds32(xl + 16 + 4 * n);
                        const int i = ((id >> 4) & 6) + ((id >> 3) & 1), key = ((id >> 6) & 6) + (i >= 3);
                        const uint32_t pw = __shfl_sync(0xffffffffu, pk0, 8 * (key & 3) + (key & 4) + ((id >> 12) & 3));
                        const float cr = bf_hi(id) * ((id & 16) ? bf_hi(pw) : bf_lo(pw));
                        const int d = (int)(64 * ((id >> 9) & 7) + 4 * (id & 4) + 4 * (i >= 3 ? i - 3 : i) + (id & 3) + ((~id >> 5) & 1024)) - 16 * lane;
#pragma unroll
                        for (int k = 0; k < 12; k++) if (d == k) acc[k >> 2][k & 3] += cr;
                    }
                } else {
                    const uint4* vg = reinterpret_cast<const uint4*>(static_cast<const char*>(maps.vp) + (size_t)row0 * 128) + 48 * t + g;
#pragma unroll 1
                    for (int s = 0; s < 2; s++) {
                        P_FRAGS(s)
#pragma unroll
                        for (int j = 0; j < 4; j++) {
#pragma unroll
                            for (int u = 0; u < 3; u++) {
                                if (s == 1 && (j & 1) && u) continue;
                                const uint4 w = ldg128(vg + 384 * s + 192 * (j >> 1) + 24 * (j & 1) + 8 * u);
                                mma16816v(acc[u], w.x, w.y, w.z, w.w, pb[j][0], pb[j][1]);
                            }
                        }
                    }
                }
#pragma unroll
                for (int s = 2; s > 0; s--) {
                    P_FRAGS(s)
#pragma unroll
                    for (int j = 0; j < 4; j++) {
#pragma unroll
                        for (int u = 0; u < 3; u++) {
                            if (s == 1 && !((j & 1) && u)) continue;
                            const int k = s == 2 ? 12 + 2 * (3 * (j & 1) + u) + (j >> 1) : 35 + (j >> 1) * 2 + u;
                            mma16816(acc[u], kq[k][0], kq[k][1], kq[k][2], kq[k][3], pb[j][0], pb[j][1]);
                        }
                    }
                }
                    }
                    P_FRAGS(i)
                    mbar_wait(tb, PAR2(i));
                    PROF_T(34 + i);
#pragma unroll
                    for (int k = 0; k < 6; k++) {
                        const uint32_t a = tile + V_OFF(k);
                        lds128(a, kq[24 + k][0], kq[24 + k][1], kq[24 + k][2], kq[24 + k][3]);
                        lds128(a + 3072, kq[30 + k][0], kq[30 + k][1], kq[30 + k][2], kq[30 + k][3]);
                    }
#pragma unroll
                    for (int j = 0; j < 4; j++) {
#pragma unroll
                        for (int u = 0; u < 3; u++) {
                            const int k = 24 + 6 * (j >> 1) + 3 * (j & 1) + u;
                            mma16816(acc[u], kq[k][0], kq[k][1], kq[k][2], kq[k][3], pb[j][0], pb[j][1]);
                        }
                    }
                    __syncwarp();
                    if (wu < L1R && i == 5 - (wu & 1)) tile_load_l1(tile, maps.vp, row0 + (i + 2) * 48, tb, lane);
                    else if (i == 4 || i == 5) tile_load(tile, &maps.v, row0 + (i + 2) * 48, tb, lds32(tile), maps.zero);
                    if (i == WO_AT1 && HAS_FFN && elect_one()) {
                        if (atomicAdd(reinterpret_cast<unsigned*>(misc + 2), 1u) == 7u) {
                            PROF_X(63);
                            load_wo(maps, sb + SM_Q, h, c, wbar, KEEP4 && __float_as_uint(misc[1]) >= DN0 ? 5 : 6);
                        }
                    }
                }
            }
#undef P_FRAGS
#undef P_CONSTS
#undef LANE_IDS
        }
        PROF_T(3 + layer * 16);
        PC(layer * 32 + 1);

        {
            const int lane = opq(tid) & 31;
            const uint32_t a = sb + SM_R + wu * 784 + 8 * (lane & 28) + 16 * (lane & 1);
#pragma unroll
            for (int u = 0; u < 3; u++) sts128p(a + 256 * u, acc[u][0] * sc3, acc[u][1] * sc3, acc[u][2] * sc3, acc[u][3] * sc3, lane & 2);
        }
        const uint32_t role1 = layer ? lds32(sb + SM_MISC + 4) : DN0 + NDN;
        const uint32_t pc = opq(sb + SM_R + 16 * opq(tid));
        uint4* const px0 = opq(&g_scr.hx[b * 48 + opq(tid)]);
        __syncthreads();
        PROF_T(4 + layer * 16);
        PC(layer * 32 + 2);
        float4 o = make_float4(0.f, 0.f, 0.f, 0.f);
        if (wu < 2) {
            float4 v[8];
#pragma unroll
            for (int w = 0; w < 8; w++) v[w] = lds4f(pc + w * 784);
            o.x = ((v[0].x + v[1].x) + (v[2].x + v[3].x)) + ((v[4].x + v[5].x) + (v[6].x + v[7].x));
            o.y = ((v[0].y + v[1].y) + (v[2].y + v[3].y)) + ((v[4].y + v[5].y) + (v[6].y + v[7].y));
            o.z = ((v[0].z + v[1].z) + (v[2].z + v[3].z)) + ((v[4].z + v[5].z) + (v[6].z + v[7].z));
            o.w = ((v[0].w + v[1].w) + (v[2].w + v[3].w)) + ((v[4].w + v[5].w) + (v[6].w + v[7].w));
            o.w = f_(__float_as_uint(o.w) & ~1u);
            st_pktp(px0, __float_as_uint(o.x), __float_as_uint(o.y), __float_as_uint(o.z), __float_as_uint(o.w), threadIdx.x < 48);
        }
        uint32_t ticket = 0;
        if (layer == 0 && tid == 224)
            asm volatile("atom.relaxed.gpu.global.inc.u32 %0, [%1], 0x7fffffff;" : "=r"(ticket) : "l"(g_scr.ticket + 8 + (b >> 3)) : "memory");
        if (layer == 0 && tid == 224 && lds32(sb + SM_MISC + 12) < 256u) {
            int it = 0;
            while ((int)(now_ns() - lds32(sb + SM_XL + 4)) < 0 && ++it < SPIN_CAP) {}
            PROF_X(47);
            load_wo(maps, sb + SM_B, h, c, wbar, 6);
        }
        uint32_t pr;
        uint4* pacc;
        {
            const int tid = opq(threadIdx.x), warp = tid >> 5, lane = tid & 31, g = lane >> 2, t = lane & 3, mat = lane >> 3, r8 = lane & 7;
            const int kg = warp >> 1, mg = warp & 1;
            const bool wo2 = role1 < DN0 + NDN;
            const uint32_t aw2 = 40960 + (wo2 && KEEP4 && role1 >= DN0 && kg >= 2 ? SM_B - SM_Q : 0);
            uint32_t aw[5];
#pragma unroll
            for (int i = 0; i < 5; i++) {
                const uint32_t lin = ((mat >> 1) * 8 + r8) * 320 + 64 * i + 32 * mg + 16 * (mat & 1);
                aw[i] = sb + (wo2 ? SM_Q : SM_B) + 5120 * kg + (lin ^ ((lin >> 3) & 48));
            }
#define CXE 0
            const uint32_t ao = pin(sb + SM_OS + 96 * kg + 16 * t), dw = pin(sb + SM_R + 16 * (16 * mg + g) + 4 * kg);
            pr = pin(sb + SM_R + 48 * tid); pacc = pin(&g_scr.acc[layer][(54 * c + tid) * ACC_STR]);
            const int w = 2 * min(tid, 47);
            const uint32_t d0 = pin(sb + SM_OS + 4 * (24 * ((w >> 3) & 3) + ((w >> 2) & 1) + (w < 64 ? 4 * (w & 3) + 2 * (w >> 5) : 16 + 2 * (w & 3))));
            const uint32_t d1 = pin(d0 + (w < 64 ? 16 : 8));
            const uint4* pp[3];
#pragma unroll
            for (int k = 0; k < 3; k++) pp[k] = pin(&g_scr.hx[(h * 4 + ((c + 1 + k) & 3)) * 48 + min(tid, 47)]);
            bool ok = true;
            if ((PRE1 & 8) && layer) {
#pragma unroll
                for (int ks = 0; ks < 3; ks++) {
                    mbar_wait(wbar + 8 * ks, wo2);
#pragma unroll
                    for (int i = 0; i < 5; i++) ldsm4t(aw[i] + (ks == 2 ? aw2 : 20480 * ks), kq[3 * i + ks]);
                    if (ks == CXE && wu < 2) {
#pragma unroll
                        for (int k = 0; k < 3; k++) { const uint4 v = ld_pkt(pp[k]); kq[20 + k][0] = v.x; kq[20 + k][1] = v.y; kq[20 + k][2] = v.z; kq[20 + k][3] = v.w; }
                    }
                }
                PROF_T(50);
                if (CXE < 3 && wu < 2) {
                    ok = any_odd(kq[20][3], kq[21][3], kq[22][3]);
                    if (!ok) {
#pragma unroll
                        for (int k = 0; k < 3; k++) { o.x += f_(kq[20 + k][0]); o.y += f_(kq[20 + k][1]); o.z += f_(kq[20 + k][2]); o.w += f_(kq[20 + k][3]); }
                    }
                }
            }
            if (wu < 2) {
                if (ok) {
                    uint4 v3[3];
                    int it = 0;
                    do {
#pragma unroll
                        for (int k = 0; k < 3; k++) v3[k] = ld_pkt(pp[k]);
                        ok = any_odd(v3[0].w, v3[1].w, v3[2].w);
                    } while (ok && ++it < SPIN_CAP);
#pragma unroll
                    for (int k = 0; k < 3; k++) { o.x += f_(v3[k].x); o.y += f_(v3[k].y); o.z += f_(v3[k].z); o.w += f_(v3[k].w); }
                }
                sts32p(d0, f_(pack2(o.x, o.y)), tid >= 48);
                sts32p(d1, f_(pack2(o.z, o.w)), tid >= 48);
            }
            PC(layer * 32 + 3);
            __syncthreads();
            PROF_T(5 + layer * 16);
            PC(layer * 32 + 5);
            if (tid == 224 && layer == 0) {
                if (ticket >= 6 + ((b >> 3) & 1)) ticket = DN0 + NDN;
                else asm volatile("atom.relaxed.gpu.global.inc.u32 %0, [%1], 0x7fffffff;" : "=r"(ticket) : "l"(g_scr.ticket) : "memory");
            }
            uint32_t ob[6];
            lds128(ao, ob[0], ob[1], ob[2], ob[3]);
            lds64(ao + 64 - 8 * t, ob[4], ob[5]);
            float cc[5][4];
#pragma unroll
            for (int i = 0; i < 5; i++) cc[i][0] = cc[i][1] = cc[i][2] = cc[i][3] = 0.f;
            if ((PRE1 & 8) && layer) {
#pragma unroll
                for (int ks = 0; ks < 3; ks++) {
#pragma unroll
                    for (int i = 0; i < 5; i++) mma16816(cc[i], kq[3 * i + ks][0], kq[3 * i + ks][1], kq[3 * i + ks][2], kq[3 * i + ks][3], ob[2 * ks], ob[2 * ks + 1]);
                }
            } else {
#pragma unroll
                for (int ks = 0; ks < 3; ks++) {
                    mbar_wait(wbar + 8 * ks, wo2);
                    if (ks == 2) { PC(layer * 32 + 4); PROF_T(48 + layer * 2); }
                    uint32_t a[5][4];
#pragma unroll
                    for (int i = 0; i < 5; i++) ldsm4t(aw[i] + (ks == 2 ? aw2 : 20480 * ks), a[i]);
#pragma unroll
                    for (int i = 0; i < 5; i++) mma16816(cc[i], a[i][0], a[i][1], a[i][2], a[i][3], ob[2 * ks], ob[2 * ks + 1]);
                }
            }
            if (t == 0) {
#pragma unroll
                for (int i = 0; i < 5; i++) { sts32(dw + 512 * i, cc[i][0]); sts32(dw + 512 * i + 128, cc[i][2]); }
            }
        }
        PC(layer * 32 + 6);
        __syncthreads();
        PROF_T(6 + layer * 16);
        PC(layer * 32 + 7);
        if (tid < 54) {
            const float4 v0 = lds4f(pr), v1 = lds4f(pr + 16), v2 = lds4f(pr + 32);
            const float y0 = (v0.x + v0.y) + (v0.z + v0.w), y1 = (v1.x + v1.y) + (v1.z + v1.w), y2 = (v2.x + v2.y) + (v2.z + v2.w);
            red_pkt(pacc, y0, tid == 53 ? 0.f : y1, tid == 53 ? 0.f : y2);
        }
        if (tid == 224 && layer == 0) {
            misc[1] = __uint_as_float(ticket);
            if (ticket < DN0 + NDN && (ticket < NG || !DNTH)) load_ffn(maps, ticket, sb + SM_B, fbar);
        }
        PROF_T(7 + layer * 16);
        PC(layer * 32 + 8);
        __syncthreads();
        const int role = (int)__float_as_uint(misc[1]);
        PC(layer * 32 + 9);
        const uint32_t fbase = sb + SM_B;
        const uint32_t DONE32 = 0x42000000u;
        if (role < NG) {
            const int tid = opq(threadIdx.x), warp = tid >> 5, lane = tid & 31, g = lane >> 2, t = lane & 3, mat = lane >> 3, r8 = lane & 7;
            const uint32_t ag = fbase + (80 * warp + (mat >> 1) * 8 + r8) * 96 + (((mat & 1) ^ (r8 >> 2)) << 4);
            constexpr int GI = 32, GK = 16 * 96;
            const bool on = (g & 1) == (t >> 1), isx = on && g < 2;
            const uint32_t pm = opq(isx ? sb + SM_XS + 160 * warp + 16 * t : sb + (on ? SM_ONE : SM_ZERO)), pm2 = opq(pm + 128 - (isx ? 8 * t : 0));
            const uint32_t dg = opq(sb + SM_R + 4 * (2 * (warp * 48 + g) + t)), ds = opq(sb + SM_ST + 8 * warp + (lane < 16 ? 4 : 0));
            const bool ws = (lane & 15) == 0, lo = lane < 16;
            uint32_t pre[6][4];
            float s1 = 0.f, s2 = 0.f;
            {
                bool hx = wu == 7;
                int it = 0;
                const uint4* px = &g_scr.acc[layer][min(tid, 215) * ACC_STR];
                const int cq = tid / 54, r = tid - 54 * cq, k0 = min(160 * cq + 3 * r, DM - 1);
                const uint32_t w0 = sb + SM_XS + 4 * xpos(k0 >> 1), w1 = sb + SM_XS + 4 * xpos(min((k0 >> 1) + 1, DM / 2 - 1));
                const uint32_t e0 = w0 + 2 * (k0 & 1), e1 = (k0 & 1) ? w1 : w0 + 2, e2 = w1 + 2 * (k0 & 1);
                                auto sts16 = [](uint32_t a, uint32_t x, bool on) {
                    asm volatile("{\n.reg .pred p;\nsetp.ne.u32 p, %2, 0;\n@p st.shared.u16 [%0], %1;\n}" ::"r"(a), "h"((unsigned short)x), "r"((uint32_t)on) : "memory");
                };
                const bool on0 = tid < 216, on1 = on0 && r != 53;
                const float x0 = on0 ? f_(lds16(e0) << 16) : 0.f, x1 = on1 ? f_(lds16(e1) << 16) : 0.f, x2 = on1 ? f_(lds16(e2) << 16) : 0.f;
                auto take_x = [&](const uint4 v) {
                    if (__all_sync(0xffffffffu, v.w == DONE32)) {
                        hx = true;
                        const uint32_t a = pack2(f_(v.x), f_(v.y)), p = pack2(x0 + bf_lo(a), x1 + bf_hi(a)), q = pack2(x2 + bfr(f_(v.z)), 0.f);
                        sts16(e0, p, on0); sts16(e1, p >> 16, on1); sts16(e2, q, on1);
                        const float y0 = on0 ? bf_lo(p) : 0.f, y1 = on0 ? bf_hi(p) : 0.f, y2 = on0 ? bf_lo(q) : 0.f;
                        s1 = y0 + (y1 + y2); s2 = y0 * y0 + (y1 * y1 + y2 * y2);
                    }
                };
                auto try_x = [&]() { take_x(ld_pkt(px)); };
                while (!mbar_test(fbar, 0) && ++it < SPIN_CAP) { if (!hx) try_x(); }
                uint4 v0 = make_uint4(0u, 0u, 0u, 0u);
                if ((PRE1 & 4) && !hx) v0 = ld_pkt(px);
#pragma unroll
                for (int n = 0; n < 6; n++) ldsm4t(ag + (n % 3) * GI + (n / 3) * GK, pre[n]);
                if ((PRE1 & 1) && layer) {
#pragma unroll
                    for (int n = 6; n < 15; n++) ldsm4t(ag + (n % 3) * GI + (n / 3) * GK, kq[n - 6]);
                }
                if ((PRE1 & 4) && !hx) take_x(v0);
                PC(layer * 32 + 10);
                while (!hx && ++it < SPIN_CAP) try_x();
                PC(layer * 32 + 11);
            __syncthreads();
            PC(layer * 32 + 12);
            PROF_T(9 + layer * 16);
            float sv = lo ? s1 : s2, cc[3][4];
            if ((PRE1 & 1) && layer) gemv15r(cc, pre, kq, pm, pm2, sv, lo ? s2 : s1);
            else gemv15<GK>(cc, pre, [&](int i) { return ag + i * GI; }, pm, pm2, sv, lo ? s2 : s1);
#pragma unroll
            for (int i = 0; i < 3; i++) { sts32p(dg + 128 * i, cc[i][0] + cc[i][3], t & 2); sts32p(dg + 128 * i + 64, cc[i][1] + cc[i][2], t & 2); }
            if (ws) sts32(ds, sv);
            const uint32_t pg = opq(sb + SM_R + 8 * (24 * warp + (lane < 24 ? lane : 0))), st = opq(sb + SM_ST);
            uint4* const ph = opq(lane < 24 && lane % 6 == 0 ? &g_scr.ah[role * 8 + 4 * warp + lane / 6] : nullptr);
            PC(layer * 32 + 13);
            __syncthreads();
            PC(layer * 32 + 14);
            PROF_T(43 + layer * 16);
            if (wu < 2) {
                float mean, inv;
                ln_stats(st, mean, inv);
                float2 v[8];
#pragma unroll
                for (int w = 0; w < 8; w++) v[w] = lds2f(pg + w * 384);
                const float gx = ((v[0].x + v[1].x) + (v[2].x + v[3].x)) + ((v[4].x + v[5].x) + (v[6].x + v[7].x));
                const float gs = ((v[0].y + v[1].y) + (v[2].y + v[3].y)) + ((v[4].y + v[5].y) + (v[6].y + v[7].y));
                float ga = inv * (gx - mean * gs);
                if (role < NG / 2) { ga = bfr(ga); ga *= rcp(1.0f + ex2(-1.4426950408889634f * ga)); }
                const uint32_t wd = pack2(ga, __shfl_down_sync(0xffffffffu, ga, 1));
                const uint32_t wa = __shfl_down_sync(0xffffffffu, wd, 2), wb = __shfl_down_sync(0xffffffffu, wd, 4);
                if (ph) st_pkt(ph, wd, wa, wb, tag);
            }
            if (HOLD & 2) __syncthreads();
            }
            PROF_T(10 + layer * 16);
            PC(layer * 32 + 15);
        } else if (role < DN0 + NDN) {
            const int j = role - DN0;
            const int tid = opq(threadIdx.x), warp = tid >> 5, lane = tid & 31, g = lane >> 2, t = lane & 3, mat = lane >> 3, r8 = lane & 7;
            float xres = 0.f;
            uint32_t xr0 = 0, xr1 = 0;
            if (wu == 0) {
                const int col = 16 * j + (lane & 15), cc = col / 160, r = col - 160 * cc, e = r % 3;
                const uint4* px = &g_scr.acc[layer][(54 * cc + r / 3) * ACC_STR];
                const float x0 = __bfloat162float(reinterpret_cast<const __nv_bfloat16*>(xs32)[2 * xpos(col >> 1) + (col & 1)]);
                uint4 v;
                int it = 0;
                bool ld = DNTH && layer == 0;
                do {
                    v = ld_pkt(px);
                    if (ld && f_(__shfl_sync(0xffffffffu, v.w, 0)) >= (float)DNTH) { ld = false; if (lane == 0) load_ffn(maps, role, sb + SM_B, fbar); }
                } while (!__all_sync(0xffffffffu, v.w == DONE32) && ++it < SPIN_CAP);
                if (ld && lane == 0) load_ffn(maps, role, sb + SM_B, fbar);
                xres = x0 + bfr(f_(e == 0 ? v.x : (e == 1 ? v.y : v.z)));
                const int p4 = 4 * (lane & 3);
                xr0 = pack2(__shfl_sync(0xffffffffu, xres, p4), __shfl_sync(0xffffffffu, xres, p4 + 1));
                xr1 = pack2(__shfl_sync(0xffffffffu, xres, p4 + 2), __shfl_sync(0xffffffffu, xres, p4 + 3));
            }
            PC(layer * 32 + 17);
            PROF_T(9 + layer * 16);
            const uint32_t ad = fbase + (192 * warp + (mat >> 1) * 8 + r8) * 32 + (((mat & 1) ^ (r8 >> 2)) << 4);
            uint32_t* hs = reinterpret_cast<uint32_t*>(rr) + warp * 96;
            uint32_t pre[NPRE][4];
            {
                uint32_t pos[3];
#pragma unroll
                for (int i = 0; i < 3; i++) { const int w = 3 * lane + i; pos[i] = pin(sb + SM_R + 384 * warp + 4 * ((w & ~15) + 4 * (w & 3) + ((w >> 2) & 1) + ((w >> 2) & 2))); }
                uint4 v = make_uint4(0u, 0u, 0u, 0u), u = v;
                if (layer == 0) { v = ld_pkt(&g_scr.ah[tid]); u = ld_pkt(&g_scr.ah[256 + tid]); }
                mbar_wait(fbar, 0);
#pragma unroll
                for (int n = 0; n < NPRE; n++) ldsm4t(ad + n * 512, pre[n]);
                if ((PRE1 & 2) && layer) {
#pragma unroll
                    for (int n = NPRE; n < 12; n++) ldsm4t(ad + n * 512, kq[12 + n]);
                }
                PC(layer * 32 + 18);
                int it = 0;
                for (; any_ne(v.w, u.w, tag) && it < SPIN_CAP; it++) { v = ld_pkt(&g_scr.ah[tid]); u = ld_pkt(&g_scr.ah[256 + tid]); }
                PC(layer * 32 + 19);
                sts32(pos[0], f_(bmul2(v.x, u.x))); sts32(pos[1], f_(bmul2(v.y, u.y))); sts32(pos[2], f_(bmul2(v.z, u.z)));
            __syncwarp();
            PROF_T(11 + layer * 16);
            PC(layer * 32 + 20);
            float ca[4] = {0.f, 0.f, 0.f, 0.f}, cb[4] = {0.f, 0.f, 0.f, 0.f};
            if ((PRE1 & 2) && layer) {
                float cc[4] = {0.f, 0.f, 0.f, 0.f}, cd[4] = {0.f, 0.f, 0.f, 0.f};
#pragma unroll
                for (int jj = 0; jj < 6; jj++) {
                    const uint4 hv = *reinterpret_cast<const uint4*>(hs + 16 * jj + 4 * t);
                    const uint32_t (&f0)[4] = 2 * jj < NPRE ? pre[2 * jj < NPRE ? 2 * jj : 0] : kq[12 + 2 * jj];
                    const uint32_t (&f1)[4] = 2 * jj + 1 < NPRE ? pre[2 * jj + 1 < NPRE ? 2 * jj + 1 : 0] : kq[13 + 2 * jj];
                    if (jj & 1) { mma16816(cc, f0[0], f0[1], f0[2], f0[3], hv.x, hv.y); mma16816(cd, f1[0], f1[1], f1[2], f1[3], hv.z, hv.w); }
                    else { mma16816(ca, f0[0], f0[1], f0[2], f0[3], hv.x, hv.y); mma16816(cb, f1[0], f1[1], f1[2], f1[3], hv.z, hv.w); }
                }
#pragma unroll
                for (int e = 0; e < 4; e++) { ca[e] += cc[e]; cb[e] += cd[e]; }
            } else {
#pragma unroll
                for (int jj = 0; jj < 6; jj++) {
                    const uint4 hv = *reinterpret_cast<const uint4*>(hs + 16 * jj + 4 * t);
                    uint32_t a[4];
                    if (2 * jj < NPRE) { a[0] = pre[2 * jj][0]; a[1] = pre[2 * jj][1]; a[2] = pre[2 * jj][2]; a[3] = pre[2 * jj][3]; }
                    else ldsm4t(ad + 2 * jj * 512, a);
                    mma16816(ca, a[0], a[1], a[2], a[3], hv.x, hv.y);
                    if (2 * jj + 1 < NPRE) { a[0] = pre[2 * jj + 1][0]; a[1] = pre[2 * jj + 1][1]; a[2] = pre[2 * jj + 1][2]; a[3] = pre[2 * jj + 1][3]; }
                    else ldsm4t(ad + (2 * jj + 1) * 512, a);
                    mma16816(cb, a[0], a[1], a[2], a[3], hv.z, hv.w);
                }
            }
            if (t == 0) { rr[768 + warp * 16 + g] = ca[0] + cb[0]; rr[768 + warp * 16 + 8 + g] = ca[2] + cb[2]; }
            const uint32_t pd = opq(sb + SM_R + 3072 + 16 * (lane & 3));
            uint4* const py = opq(&g_scr.ay[j * 4 + lane]);
            uint2* const po = opq(reinterpret_cast<uint2*>(out + 16 * j) + lane);
            PC(layer * 32 + 21);
            __syncthreads();
            PC(layer * 32 + 22);
            if (wu == 0) {
                float4 p[8];
#pragma unroll
                for (int w = 0; w < 8; w++) p[w] = lds4f(pd + 64 * w);
                const uint32_t y0 = pack2(((p[0].x + p[1].x) + (p[2].x + p[3].x)) + ((p[4].x + p[5].x) + (p[6].x + p[7].x)),
                                          ((p[0].y + p[1].y) + (p[2].y + p[3].y)) + ((p[4].y + p[5].y) + (p[6].y + p[7].y)));
                const uint32_t y1 = pack2(((p[0].z + p[1].z) + (p[2].z + p[3].z)) + ((p[4].z + p[5].z) + (p[6].z + p[7].z)),
                                          ((p[0].w + p[1].w) + (p[2].w + p[3].w)) + ((p[4].w + p[5].w) + (p[6].w + p[7].w)));
                uint32_t wd, wn;
                asm("add.rn.bf16x2 %0, %1, %2;" : "=r"(wd) : "r"(xr0), "r"(y0));
                asm("add.rn.bf16x2 %0, %1, %2;" : "=r"(wn) : "r"(xr1), "r"(y1));
                asm volatile("{\n.reg .pred p;\nsetp.ne.u32 p, %3, 0;\n@p st.global.v2.u32 [%0], {%1,%2};\n}" ::"l"(po), "r"(wd), "r"(wn), "r"((uint32_t)(layer && tid < 4)) : "memory");
                st_pktp(py, wd, wn, 0, tag, tid < 4);
            }
            if (HOLD & 1) __syncthreads();
            }
            PROF_T(12 + layer * 16);
            PC(layer * 32 + 23);
        }
    }
}

typedef CUresult (*EncodeFn)(CUtensorMap*, CUtensorMapDataType, cuuint32_t, void*, const cuuint64_t*, const cuuint64_t*, const cuuint32_t*,
                             const cuuint32_t*, CUtensorMapInterleave, CUtensorMapSwizzle, CUtensorMapL2promotion, CUtensorMapFloatOOBfill);

void make_map(EncodeFn enc, CUtensorMap* m, const void* base, int rank, uint64_t d0, uint64_t d1, uint64_t d2, uint64_t s1, uint64_t s2,
              uint32_t b0, uint32_t b1, uint32_t b2, CUtensorMapSwizzle sw, CUtensorMapL2promotion pr = CU_TENSOR_MAP_L2_PROMOTION_NONE) {
    cuuint64_t dims[3] = {d0, d1, d2};
    cuuint64_t strides[2] = {s1, s2};
    cuuint32_t box[3] = {b0, b1, b2};
    cuuint32_t es[3] = {1, 1, 1};
    enc(m, CU_TENSOR_MAP_DATA_TYPE_BFLOAT16, rank, const_cast<void*>(base), dims, strides, box, es, CU_TENSOR_MAP_INTERLEAVE_NONE, sw,
        pr, CU_TENSOR_MAP_FLOAT_OOB_FILL_NONE);
}

}

extern "C" void kernel_launch(void* const* d_in, const int* in_sizes, int n_in, void* d_out, int out_size) {
    (void)in_sizes; (void)n_in; (void)out_size;
    static EncodeFn enc = nullptr;
    if (!enc) {
        void* fn = nullptr;
        cudaDriverEntryPointQueryResult qr;
        cudaGetDriverEntryPoint("cuTensorMapEncodeTiled", &fn, cudaEnableDefault, &qr);
        enc = reinterpret_cast<EncodeFn>(fn);
        cudaFuncSetAttribute(decode_kernel, cudaFuncAttributeMaxDynamicSharedMemorySize, SM_TOTAL);
    }
    Maps maps;
    make_map(enc, &maps.k, d_in[1], 2, 64, (uint64_t)NH * SK * 3, 1, 128, 0, 64, 48, 1, CU_TENSOR_MAP_SWIZZLE_128B);
    make_map(enc, &maps.v, d_in[2], 2, 64, (uint64_t)NH * SK * 3, 1, 128, 0, 64, 48, 1, CU_TENSOR_MAP_SWIZZLE_128B);
    make_map(enc, &maps.wq, d_in[3], 3, 64, DM, NH * DH / 64, NH * DH * 2, 128, 64, 160, 3, CU_TENSOR_MAP_SWIZZLE_128B);
    make_map(enc, &maps.wo, d_in[4], 3, 32, DM / 32, NH * DH, 64, DM * 2, 32, 5, 32, CU_TENSOR_MAP_SWIZZLE_64B);
    make_map(enc, &maps.vr, (const char*)d_in[2] + 512, 2, 128, (uint64_t)NH * SK / 2, 1, 768, 0, 128, 2, 1, CU_TENSOR_MAP_SWIZZLE_NONE);
    constexpr int GW = 48;
    make_map(enc, &maps.w1, d_in[6], 3, FF, 160, 4, FF * 2, 160 * FF * 2, GW, 160, 4, CU_TENSOR_MAP_SWIZZLE_NONE, FFN_PROMO);
    make_map(enc, &maps.w3, d_in[7], 3, FF, 160, 4, FF * 2, 160 * FF * 2, GW, 160, 4, CU_TENSOR_MAP_SWIZZLE_NONE, FFN_PROMO);
    make_map(enc, &maps.w2, d_in[8], 3, DM, 256, 6, DM * 2, 256 * DM * 2, 16, 256, 6, CU_TENSOR_MAP_SWIZZLE_32B, FFN_PROMO);
    maps.vp = d_in[2];
    maps.kp = d_in[1];
    maps.zero = 0;
    decode_kernel<<<NCTA, NT, SM_TOTAL, cudaStreamPerThread>>>(maps, (const __nv_bfloat16*)d_in[0], (__nv_bfloat16*)d_out);
}
```

```cpp
#include <cuda_runtime.h>
#include <cuda_bf16.h>
#include <cuda.h>
#include <stdint.h>
#include <math.h>

namespace {

constexpr int DM = 640;
constexpr int NH = 32;
constexpr int DH = 192;
constexpr int SK = 32768;
constexpr int WIN = 4096;
constexpr int FF = 1536;
constexpr int NCTA = 128;
constexpr int NT = 256;
constexpr int TILE = 6144;
constexpr int NG = 64;
constexpr int DN0 = 64;
constexpr int NDN = 40;

constexpr int SM_RING = 0;
constexpr int SM_B = 8 * 2 * TILE;
constexpr int SM_Q = SM_B + 61440;
__host__ __device__ constexpr int c_slot(int w) { return w < 2 ? 4096 + 10240 * w : 12288 + 6144 * w; }
__host__ __device__ constexpr int v1_pos(int n) { return 10240 * (n >> 3) + 512 * (n & 7); }
constexpr int SM_XS = SM_Q + 61440;
constexpr int SM_R = SM_XS + 1280;
constexpr int SM_ST = SM_R + 4096;
constexpr int SM_QS = SM_R + 6272;
constexpr int SM_OS = SM_QS + 384;
constexpr int SM_BAR = SM_OS + 384;
constexpr int SM_XBAR = SM_BAR + 24 * 8;
constexpr int SM_MISC = SM_XBAR + 8 * 8;
constexpr int SM_ONE = SM_MISC + 16;
constexpr int SM_ZERO = SM_ONE + 160;
constexpr int XCAP = 48;
constexpr int XSTR = 16 + 4 * XCAP;
constexpr int SM_XL = SM_ZERO + 160;
constexpr int SM_TOTAL = SM_XL + 8 * XSTR;
static_assert(SM_TOTAL <= 232448, "shared memory");

constexpr unsigned long long POL_EF = 0x12F0000000000000ull;
constexpr unsigned long long POL_EN = 0x16F0000000000000ull;

#define RT_MASK 0xF2E0u
#define RT_MASK2 0xEAE0u
#define WO_AT1 5
#define FFN_PROMO CU_TENSOR_MAP_L2_PROMOTION_NONE
#define FFN_POL POL_EF
#define HAS_FFN (__float_as_uint(misc[1]) < DN0 + NDN)
#define ACC_STR 1
#define NPRE 6

#define STAG 200
#define L1R 3
#define PRE1 13
#define HOLD 2
#define DNTH 23
constexpr int V0_AT = 8;
constexpr unsigned long long SEQ1 = 0x2765431076543210ull;
constexpr uint32_t IN_S1 = 0xAA49, IN_S0 = 0x124, PARITY1 = 0x6638, PARITY2 = 0xCE;
#define KEEP4 1
constexpr int NQ = 48;
constexpr int SPIN_CAP = 1 << 19;
constexpr uint32_t ONES = 0x3F803F80u;

struct alignas(1024) Scratch {
    uint4 hx[NCTA * 48];
    uint4 pad0[32 * 5 * 32 + 160];
    uint4 acc[2][216 * 8];
    uint4 ay[160];
    uint4 ah[NG * 8];
    uint2 mx[NH * 32];
    uint32_t ticket[32];
    uint32_t pad1[32];
};
__device__ Scratch g_scr;
#define PROF_T(i)
#define PROF_X(i)
#define PC(i)

__device__ __forceinline__ uint32_t smem_u32(const void* p) { return (uint32_t)__cvta_generic_to_shared(p); }
__device__ __forceinline__ void mbar_init(uint32_t bar, uint32_t cnt) {
    asm volatile("mbarrier.init.shared::cta.b64 [%0], %1;" ::"r"(bar), "r"(cnt) : "memory");
}
__device__ __forceinline__ void mbar_expect_tx(uint32_t bar, uint32_t bytes) {
    asm volatile("mbarrier.arrive.expect_tx.shared::cta.b64 _, [%0], %1;" ::"r"(bar), "r"(bytes) : "memory");
}
__device__ __forceinline__ bool mbar_test(uint32_t bar, uint32_t parity) {
    uint32_t done;
    asm volatile("{\n.reg .pred p;\nmbarrier.try_wait.parity.shared::cta.b64 p, [%1], %2;\nselp.u32 %0, 1, 0, p;\n}"
                 : "=r"(done) : "r"(bar), "r"(parity) : "memory");
    return done;
}
__device__ __forceinline__ void mbar_wait(uint32_t bar, uint32_t parity) {
    int it = 0;
    while (!mbar_test(bar, parity) && ++it < SPIN_CAP) {}
}
__device__ __forceinline__ void tma2d(uint32_t dst, const CUtensorMap* map, int c0, int c1, uint32_t bar, unsigned long long pol) {
    asm volatile("cp.async.bulk.tensor.2d.shared::cluster.global.mbarrier::complete_tx::bytes.L2::cache_hint [%0], [%1, {%3, %4}], [%2], %5;"
                 ::"r"(dst), "l"(map), "r"(bar), "r"(c0), "r"(c1), "l"(pol) : "memory");
}
__device__ __forceinline__ void tma3d(uint32_t dst, const CUtensorMap* map, int c0, int c1, int c2, uint32_t bar, unsigned long long pol) {
    asm volatile("cp.async.bulk.tensor.3d.shared::cluster.global.mbarrier::complete_tx::bytes.L2::cache_hint [%0], [%1, {%3, %4, %5}], [%2], %6;"
                 ::"r"(dst), "l"(map), "r"(bar), "r"(c0), "r"(c1), "r"(c2), "l"(pol) : "memory");
}
__device__ __forceinline__ void tile_load(uint32_t dst, const CUtensorMap* map, int row, uint32_t bar, uint32_t dep, uint32_t zero) {
    asm volatile("{\n.reg .pred p;\n.reg .b32 n;\nmad.lo.u32 n, %5, %6, 6144;\nelect.sync _|p, 0xffffffff;\n"
                 "@p mbarrier.arrive.expect_tx.shared::cta.b64 _, [%2], n;\n"
                 "@p cp.async.bulk.tensor.2d.shared::cluster.global.mbarrier::complete_tx::bytes.L2::cache_hint [%0], [%1, {0, %3}], [%2], %4;\n}"
                 ::"r"(dst), "l"(map), "r"(bar), "r"(row), "l"(POL_EF), "r"(dep), "r"(zero) : "memory");
}
__device__ __forceinline__ void tile_keep(const CUtensorMap* map, int row) {
    asm volatile("{\n.reg .pred p;\nelect.sync _|p, 0xffffffff;\n"
                 "@p cp.async.bulk.prefetch.tensor.2d.L2.global.L2::cache_hint [%0, {0, %1}], %2;\n}"
                 ::"l"(map), "r"(row), "l"(POL_EN) : "memory");
}
__device__ __forceinline__ void tile_load_l1(uint32_t dst, const void* base, int row, uint32_t bar, int lane) {
    const char* g = static_cast<const char*>(base) + (size_t)row * 128 + lane * 16;
    const uint32_t s0 = dst + (lane >> 3) * 128 + (((lane & 7) ^ (lane >> 3)) << 4), s1 = s0 ^ 64;
#pragma unroll
    for (int k = 0; k < 12; k++)
        asm volatile("cp.async.ca.shared.global.L2::cache_hint [%0], [%1], 16, %2;" ::"r"(((k & 1) ? s1 : s0) + k * 512), "l"(g + k * 512), "l"(POL_EF) : "memory");
    asm volatile("cp.async.mbarrier.arrive.shared::cta.b64 [%0];" ::"r"(bar) : "memory");
    __syncwarp();
    if (lane == 0) asm volatile("mbarrier.arrive.shared::cta.b64 _, [%0];" ::"r"(bar) : "memory");
}
__device__ __forceinline__ bool elect_one() {
    uint32_t p;
    asm volatile("{\n.reg .pred p;\nelect.sync _|p, 0xffffffff;\nselp.u32 %0, 1, 0, p;\n}" : "=r"(p));
    return p;
}
__device__ __forceinline__ void lds128(uint32_t addr, uint32_t& a, uint32_t& b, uint32_t& c, uint32_t& d) {
    asm volatile("ld.shared.v4.u32 {%0,%1,%2,%3}, [%4];" : "=r"(a), "=r"(b), "=r"(c), "=r"(d) : "r"(addr) : "memory");
}
__device__ __forceinline__ void lds128p(uint32_t addr, uint32_t on, uint32_t& a, uint32_t& b, uint32_t& c, uint32_t& d) {
    asm volatile("{\n.reg .pred p;\nsetp.ne.u32 p, %5, 0;\n@p ld.shared.v4.u32 {%0,%1,%2,%3}, [%4];\n}" : "+r"(a), "+r"(b), "+r"(c), "+r"(d) : "r"(addr), "r"(on) : "memory");
}
__device__ __forceinline__ void lds64(uint32_t addr, uint32_t& a, uint32_t& b) {
    asm volatile("ld.shared.v2.u32 {%0,%1}, [%2];" : "=r"(a), "=r"(b) : "r"(addr) : "memory");
}
__device__ __forceinline__ void ldsm4t(uint32_t addr, uint32_t (&a)[4]) {
    asm volatile("ldmatrix.sync.aligned.m8n8.x4.trans.shared.b16 {%0,%1,%2,%3}, [%4];" : "=r"(a[0]), "=r"(a[1]), "=r"(a[2]), "=r"(a[3]) : "r"(addr) : "memory");
}
__device__ __forceinline__ void mma16816(float (&c)[4], uint32_t a0, uint32_t a1, uint32_t a2, uint32_t a3, uint32_t b0, uint32_t b1) {
    asm("mma.sync.aligned.m16n8k16.row.col.f32.bf16.bf16.f32 {%0,%1,%2,%3}, {%4,%5,%6,%7}, {%8,%9}, {%0,%1,%2,%3};"
        : "+f"(c[0]), "+f"(c[1]), "+f"(c[2]), "+f"(c[3]) : "r"(a0), "r"(a1), "r"(a2), "r"(a3), "r"(b0), "r"(b1));
}
__device__ __forceinline__ void mma16816v(float (&c)[4], uint32_t a0, uint32_t a1, uint32_t a2, uint32_t a3, uint32_t b0, uint32_t b1) {
    asm volatile("mma.sync.aligned.m16n8k16.row.col.f32.bf16.bf16.f32 {%0,%1,%2,%3}, {%4,%5,%6,%7}, {%8,%9}, {%0,%1,%2,%3};"
        : "+f"(c[0]), "+f"(c[1]), "+f"(c[2]), "+f"(c[3]) : "r"(a0), "r"(a1), "r"(a2), "r"(a3), "r"(b0), "r"(b1));
}
__device__ __forceinline__ int xpos(int w) {
    const int seg = w / 40, r = w - 40 * seg;
    return 40 * seg + (r < 32 ? (r & 16) + 4 * (r & 3) + ((r >> 2) & 3) : 32 + 2 * (r & 3) + ((r >> 2) & 1));
}
#define NA_LD ""
#define NA_ST ""
__device__ __forceinline__ void st_pkt(uint4* p, uint32_t a, uint32_t b, uint32_t c, uint32_t d) {
    asm volatile("{\n.reg .b128 t;\n.reg .b64 lo, hi;\nmov.b64 lo, {%1,%2};\nmov.b64 hi, {%3,%4};\nmov.b128 t, {lo,hi};\nst.relaxed.gpu.global" NA_ST ".b128 [%0], t;\n}"
                 ::"l"(p), "r"(a), "r"(b), "r"(c), "r"(d) : "memory");
}
__device__ __forceinline__ void red_pkt(uint4* p, float a, float b, float c) {
    asm volatile("red.relaxed.gpu.global.add.v4.f32 [%0], {%1,%2,%3,%4};" ::"l"(p), "f"(a), "f"(b), "f"(c), "f"(1.0f) : "memory");
}
__device__ __forceinline__ void st_pktp(uint4* p, uint32_t a, uint32_t b, uint32_t c, uint32_t d, bool on) {
    asm volatile("{\n.reg .pred p;\n.reg .b128 t;\n.reg .b64 lo, hi;\nsetp.ne.u32 p, %5, 0;\nmov.b64 lo, {%1,%2};\nmov.b64 hi, {%3,%4};\nmov.b128 t, {lo,hi};\n"
                 "@p st.relaxed.gpu.global.b128 [%0], t;\n}" ::"l"(p), "r"(a), "r"(b), "r"(c), "r"(d), "r"((uint32_t)on) : "memory");
}
__device__ __forceinline__ void st_pktfp(uint4* p, float a, float b, float c, float d, uint32_t bit, bool on) {
    st_pktp(p, __float_as_uint(a), __float_as_uint(b), __float_as_uint(c), (__float_as_uint(d) & ~1u) | bit, on);
}
__device__ __forceinline__ uint4 ld_pkt(const uint4* p) {
    uint4 v;
    asm volatile("{\n.reg .b128 t;\n.reg .b64 lo, hi;\nld.relaxed.gpu.global" NA_LD ".b128 t, [%4];\nmov.b128 {lo,hi}, t;\nmov.b64 {%0,%1}, lo;\nmov.b64 {%2,%3}, hi;\n}"
                 : "=r"(v.x), "=r"(v.y), "=r"(v.z), "=r"(v.w) : "l"(p) : "memory");
    return v;
}
__device__ __forceinline__ bool all_odd(uint32_t a, uint32_t b, uint32_t c, uint32_t d) {
    uint32_t r;
    asm volatile("{\n.reg .pred p, q, t;\n.reg .b32 x;\nsetp.eq.b32 t, 0, 0;\nlop3.b32 x, %1, %2, %3, 0x80;\nlop3.and.b32 _|p, x, %4, 1, 0x80, t;\n"
                 "vote.sync.all.pred q, p, 0xffffffff;\nselp.u32 %0, 1, 0, q;\n}" : "=r"(r) : "r"(a), "r"(b), "r"(c), "r"(d));
    return r;
}
__device__ __forceinline__ bool any_odd(uint32_t a, uint32_t b, uint32_t c) {
    uint32_t r;
    asm volatile("{\n.reg .pred p, q, t;\n.reg .b32 x;\nsetp.eq.b32 t, 0, 0;\nlop3.b32 x, %1, %2, %3, 0xFE;\nlop3.and.b32 _|p, x, 1, 0, 0xC0, t;\n"
                 "vote.sync.any.pred q, p, 0xffffffff;\nselp.u32 %0, 1, 0, q;\n}" : "=r"(r) : "r"(a), "r"(b), "r"(c));
    return r;
}
__device__ __forceinline__ bool any_ne(uint32_t a, uint32_t b, uint32_t c) {
    uint32_t r;
    asm volatile("{\n.reg .pred p, q, t;\nsetp.eq.b32 t, 0, 0;\nlop3.and.b32 _|p, %1, %2, %3, 0x7E, t;\n"
                 "vote.sync.any.pred q, p, 0xffffffff;\nselp.u32 %0, 1, 0, q;\n}" : "=r"(r) : "r"(a), "r"(b), "r"(c));
    return r;
}
__device__ __forceinline__ uint2 ld_pkt2(const uint2* p) {
    unsigned long long v;
    asm volatile("ld.relaxed.gpu.global" NA_LD ".b64 %0, [%1];" : "=l"(v) : "l"(p) : "memory");
    return make_uint2((uint32_t)v, (uint32_t)(v >> 32));
}
__device__ __forceinline__ void st_pkt2(uint2* p, uint32_t a, uint32_t b) {
    asm volatile("st.relaxed.gpu.global" NA_ST ".b64 [%0], %1;" ::"l"(p), "l"((unsigned long long)a | ((unsigned long long)b << 32)) : "memory");
}
__device__ __forceinline__ float ex2(float x) { float y; asm("ex2.approx.ftz.f32 %0, %1;" : "=f"(y) : "f"(x)); return y; }
__device__ __forceinline__ float rcp(float x) { float y; asm("rcp.approx.ftz.f32 %0, %1;" : "=f"(y) : "f"(x)); return y; }
__device__ __forceinline__ uint32_t pack2(float lo, float hi) {
    uint32_t r; asm("cvt.rn.bf16x2.f32 %0, %1, %2;" : "=r"(r) : "f"(hi), "f"(lo)); return r;
}
__device__ __forceinline__ float bf_lo(uint32_t w) { return __uint_as_float(w << 16); }
__device__ __forceinline__ float bf_hi(uint32_t w) { return __uint_as_float(w & 0xffff0000u); }
__device__ __forceinline__ float bfr(float x) { return bf_lo(pack2(x, 0.f)); }
__device__ __forceinline__ float f_(uint32_t u) { return __uint_as_float(u); }

template <int SK, typename AddrF>
__device__ __forceinline__ void gemv15(float (&cc)[3][4], uint32_t (&pre)[6][4], AddrF ad, uint32_t px, uint32_t px2, float& sv, float so) {
    uint32_t x0[4], x1[4], a[3][4];
    asm volatile("ld.shared.v4.u32 {%0,%1,%2,%3}, [%20];\nld.shared.v4.u32 {%4,%5,%6,%7}, [%20+64];\n"
                 "ldmatrix.sync.aligned.m8n8.x4.trans.shared.b16 {%8,%9,%10,%11}, [%21];\n"
                 "ldmatrix.sync.aligned.m8n8.x4.trans.shared.b16 {%12,%13,%14,%15}, [%22];\n"
                 "ldmatrix.sync.aligned.m8n8.x4.trans.shared.b16 {%16,%17,%18,%19}, [%23];\nbar.warp.sync 0xffffffff;"
                 : "=r"(x0[0]), "=r"(x0[1]), "=r"(x0[2]), "=r"(x0[3]), "=r"(x1[0]), "=r"(x1[1]), "=r"(x1[2]), "=r"(x1[3]),
                   "=r"(a[0][0]), "=r"(a[0][1]), "=r"(a[0][2]), "=r"(a[0][3]), "=r"(a[1][0]), "=r"(a[1][1]), "=r"(a[1][2]), "=r"(a[1][3]),
                   "=r"(a[2][0]), "=r"(a[2][1]), "=r"(a[2][2]), "=r"(a[2][3])
                 : "r"(px), "r"(ad(0) + 2 * SK), "r"(ad(1) + 2 * SK), "r"(ad(2) + 2 * SK) : "memory");
    __syncwarp();
    sv += __shfl_xor_sync(0xffffffffu, so, 16);
#pragma unroll
    for (int i = 0; i < 3; i++) {
        cc[i][0] = cc[i][1] = cc[i][2] = cc[i][3] = 0.f;
        mma16816v(cc[i], pre[i][0], pre[i][1], pre[i][2], pre[i][3], x0[0], x0[1]);
    }
    sv += __shfl_xor_sync(0xffffffffu, sv, 8);
#pragma unroll
    for (int i = 0; i < 3; i++) {
        mma16816v(cc[i], pre[3 + i][0], pre[3 + i][1], pre[3 + i][2], pre[3 + i][3], x0[2], x0[3]);
        ldsm4t(ad(i) + 3 * SK, pre[i]);
    }
    lds64(px2, x0[0], x0[1]);
    __syncwarp();
    sv += __shfl_xor_sync(0xffffffffu, sv, 4);
#pragma unroll
    for (int i = 0; i < 3; i++) {
        mma16816v(cc[i], a[i][0], a[i][1], a[i][2], a[i][3], x1[0], x1[1]);
        ldsm4t(ad(i) + 4 * SK, pre[3 + i]);
    }
    __syncwarp();
    sv += __shfl_xor_sync(0xffffffffu, sv, 2);
#pragma unroll
    for (int i = 0; i < 3; i++) mma16816v(cc[i], pre[i][0], pre[i][1], pre[i][2], pre[i][3], x1[2], x1[3]);
    sv += __shfl_xor_sync(0xffffffffu, sv, 1);
#pragma unroll
    for (int i = 0; i < 3; i++) mma16816v(cc[i], pre[3 + i][0], pre[3 + i][1], pre[3 + i][2], pre[3 + i][3], x0[0], x0[1]);
}
__device__ __forceinline__ void gemv15r(float (&cc)[3][4], const uint32_t (&pre)[6][4], const uint32_t (&ext)[NQ][4], uint32_t px, uint32_t px2, float& sv, float so) {
    uint32_t x0[4], x1[4], x2[2];
    float cd[3][4];
    lds128(px, x0[0], x0[1], x0[2], x0[3]);
    lds128(px + 64, x1[0], x1[1], x1[2], x1[3]);
    lds64(px2, x2[0], x2[1]);
    sv += __shfl_xor_sync(0xffffffffu, so, 16);
#pragma unroll
    for (int i = 0; i < 3; i++) {
        cc[i][0] = cc[i][1] = cc[i][2] = cc[i][3] = cd[i][0] = cd[i][1] = cd[i][2] = cd[i][3] = 0.f;
        mma16816v(cc[i], pre[i][0], pre[i][1], pre[i][2], pre[i][3], x0[0], x0[1]);
        mma16816v(cd[i], pre[3 + i][0], pre[3 + i][1], pre[3 + i][2], pre[3 + i][3], x0[2], x0[3]);
    }
    sv += __shfl_xor_sync(0xffffffffu, sv, 8);
#pragma unroll
    for (int i = 0; i < 3; i++) {
        mma16816v(cc[i], ext[i][0], ext[i][1], ext[i][2], ext[i][3], x1[0], x1[1]);
        mma16816v(cd[i], ext[3 + i][0], ext[3 + i][1], ext[3 + i][2], ext[3 + i][3], x1[2], x1[3]);
    }
    sv += __shfl_xor_sync(0xffffffffu, sv, 4);
#pragma unroll
    for (int i = 0; i < 3; i++) mma16816v(cc[i], ext[6 + i][0], ext[6 + i][1], ext[6 + i][2], ext[6 + i][3], x2[0], x2[1]);
    sv += __shfl_xor_sync(0xffffffffu, sv, 2);
    sv += __shfl_xor_sync(0xffffffffu, sv, 1);
#pragma unroll
    for (int i = 0; i < 3; i++) { cc[i][0] += cd[i][0]; cc[i][1] += cd[i][1]; cc[i][2] += cd[i][2]; cc[i][3] += cd[i][3]; }
}

__device__ __forceinline__ float warp_max(float x) {
    int i = __float_as_int(x);
    i = __reduce_max_sync(0xffffffffu, i ^ ((i >> 31) & 0x7fffffff));
    return __int_as_float(i ^ ((i >> 31) & 0x7fffffff));
}
__device__ __forceinline__ void idle(uint32_t clk) {
    uint32_t t0, t;
    asm volatile("mov.u32 %0, %%clock;" : "=r"(t0) :: "memory");
    do asm volatile("mov.u32 %0, %%clock;" : "=r"(t) :: "memory"); while (t - t0 < clk);
}
__device__ __forceinline__ uint32_t now_ns() { uint32_t t; asm volatile("mov.u32 %0, %%globaltimer_lo;" : "=r"(t)); return t; }
__device__ __forceinline__ int opq(int x) { asm volatile("" : "+r"(x)); return x; }
__device__ __forceinline__ uint32_t opq(uint32_t x) { asm volatile("" : "+r"(x)); return x; }
__device__ __forceinline__ uint32_t pin(uint32_t x) { return __shfl_sync(0xffffffffu, x, threadIdx.x & 31); }
template <typename T> __device__ __forceinline__ T* pin(T* p) {
    const unsigned long long v = (unsigned long long)p;
    return (T*)((unsigned long long)pin((uint32_t)v) | (unsigned long long)pin((uint32_t)(v >> 32)) << 32);
}
template <typename T> __device__ __forceinline__ T* opq(T* p) { asm volatile("" : "+l"(p)); return p; }
__device__ __forceinline__ float4 lds4f(uint32_t a) { float4 v; asm volatile("ld.shared.v4.f32 {%0,%1,%2,%3}, [%4];" : "=f"(v.x), "=f"(v.y), "=f"(v.z), "=f"(v.w) : "r"(a) : "memory"); return v; }
__device__ __forceinline__ float2 lds2f(uint32_t a) { float2 v; asm volatile("ld.shared.v2.f32 {%0,%1}, [%2];" : "=f"(v.x), "=f"(v.y) : "r"(a) : "memory"); return v; }
__device__ __forceinline__ void ln_stats(uint32_t st, float& mean, float& inv) {
    const float4 a = lds4f(st), b = lds4f(st + 16), c = lds4f(st + 32), d = lds4f(st + 48);
    const float s2 = ((a.x + a.z) + (b.x + b.z)) + ((c.x + c.z) + (d.x + d.z));
    const float md = (((a.y + a.w) + (b.y + b.w)) + ((c.y + c.w) + (d.y + d.w))) * (1.0f / DM);
    const float var = fmaxf(s2 * (1.0f / DM) - md * md, 0.f);
    mean = bfr(md);
    asm("rsqrt.approx.ftz.f32 %0, %1;" : "=f"(inv) : "f"(var + 1e-5f));
}
__device__ __forceinline__ void sts32(uint32_t a, float v) { asm volatile("st.shared.f32 [%0], %1;" ::"r"(a), "f"(v) : "memory"); }
__device__ __forceinline__ void sts32p(uint32_t a, float v, uint32_t off) {
    asm volatile("{\n.reg .pred p;\nsetp.eq.u32 p, %2, 0;\n@p st.shared.f32 [%0], %1;\n}" ::"r"(a), "f"(v), "r"(off) : "memory");
}
__device__ __forceinline__ void sts128p(uint32_t a, float x, float y, float z, float w, uint32_t off) {
    asm volatile("{\n.reg .pred p;\nsetp.eq.u32 p, %5, 0;\n@p st.shared.v4.f32 [%0], {%1,%2,%3,%4};\n}" ::"r"(a), "f"(x), "f"(y), "f"(z), "f"(w), "r"(off) : "memory");
}
__device__ __forceinline__ void sts64(uint32_t a, float v, float w) { asm volatile("st.shared.v2.f32 [%0], {%1,%2};" ::"r"(a), "f"(v), "f"(w) : "memory"); }

__device__ __forceinline__ uint32_t prmt(uint32_t a, uint32_t b, uint32_t s) { uint32_t r; asm("prmt.b32 %0, %1, %2, %3;" : "=r"(r) : "r"(a), "r"(b), "r"(s)); return r; }
__device__ __forceinline__ uint32_t bmul2(uint32_t a, uint32_t b) { uint32_t r; asm("mul.rn.bf16x2 %0, %1, %2;" : "=r"(r) : "r"(a), "r"(b)); return r; }
__device__ __forceinline__ void sts128(uint32_t addr, uint32_t a, uint32_t b, uint32_t c, uint32_t d) {
    asm volatile("st.shared.v4.u32 [%0], {%1,%2,%3,%4};" ::"r"(addr), "r"(a), "r"(b), "r"(c), "r"(d) : "memory");
}
__device__ __forceinline__ uint4 ldg128(const uint4* p) {
    uint4 v;
    asm volatile("ld.volatile.global.v4.u32 {%0,%1,%2,%3}, [%4];" : "=r"(v.x), "=r"(v.y), "=r"(v.z), "=r"(v.w) : "l"(p) : "memory");
    return v;
}
__device__ __forceinline__ uint32_t lds32(uint32_t a) { uint32_t v; asm volatile("ld.shared.u32 %0, [%1];" : "=r"(v) : "r"(a) : "memory"); return v; }
__device__ __forceinline__ uint32_t lds16(uint32_t a) { unsigned short v; asm volatile("ld.shared.u16 %0, [%1];" : "=h"(v) : "r"(a) : "memory"); return v; }
__device__ __forceinline__ void unpack8(uint32_t la, uint32_t lb, uint32_t c, uint32_t (&w)[4]) {
    const uint32_t ha = c & 0x87878787u, hb = __funnelshift_l(c, c, 4) & 0x87878787u;
    w[0] = prmt(la, ha, 0x5140); w[1] = prmt(la, ha, 0x7362); w[2] = prmt(lb, hb, 0x5140); w[3] = prmt(lb, hb, 0x7362);
}
__device__ __forceinline__ uint32_t bdiff2(uint32_t y, uint32_t inv, uint32_t x) {
    uint32_t r;
    asm("{\n.reg .b32 n;\nneg.bf16x2 n, %3;\nfma.rn.bf16x2 %0, %1, %2, n;\n}" : "=r"(r) : "r"(y), "r"(inv), "r"(x));
    return r;
}
__device__ __forceinline__ uint32_t pack_scale(uint32_t tile, int lane, uint32_t inv_addr) {
    uint32_t m = 0;
#pragma unroll 1
    for (int k = 0; k < 12; k++) {
        uint32_t a, b, c, d;
        lds128(tile + k * 512 + lane * 16, a, b, c, d);
        asm("max.xorsign.abs.bf16x2 %0, %0, %1;" : "+r"(a) : "r"(b));
        asm("max.xorsign.abs.bf16x2 %0, %0, %1;" : "+r"(c) : "r"(d));
        asm("max.xorsign.abs.bf16x2 %0, %0, %1;" : "+r"(a) : "r"(c));
        asm("max.xorsign.abs.bf16x2 %0, %0, %1;" : "+r"(m) : "r"(a));
    }
    m = __reduce_max_sync(0xffffffffu, max(m & 0x7fffu, (m >> 16) & 0x7fffu));
    const uint32_t inv = (112u + min((m + 0x28u) >> 7, 141u)) * 0x00800080u;
    if (lane == 0) asm volatile("st.shared.u32 [%0], %1;" ::"r"(inv_addr), "r"(inv) : "memory");
    return inv;
}

#define K_OFF(i) ((uint32_t)((3 * ((g >> 1) + 4 * (g & 1)) + ((i) >> 1)) * 128 + ((t ^ ((3 * ((g >> 1) + 4 * (g & 1)) + ((i) >> 1)) & 7) ^ (((i) & 1) << 2)) << 4)))
#define V_OFF(i) ((uint32_t)((6 * t + (i)) * 128 + ((g ^ ((6 * t + (i)) & 7)) << 4)))
template <bool ISV, typename DST>
__device__ __forceinline__ void pack_tile(uint32_t tile, int tau, int nm, uint32_t inv, uint32_t xl, int lane, DST dst) {
    const int g = lane >> 2, t = lane & 3;
    const uint32_t scl = 254u * 0x00800080u - inv;
#pragma unroll 1
    for (int m = 0; m < nm; m++) {
        const int row = ISV ? 6 * t + 2 * m : 3 * ((g >> 1) + 4 * (g & 1)) + m;
        const uint32_t a0 = tile + row * 128 + (((ISV ? g : t) ^ (row & 7)) << 4), a1 = ISV ? (a0 ^ 16) + 128 : a0 ^ 64;
        uint32_t l[8], cw[4], ck = 0, cd = 0;
#pragma unroll
        for (int r = 0; r < 4; r++) {
            uint32_t w0, w1, w2, w3;
            lds128(((r & 1) ? a1 : a0) + (r >> 1) * 3072, w0, w1, w2, w3);
            const uint32_t y0 = bmul2(w0, scl), y1 = bmul2(w1, scl), y2 = bmul2(w2, scl), y3 = bmul2(w3, scl);
            cd |= bdiff2(y0, inv, w0) | bdiff2(y1, inv, w1);
            cd |= bdiff2(y2, inv, w2) | bdiff2(y3, inv, w3);
            const uint32_t ha = prmt(y0, y1, 0x7531), hb = prmt(y2, y3, 0x7531);
            l[2 * r] = prmt(y0, y1, 0x6420); l[2 * r + 1] = prmt(y2, y3, 0x6420);
            asm("lop3.b32 %0, %1, 0x87878787, %2, 0xe2;" : "=r"(cw[r]) : "r"(ha), "r"(__funnelshift_r(hb, hb, 4)));
            ck |= ha | hb;
        }
        const uint32_t bad = __ballot_sync(0xffffffffu, (ck & 0x78787878u) | cd);
        if (bad) {
            const int src = __ffs(bad) - 1;
            const uint32_t b0 = __shfl_sync(0xffffffffu, a0, src), b1 = __shfl_sync(0xffffffffu, a1, src), n0 = lds32(xl);
            const uint32_t ax = ((lane & 8) ? b1 : b0) + (lane >> 4) * 3072 + 2 * (lane & 7), x = lds16(ax), y = bmul2(x, scl);
            const bool out = (y & 0x7800u) | bdiff2(y, inv, x);
            const uint32_t n = n0 + __popc(__ballot_sync(0xffffffffu, out) << (31 - lane)) - 1;
            if (out) {
                asm volatile("st.shared.u16 [%0], %1;" ::"r"(ax), "h"((unsigned short)0) : "memory");
                if (n < XCAP) sts32(xl + 16 + 4 * n, f_(x << 16 | tau << 12 | src << 7 | m << 5 | lane));
            }
            if (lane == 31) sts32(xl, f_(n + 1));
            __syncwarp();
            if (n0 <= XCAP) { m--; continue; }
        }
        uint32_t d[3] = {a0, a1, a0 + 3072};
        dst(m, d);
        sts128(d[0], l[0], l[1], l[2], l[3]);
        sts128(d[1], l[4], l[5], l[6], l[7]);
        sts128(d[2], cw[0], cw[1], cw[2], cw[3]);
    }
}

struct Maps { CUtensorMap k, v, wq, wo, w1, w3, w2, vr; const void* vp; const void* kp; uint32_t zero; };
#define RT_SEL ((wu & 1) ? RT_MASK2 : RT_MASK)
#define PFK 5
#define Q_AT 3
#define WO_T0 33200
#define K5D 370
#define PK_AT 6

__device__ __forceinline__ void load_ffn(const Maps& maps, int b, uint32_t dst, uint32_t bar) {
    const bool gu = b < NG;
    mbar_expect_tx(bar, gu ? 61440 : 49152);
    tma3d(dst, gu ? (b < NG / 2 ? &maps.w1 : &maps.w3) : &maps.w2, gu ? 48 * (b & (NG / 2 - 1)) : 16 * (b - DN0), 0, 0, bar, FFN_POL);
}

__device__ __forceinline__ void load_wo(const Maps& maps, uint32_t dst, int h, int c, uint32_t bar, int nbox) {
#pragma unroll 1
    for (int i = 0; i < nbox; i++) {
        if (!(i & 1)) mbar_expect_tx(bar + 4 * i, i + 1 < nbox ? 20480 : 10240);
        tma3d(dst + i * 10240, &maps.wo, 0, 5 * c, h * DH + 32 * i, bar + 4 * (i & 6), POL_EF);
    }
}

__global__ void __launch_bounds__(NT, 1)
decode_kernel(const __grid_constant__ Maps maps, const __nv_bfloat16* __restrict__ x_in, __nv_bfloat16* __restrict__ out) {
    extern __shared__ __align__(1024) unsigned char smem[];
    const int tid = threadIdx.x, warp = tid >> 5, lane = tid & 31;
    const int wu = __shfl_sync(0xffffffffu, tid >> 5, 0);
    const int b = blockIdx.x, h = b >> 2, c = b & 3;
    const uint32_t sb = smem_u32(smem);
    const uint32_t qbar = sb + SM_BAR + 16 * 8, fbar = qbar + 8, wbar = qbar + 16;
    uint32_t* xs32 = reinterpret_cast<uint32_t*>(smem + SM_XS);
    float* rr = reinterpret_cast<float*>(smem + SM_R);
    float* misc = reinterpret_cast<float*>(smem + SM_MISC);

    PROF_T(0);
    {
        uint2 xv = make_uint2(0u, 0u);
        const uint32_t t_start = now_ns();
        if (elect_one()) {
            const uint32_t rb = sb + SM_BAR + wu * 16, xb = sb + SM_XBAR + wu * 8;
            mbar_init(rb, 1); mbar_init(rb + 8, 1); mbar_init(xb, 1);
            if (wu == 0) mbar_init(qbar, 1);
            asm volatile("fence.mbarrier_init.release.cluster;" ::: "memory");
            const int row = (h * SK + (SK - WIN) + c * 1024 + wu * 128) * 3;
            const uint32_t ring = sb + SM_RING + wu * 2 * TILE;
#pragma unroll
            for (int n = 0; n < 3; n++) {
                const uint32_t bar = ((IN_S1 >> n) & 1) ? rb + 8 : ((IN_S0 >> n) & 1) ? rb : xb;
                mbar_expect_tx(bar, TILE);
                tma2d(((IN_S1 >> n) & 1) ? ring + TILE : ((IN_S0 >> n) & 1) ? ring : sb + SM_B + wu * TILE, &maps.k, 0, row + 48 * n, bar, POL_EF);
                if (n == 0 && wu == 0) {
                    mbar_expect_tx(qbar, 61440);
                    tma3d(sb + SM_Q, &maps.wq, 0, 160 * c, 3 * h, qbar, POL_EF);
                }
            }
            if (wu == 1) {
                mbar_init(fbar, 1);
#pragma unroll
                for (int i = 0; i < 3; i++) mbar_init(wbar + 8 * i, 1);
                asm volatile("fence.mbarrier_init.release.cluster;" ::: "memory");
            }
            if (wu >= 2) {
                const CUtensorMap* mp = wu == 2 ? &maps.v : wu == 3 ? &maps.wo : wu == 4 ? &maps.w1 : wu == 5 ? &maps.w3 : wu == 6 ? &maps.w2 : &maps.vr;
                asm volatile("prefetch.tensormap [%0];" ::"l"(mp) : "memory");
            }
        }
        if (tid < 160) asm volatile("ld.global.nc.v2.u32 {%0,%1}, [%2];" : "=r"(xv.x), "=r"(xv.y) : "l"(x_in + 4 * tid) : "memory");
        if (tid == 96) { misc[2] = 0.f; misc[3] = 0.f; }
        if (lane == 1) *reinterpret_cast<uint2*>(smem + SM_XL + warp * XSTR) = make_uint2(0u, t_start + WO_T0);
        if (tid >= 128 && tid < 148) {
            const uint32_t v = tid < 138 ? ONES : 0u;
            reinterpret_cast<uint4*>(smem + SM_ONE)[tid - 128] = make_uint4(v, v, v, v);
        }
        if (tid < 160) { xs32[xpos(2 * tid)] = xv.x; xs32[xpos(2 * tid + 1)] = xv.y; }
        __syncthreads();
        PROF_T(14);
        if (b == 0 && tid >= 232) asm volatile("st.relaxed.gpu.global.u32 [%0], %1;" ::"l"(g_scr.ticket + tid - 232), "r"(0) : "memory");
        if (tid == 64 || (tid == 65 && b < 216 - NCTA)) st_pkt(&g_scr.acc[1][(b + NCTA * (tid - 64)) * ACC_STR], 0, 0, 0, 0);
    }

    uint32_t kq[NQ][4];
    const float SC = 0.07216878364870322f * 1.4426950408889634f;

#pragma unroll 1
    for (int ph = 0; ph < 3; ph++) {
        const int layer = ph >> 1;
        const uint32_t tag = layer + 1;
        PROF_T(1 + layer * 16);
        if (ph) {
        {
            const int tl = opq(tid), warp = tl >> 5, lane = tl & 31, g = lane >> 2, t = lane & 3, mat = lane >> 3, r8 = lane & 7;
            const int kh = warp >> 2, mg = warp & 3;
            uint32_t aq[3];
#pragma unroll
            for (int i = 0; i < 3; i++) {
                const int ch = 6 * mg + 2 * i + (mat & 1);
                aq[i] = sb + SM_Q + (80 * kh + (mat >> 1) * 8 + r8) * 128 + (ch >> 3) * 20480 + (((ch & 7) ^ r8) << 4);
            }
#define PF_K5 if (layer == 1 && PFK) tile_keep(&maps.k, (h * SK + (SK - WIN) + c * 1024 + wu * 128 + PFK * 16) * 3);
            uint2 xv = make_uint2(0u, 0u);
            mbar_wait(qbar, 0);
            uint32_t pre[6][4];
#pragma unroll
            for (int n = 0; n < 6; n++) ldsm4t(aq[n % 3] + (n / 3) * 2048, pre[n]);
            if (layer == 1) {
                __syncthreads();
                if (elect_one()) {
                    const uint32_t bar = sb + SM_BAR + wu * 16;
                    asm volatile("mbarrier.expect_tx.relaxed.cta.shared::cta.b64 [%0], 1536;" ::"r"(bar) : "memory");
#pragma unroll
                    for (int k = 0; k < 3; k++)
                        tma2d(sb + SM_Q + v1_pos(3 * wu + k), &maps.vr, 0, (h * SK + (SK - WIN) + c * 1024 + wu * 128) / 2 + 8 + 2 * k, bar, POL_EF);
                }
            }
            const uint32_t pm = opq(g == 1 ? sb + SM_ONE : sb + SM_XS + 160 * (2 * c + kh) + 16 * t), pm2 = opq(pm + 128 - (g == 1 ? 0 : 8 * t));
            const uint32_t dq = opq(sb + SM_R + 8 * (kh * 192 + 48 * mg + g)), ds = opq(sb + SM_ST + 8 * warp + (lane < 16 ? 4 : 0));
            const bool wr = t == 0, ws = (lane & 15) == 0, lo = lane < 16;
            if (wu < 5) {
                const int p0 = xpos(2 * tl), p1 = xpos(2 * tl + 1);
                if (layer == 1) {
                    uint4 v;
                    for (int it = 0; it < SPIN_CAP; it++) { v = ld_pkt(&g_scr.ay[tl]); if (__all_sync(0xffffffffu, v.w == 1)) break; }
                    xv = make_uint2(v.x, v.y);
                    xs32[p0] = xv.x; xs32[p1] = xv.y;
                } else xv = make_uint2(xs32[p0], xs32[p1]);
            }
            if (layer) PC(24);
            __syncthreads();
            PF_K5
            if (layer) PC(25);
            PROF_T(13 + layer * 16);
            const float e0 = bf_lo(xv.x), e1 = bf_hi(xv.x), e2 = bf_lo(xv.y), e3 = bf_hi(xv.y);
            const float s1 = (e0 + e1) + (e2 + e3), s2 = (e0 * e0 + e1 * e1) + (e2 * e2 + e3 * e3);
            float sv = lo ? s1 : s2, cc[3][4];
            gemv15<2048>(cc, pre, [&](int i) { return aq[i]; }, pm, pm2, sv, lo ? s2 : s1);
            if (wr) {
#pragma unroll
                for (int i = 0; i < 3; i++) { sts64(dq + 128 * i, cc[i][0], cc[i][1]); sts64(dq + 128 * i + 64, cc[i][2], cc[i][3]); }
            }
            if (ws) sts32(ds, sv);
        }
        const uint32_t pa = opq(sb + SM_R + 32 * opq(tid)), st = opq(sb + SM_ST);
        uint4* const pq = opq(&g_scr.hx[b * 48 + opq(tid)]);
        if (layer) PC(26);
        __syncthreads();
        if (layer) PC(27);
        PROF_T(33 + layer * 16);
        if (wu < 2) {
            float mean, inv;
            ln_stats(st, mean, inv);
            const float4 a0 = lds4f(pa), a1 = lds4f(pa + 16), b0 = lds4f(pa + 1536), b1 = lds4f(pa + 1552);
            const float q0 = (a0.x + b0.x) - mean * (a0.y + b0.y), q1 = (a0.z + b0.z) - mean * (a0.w + b0.w);
            const float q2 = (a1.x + b1.x) - mean * (a1.y + b1.y), q3 = (a1.z + b1.z) - mean * (a1.w + b1.w);
            st_pktfp(pq, q0, q1, q2, q3, 1, tid < 48);
        }
        if (layer == 1 && tid >= 192 && tid < 194 && b < 108) st_pkt(&g_scr.acc[0][(2 * b + opq(tid) - 192) * ACC_STR], 0, 0, 0, 0);
        }
        if (layer) PC(28);
        if (layer == 1 && (wu & 2)) {
            idle(K5D);
#pragma unroll 1
            for (int w = wu; w >= (wu > 4 ? wu - 2 : wu); w -= 2)
                tile_load(sb + SM_Q + c_slot(w), &maps.k, (h * SK + (SK - WIN) + c * 1024 + w * 128 + 5 * 16) * 3, sb + SM_XBAR + w * 8, 0, 0);
        }

        float sc0 = -INFINITY, sc1 = -INFINITY, sc2 = 0.f, sc3 = 0.f, mw;
        uint32_t pk0, pk1;
        float acc[3][4];
        {
            const uint32_t ring = sb + SM_RING + wu * 2 * TILE, rb = sb + SM_BAR + wu * 16;
            const uint32_t xtile = sb + SM_Q + c_slot(wu), xb = sb + SM_XBAR + wu * 8;
#define V_SEQ(n) ((int)(SEQ1 >> (4 * (n))) & 7)
#define SLOT1(n) (((IN_S1 >> (n)) & 1) ? ring + TILE : ((IN_S0 >> (n)) & 1) ? ring : sb + SM_B + wu * TILE)
#define BAR1(n) (((IN_S1 >> (n)) & 1) ? rb + 8 : ((IN_S0 >> (n)) & 1) ? rb : xb)
#define PAR1(n) ((PARITY1 >> (n)) & 1)
#define PAR2(n) ((PARITY2 >> (n)) & 1)
            const int row0 = (h * SK + (SK - WIN) + c * 1024 + wu * 128) * 3;
            auto issue1 = [&](int n, uint32_t dep, bool vph = false) {
                const CUtensorMap* mp = n < 8 ? &maps.k : &maps.v;
                const int tl = V_SEQ(n), row = row0 + tl * 48;
                const uint32_t dst = SLOT1(n), bar = BAR1(n);
                if (vph && wu < L1R && tl == 7 - (wu & 1)) {
                    tile_load_l1(dst, maps.vp, row, bar, opq(tid) & 31);
                    return;
                }
                tile_load(dst, mp, row, bar, dep, maps.zero);
                if ((RT_SEL >> (tl + (n & 8))) & 1) {
                    if (n != V0_AT + 1) tile_keep(mp, row);
                    else if ((opq(tid) & 31) < 8)
                        asm volatile("cp.async.bulk.prefetch.L2.global.L2::cache_hint [%0], 256, %1;"
                                     ::"l"(static_cast<const char*>(maps.vp) + (size_t)(row + 4 + 6 * (opq(tid) & 31)) * 128), "l"(POL_EN) : "memory");
                }
            };
            auto refill1 = [&](int s, uint32_t dep, bool vph = false) { issue1(s + (!vph || s < V0_AT ? 3 : 2), dep, vph); };
#define LANE_IDS const int tl = opq(tid), lane = tl & 31, g = lane >> 2, t = lane & 3; (void)tl; (void)lane; (void)g; (void)t;
            const uint32_t xl = sb + SM_XL + wu * XSTR;
            if (layer == 0) {
#pragma unroll 1
                for (int s = ph ? Q_AT : 0; s < (ph ? 5 : Q_AT); s++) {
                    LANE_IDS
                    const uint32_t tile = SLOT1(s);
                    mbar_wait(BAR1(s), PAR1(s));
                    const uint32_t scl = s == 0 ? pack_scale(tile, lane, xl + 8) : lds32(xl + 8);
                    pack_tile<false>(tile, s, 3, scl, xl, lane, [](int, uint32_t (&)[3]) {});
#pragma unroll
                    for (int n = 0; n < 5; n++) {
                        if (s == n) {
#pragma unroll
                            for (int m = 0; m < 3; m++) {
                                const uint32_t a = tile + K_OFF(2 * m);
                                lds128(a, kq[9 * n + 3 * m][0], kq[9 * n + 3 * m][1], kq[9 * n + 3 * m][2], kq[9 * n + 3 * m][3]);
                                lds128(a ^ 64, kq[9 * n + 3 * m + 1][0], kq[9 * n + 3 * m + 1][1], kq[9 * n + 3 * m + 1][2], kq[9 * n + 3 * m + 1][3]);
                                lds128(a + 3072, kq[9 * n + 3 * m + 2][0], kq[9 * n + 3 * m + 2][1], kq[9 * n + 3 * m + 2][2], kq[9 * n + 3 * m + 2][3]);
                            }
                        }
                    }
                    __syncwarp();
                    refill1(s, lds32(tile));
                }
                if (!ph) continue;
            }
            {
                if (wu < 2) {
                    const int tl = min(opq(tid), 47);
                    const int w = 2 * tl;
                    const uint32_t pos = opq(sb + SM_QS + 4 * (((w >> 2) & 3) * 24 + 2 * (w >> 4) + ((w >> 1) & 1)));
                    uint4 v[4];
                    float mean, inv;
                    ln_stats(opq(sb + SM_ST), mean, inv);
                    for (int it = 0; it < SPIN_CAP; it++) {
#pragma unroll
                        for (int k = 0; k < 4; k++) v[k] = ld_pkt(&g_scr.hx[(h * 4 + k) * 48 + tl]);
                        if (all_odd(v[0].w, v[1].w, v[2].w, v[3].w)) break;
                    }
                    sts32(pos, f_(pack2(inv * ((f_(v[0].x) + f_(v[1].x)) + (f_(v[2].x) + f_(v[3].x))), inv * ((f_(v[0].y) + f_(v[1].y)) + (f_(v[2].y) + f_(v[3].y))))));
                    sts32(pos + 48, f_(pack2(inv * ((f_(v[0].z) + f_(v[1].z)) + (f_(v[2].z) + f_(v[3].z))), inv * ((f_(v[0].w) + f_(v[1].w)) + (f_(v[2].w) + f_(v[3].w))))));
                }
            }
            if (layer) PC(29);
            __syncthreads();
            if (layer) PC(30);
            PROF_T(2 + layer * 16);
#define V1_REST(p) ((p) < 6 ? sb + SM_Q + v1_pos(3 * wu + ((p) >> 1)) + 256 * ((p) & 1) : ((sb + SM_R + wu * 784 + 127) & ~127u) - 1536 + 256 * (p))
#define V1_LOAD(bar) if (elect_one()) tma2d(V1_REST(6), &maps.vr, 0, row0 / 6 + 14, bar, POL_EF);
#define V1_EXPECT(bar) { if ((opq(tid) & 31) == 0) asm volatile("mbarrier.expect_tx.relaxed.cta.shared::cta.b64 [%0], 512;" ::"r"(bar) : "memory"); }
            if (layer == 1 && wu < 2) tile_load(xtile, &maps.k, row0 + 5 * 48, xb, 0, 0);
            if (layer == 1 && wu >= 4) idle(STAG);
            {
                uint32_t qf[12];
                int t;
                {
                    const int lane = opq(tid) & 31;
                    t = lane & 3;
                    const uint32_t qa = sb + SM_QS + (2 * t + ((lane >> 2) & 1)) * 48;
#pragma unroll
                    for (int i = 0; i < 3; i++) lds128(qa + 16 * i, qf[4 * i], qf[4 * i + 1], qf[4 * i + 2], qf[4 * i + 3]);
                }
                const uint32_t sq = lds32(xl + 8) - 64u * 0x00800080u;
#pragma unroll
                for (int i = 0; i < 12; i++) qf[i] = bmul2(qf[i], sq);
#define KR_STEP(tau, m) \
                    _Pragma("unroll") for (int i = 2 * (m); i < 2 * (m) + 2; i++) { \
                        const int q0 = 9 * tau + 3 * (i >> 1), r = i & 1; \
                        uint32_t w[4]; \
                        unpack8(kq[q0][2 * r], kq[q0][2 * r + 1], kq[q0 + 2][r], w); \
                        mma16816(cA, w[0], w[1], w[2], w[3], qf[2 * i], qf[2 * i + 1]); \
                        unpack8(kq[q0 + 1][2 * r], kq[q0 + 1][2 * r + 1], kq[q0 + 2][2 + r], w); \
                        mma16816(cB, w[0], w[1], w[2], w[3], qf[2 * i], qf[2 * i + 1]); \
                    }
#define KR_BEGIN float cA[4] = {0.f, 0.f, 0.f, 0.f}, cB[4] = {0.f, 0.f, 0.f, 0.f};
#define KR_END(tau) \
                    const float sA = (cA[0] + cA[3]) * 18446744073709551616.f, sB = (cB[0] + cB[3]) * 18446744073709551616.f; \
                    if (t == (tau & 3)) { if (tau < 4) { sc0 = sA; sc1 = sB; } else { sc2 = sA; sc3 = sB; } }
#define KR_SCORES(tau) { KR_BEGIN KR_STEP(tau, 0) KR_STEP(tau, 1) KR_STEP(tau, 2) KR_END(tau) }
                uint32_t va[3];
                {
                    const int lane = opq(tid) & 31, g = lane >> 2, t = lane & 3;
#pragma unroll
                    for (int i = 0; i < 3; i++) va[i] = ring + V_OFF(2 * i);
                }
#define V_STG(n) _Pragma("unroll") for (int j = 3 * (n); j < 3 * (n) + 3; j++) { \
                    const int i = (j % 12) >> 1; \
                    lds128p(((i & 1) ? (va[i >> 1] ^ 16) + 128 : va[i >> 1]) + (j / 12) * TILE + (j & 1) * 3072, layer, kq[j][0], kq[j][1], kq[j][2], kq[j][3]); }
                uint32_t dep = 0;
                {
                    KR_BEGIN
                    KR_STEP(0, 0) V_STG(0) KR_STEP(0, 1) V_STG(1) KR_STEP(0, 2) V_STG(2)
                    KR_END(0)
                }
                {
                    KR_BEGIN
                    KR_STEP(1, 0) V_STG(3)
                    __syncwarp();
                    dep = lds32(ring);
                    if (layer == 1) tile_load(ring, &maps.k, row0 + 6 * 48, rb, dep, maps.zero);
                    KR_STEP(1, 1) V_STG(4) KR_STEP(1, 2) V_STG(5)
                    KR_END(1)
                }
                {
                    KR_BEGIN
                    KR_STEP(2, 0) V_STG(6) KR_STEP(2, 1) V_STG(7)
                    __syncwarp();
                    dep = lds32(ring + TILE);
                    KR_STEP(2, 2)
                    if (layer == 1) {
                        V1_EXPECT(rb + 8)
                        tile_load(ring + TILE, &maps.k, row0 + 7 * 48, rb + 8, dep, maps.zero);
                        V1_LOAD(rb + 8)
                    }
                    KR_END(2)
                }
#pragma unroll 1
                for (int s = 5; s < 8; s++) {
                    {
                        LANE_IDS
                        const uint32_t tile = !layer ? SLOT1(s) : s == 5 ? xtile : ring + (s - 6) * TILE, tb = !layer ? BAR1(s) : s == 5 ? xb : rb + (s - 6) * 8;
                        const float ur = f_((318u << 23) - (lds32(xl + 8) << 16));
                        mbar_wait(tb, layer ? PAR2(s - 5) : PAR1(s));
                        if (layer) PROF_T(29 + s);
                        float cA[4] = {0.f, 0.f, 0.f, 0.f}, cB[4] = {0.f, 0.f, 0.f, 0.f};
#pragma unroll
                        for (int i = 0; i < 6; i++) {
                            uint32_t a0, a1, a2, a3;
                            lds128(tile + K_OFF(i), a0, a1, a2, a3);
                            mma16816(cA, a0, a1, a2, a3, qf[2 * i], qf[2 * i + 1]);
                            lds128(tile + K_OFF(i) + 3072, a0, a1, a2, a3);
                            mma16816(cB, a0, a1, a2, a3, qf[2 * i], qf[2 * i + 1]);
                        }
                        __syncwarp();
                        const uint32_t last = lds32(tile);
                        if (layer) tile_load(tile, &maps.v, row0 + (s - 2) * 48, tb, last, maps.zero);
                        else refill1(s, last);
                        if (t == (s & 3)) { sc2 = (cA[0] + cA[3]) * ur; sc3 = (cB[0] + cB[3]) * ur; }
                    }
                    if (s == 5) KR_SCORES(3)
                    if (s == 6) {
                        KR_SCORES(4)
                        const int lane = opq(tid) & 31;
                        const uint32_t nx = min(lds32(xl), (uint32_t)XCAP);
#pragma unroll 1
                        for (uint32_t n = 0; n < nx; n++) {
                            const uint32_t id = lds32(xl + 16 + 4 * n);
                            const uint32_t qo = 96 * ((id >> 7) & 3) + 48 * ((id >> 1) & 1) + 16 * ((id >> 5) & 3) + (id & 12) + 2 * (id & 1);
                            const float cr = bf_hi(id) * f_(lds16(sb + SM_QS + qo) << 16);
                            const int d = (int)(16 * ((id >> 9) & 7) + 4 * ((id >> 12) & 3) + ((id >> 13) & 2) + ((id >> 4) & 1) + ((id >> 8) & 128)) - 4 * lane;
                            if (d == 0) sc0 += cr;
                            if (d == 1) sc1 += cr;
                            if (d == 2) sc2 += cr;
                            if (d == 3) sc3 += cr;
                        }
                    }
                }
#undef KR_SCORES
#undef KR_STEP
#undef KR_BEGIN
#undef KR_END
#undef V_STG
                {
                    LANE_IDS
                    if (lds32(xl) > XCAP || !__all_sync(0xffffffffu, (fabsf(sc0) + fabsf(sc1)) + (fabsf(sc2) + fabsf(sc3)) < INFINITY)) {
                        const uint32_t qa = sb + SM_QS + (2 * t + (g & 1)) * 48;
#pragma unroll
                        for (int i = 0; i < 3; i++) lds128(qa + 16 * i, qf[4 * i], qf[4 * i + 1], qf[4 * i + 2], qf[4 * i + 3]);
                        const uint4* kg = reinterpret_cast<const uint4*>(static_cast<const char*>(maps.kp) + (size_t)row0 * 128) + ((g >> 1) + 4 * (g & 1)) * 24 + t;
#pragma unroll 1
                        for (int s = 0; s < 8; s++) {
                            float cA[4] = {0.f, 0.f, 0.f, 0.f}, cB[4] = {0.f, 0.f, 0.f, 0.f};
#pragma unroll
                            for (int i = 0; i < 6; i++) {
                                uint4 u = ldg128(kg + s * 384 + 4 * i);
                                mma16816v(cA, u.x, u.y, u.z, u.w, qf[2 * i], qf[2 * i + 1]);
                                u = ldg128(kg + s * 384 + 4 * i + 192);
                                mma16816v(cB, u.x, u.y, u.z, u.w, qf[2 * i], qf[2 * i + 1]);
                            }
                            if (t == s) { sc0 = cA[0] + cA[3]; sc1 = cB[0] + cB[3]; }
                            if (t + 4 == s) { sc2 = cA[0] + cA[3]; sc3 = cB[0] + cB[3]; }
                        }
                    }
                }
            }
            mw = warp_max(fmaxf(fmaxf(sc0, sc1), fmaxf(sc2, sc3)));
            pk0 = pack2(ex2((sc0 - mw) * SC), ex2((sc1 - mw) * SC));
            pk1 = pack2(ex2((sc2 - mw) * SC), ex2((sc3 - mw) * SC));
            sc2 = (bf_lo(pk0) + bf_hi(pk0)) + (bf_lo(pk1) + bf_hi(pk1));
            sc2 = (float)__reduce_add_sync(0xffffffffu, __float2uint_rn(sc2 * 16777216.f)) * (1.0f / 16777216.f);
            if ((opq(tid) & 31) == 0) st_pkt2(&g_scr.mx[h * 32 + c * 8 + wu], __float_as_uint(mw), (__float_as_uint(sc2) & ~3u) | tag);
            auto head_factor = [&]() {
                const int lane = opq(tid) & 31;
                int it = 0;
                while (!__all_sync(0xffffffffu, (__float_as_uint(sc1) & 3u) == tag) && ++it < SPIN_CAP) {
                    const uint2 mv = ld_pkt2(&g_scr.mx[h * 32 + lane]); sc0 = f_(mv.x); sc1 = f_(mv.y);
                }
                const float e = ex2((sc0 - warp_max(sc0)) * SC);
                const uint32_t d = __reduce_add_sync(0xffffffffu, __float2uint_rn(sc1 * e * 524288.f));
                sc3 = __shfl_sync(0xffffffffu, e, c * 8 + wu) * 524288.f * rcp((float)d);
            };
#pragma unroll
            for (int s = 0; s < 3; s++) { acc[s][0] = acc[s][1] = acc[s][2] = acc[s][3] = 0.f; }
#define P_CONSTS \
                const uint32_t sel0 = g == 0 ? 0x4410u : (g == 1 ? 0x1044u : 0x4444u); \
                const uint32_t sel1 = g == 2 ? 0x4410u : (g == 3 ? 0x1044u : 0x4444u); \
                const int src00 = 4 * (t < 2 ? 4 * t : 4 * (t - 2) + 1);
#define P_FRAGS(tau) \
                const uint32_t pk = ((tau) & 4) ? pk1 : pk0; \
                const uint32_t w0 = __shfl_sync(0xffffffffu, pk, src00 + ((tau) & 3)); \
                const uint32_t w1 = __shfl_sync(0xffffffffu, pk, src00 + ((tau) & 3) + 8); \
                uint32_t pb[4][2]; \
                _Pragma("unroll") for (int j = 0; j < 4; j++) { \
                    const uint32_t src = ((j & 1) ? w1 : w0) >> ((j >> 1) * 16); \
                    pb[j][0] = __byte_perm(src, 0, sel0); pb[j][1] = __byte_perm(src, 0, sel1); \
                }
            if (layer == 0) {
#pragma unroll 1
                for (int s = 8; s < 16; s++) {
                    LANE_IDS
                    P_CONSTS
                    if (s == 13) { const uint2 mv = ld_pkt2(&g_scr.mx[h * 32 + lane]); sc0 = f_(mv.x); sc1 = f_(mv.y); }
                    P_FRAGS(V_SEQ(s))
                    mbar_wait(BAR1(s), PAR1(s));
                    const uint32_t tile = SLOT1(s);
#pragma unroll
                    for (int j = 0; j < 4; j++) {
#pragma unroll
                        for (int u = 0; u < 3; u++) {
                            uint32_t a0, a1, a2, a3;
                            lds128(tile + (j >> 1) * 3072 + V_OFF(3 * (j & 1) + u), a0, a1, a2, a3);
                            mma16816(acc[u], a0, a1, a2, a3, pb[j][0], pb[j][1]);

                        }
                    }
                    __syncwarp();
                    if (s < V0_AT || (s > V0_AT + 1 && s < 14)) refill1(s, lds32(tile), true);
                    if (s == V0_AT || s == V0_AT + 1) {
                        {
                            const uint32_t ar = sb + SM_R + wu * 784 + 32 * g + 16 * t;
                            if (t < 2) {
#pragma unroll
                                for (int u = 0; u < 3; u++) sts128(ar + 256 * u, __float_as_uint(acc[u][0]), __float_as_uint(acc[u][1]), __float_as_uint(acc[u][2]), __float_as_uint(acc[u][3]));
                            }
                        }
                        const uint32_t scl = s == V0_AT ? pack_scale(tile, lane, xl + 12) : lds32(xl + 12);
                        pack_tile<true>(tile, s + 8 - V0_AT, V0_AT + 3 - s, scl, xl, lane, [&](int m, uint32_t (&d)[3]) {
                            if (s != V0_AT && m == 0) {
#pragma unroll
                                for (int k = 0; k < 3; k++) d[k] = ring + 3072 + V_OFF(2 * k + 1);
                            }
                        });
                        if (s != V0_AT) {
                            lds128(tile + V_OFF(2), kq[45][0], kq[45][1], kq[45][2], kq[45][3]);
                            lds128(tile + V_OFF(3), kq[46][0], kq[46][1], kq[46][2], kq[46][3]);
                            lds128(tile + V_OFF(2) + 3072, kq[47][0], kq[47][1], kq[47][2], kq[47][3]);
                            __syncwarp();
                            issue1(V0_AT + 3, lds32(tile));
                        }
                        const int ln = opq(tid) & 31;
                        const uint32_t ar = sb + SM_R + wu * 784 + 8 * (ln & 28) + 16 * (ln & 1);
#pragma unroll
                        for (int u = 0; u < 3; u++) {
                            uint32_t a0, a1, a2, a3;
                            lds128(ar + 256 * u, a0, a1, a2, a3);
                            acc[u][0] = f_(a0); acc[u][1] = f_(a1); acc[u][2] = f_(a2); acc[u][3] = f_(a3);
                        }
                    }
                    if (s == 13) head_factor();
                    if (s >= 14 && elect_one()) {
                        if (atomicAdd(reinterpret_cast<unsigned*>(misc + 3), 1u) == 14u && (int)(now_ns() - lds32(xl + 4)) >= 0) {
                            PROF_X(47);
                            load_wo(maps, sb + SM_B, h, c, wbar, 6);
                            atomicAdd(reinterpret_cast<unsigned*>(misc + 3), 256u);
                        }
                    }
                }
            } else {
                LANE_IDS
                P_CONSTS
#pragma unroll
                for (int k = 0; k < 4; k++) lds128(V1_REST(t + 4 * (k >> 1)) + 16 * g + 128 * (k & 1), kq[36 + k][0], kq[36 + k][1], kq[36 + k][2], kq[36 + k][3]);
#pragma unroll 1
                for (int i = 3; i < 8; i++) {
                    const uint32_t tile = i > 3 ? ring + (i & 1) * TILE : xtile, tb = i > 3 ? rb + (i & 1) * 8 : xb;
                    if (i == 6) { const uint2 mv = ld_pkt2(&g_scr.mx[h * 32 + lane]); sc0 = f_(mv.x); sc1 = f_(mv.y); }
                    if (i == 7) head_factor();
                    if (i == PK_AT) {
                uint32_t nx, nk, ik, iv;
                lds128(xl, nx, nk, ik, iv);
                if (nx <= XCAP) {
                    const uint32_t pks = bmul2(pk0, iv);
#pragma unroll
                    for (int s = 0; s < 2; s++) {
                        const uint32_t pk1 = 0, pk0 = pks;
                        P_FRAGS(s)
#pragma unroll
                        for (int j = 0; j < 4; j++) {
#pragma unroll
                            for (int u = 0; u < 3; u++) {
                                const int i = 3 * (j & 1) + u, m = i >> 1, r = i & 1, hf = j >> 1;
                                if (s == 1 && m == 2) continue;
                                const int ql = s == 0 ? 4 * m + 2 * hf : m == 0 ? 3 + 4 * hf : 45 + hf, qc = s == 0 ? 4 * m + 1 : m == 0 ? 11 : 47;
                                uint32_t w[4];
                                unpack8(kq[ql][2 * r], kq[ql][2 * r + 1], kq[qc][2 * hf + r], w);
                                mma16816(acc[u], w[0], w[1], w[2], w[3], pb[j][0], pb[j][1]);
                            }
                        }
                    }
#pragma unroll 1
                    for (uint32_t n = 0; n < nx; n++) {
                        const uint32_t id = lds32(xl + 16 + 4 * n);
                        const int i = ((id >> 4) & 6) + ((id >> 3) & 1), key = ((id >> 6) & 6) + (i >= 3);
                        const uint32_t pw = __shfl_sync(0xffffffffu, pk0, 8 * (key & 3) + (key & 4) + ((id >> 12) & 3));
                        const float cr = bf_hi(id) * ((id & 16) ? bf_hi(pw) : bf_lo(pw));
                        const int d = (int)(64 * ((id >> 9) & 7) + 4 * (id & 4) + 4 * (i >= 3 ? i - 3 : i) + (id & 3) + ((~id >> 5) & 1024)) - 16 * lane;
#pragma unroll
                        for (int k = 0; k < 12; k++) if (d == k) acc[k >> 2][k & 3] += cr;
                    }
                } else {
                    const uint4* vg = reinterpret_cast<const uint4*>(static_cast<const char*>(maps.vp) + (size_t)row0 * 128) + 48 * t + g;
#pragma unroll 1
                    for (int s = 0; s < 2; s++) {
                        P_FRAGS(s)
#pragma unroll
                        for (int j = 0; j < 4; j++) {
#pragma unroll
                            for (int u = 0; u < 3; u++) {
                                if (s == 1 && (j & 1) && u) continue;
                                const uint4 w = ldg128(vg + 384 * s + 192 * (j >> 1) + 24 * (j & 1) + 8 * u);
                                mma16816v(acc[u], w.x, w.y, w.z, w.w, pb[j][0], pb[j][1]);
                            }
                        }
                    }
                }
#pragma unroll
                for (int s = 2; s > 0; s--) {
                    P_FRAGS(s)
#pragma unroll
                    for (int j = 0; j < 4; j++) {
#pragma unroll
                        for (int u = 0; u < 3; u++) {
                            if (s == 1 && !((j & 1) && u)) continue;
                            const int k = s == 2 ? 12 + 2 * (3 * (j & 1) + u) + (j >> 1) : 35 + (j >> 1) * 2 + u;
                            mma16816(acc[u], kq[k][0], kq[k][1], kq[k][2], kq[k][3], pb[j][0], pb[j][1]);
                        }
                    }
                }
                    }
                    P_FRAGS(i)
                    mbar_wait(tb, PAR2(i));
                    PROF_T(34 + i);
#pragma unroll
                    for (int k = 0; k < 6; k++) {
                        const uint32_t a = tile + V_OFF(k);
                        lds128(a, kq[24 + k][0], kq[24 + k][1], kq[24 + k][2], kq[24 + k][3]);
                        lds128(a + 3072, kq[30 + k][0], kq[30 + k][1], kq[30 + k][2], kq[30 + k][3]);
                    }
#pragma unroll
                    for (int j = 0; j < 4; j++) {
#pragma unroll
                        for (int u = 0; u < 3; u++) {
                            const int k = 24 + 6 * (j >> 1) + 3 * (j & 1) + u;
                            mma16816(acc[u], kq[k][0], kq[k][1], kq[k][2], kq[k][3], pb[j][0], pb[j][1]);
                        }
                    }
                    __syncwarp();
                    if (wu < L1R && i == 5 - (wu & 1)) tile_load_l1(tile, maps.vp, row0 + (i + 2) * 48, tb, lane);
                    else if (i == 4 || i == 5) tile_load(tile, &maps.v, row0 + (i + 2) * 48, tb, lds32(tile), maps.zero);
                    if (i == WO_AT1 && HAS_FFN && elect_one()) {
                        if (atomicAdd(reinterpret_cast<unsigned*>(misc + 2), 1u) == 7u) {
                            PROF_X(63);
                            load_wo(maps, sb + SM_Q, h, c, wbar, KEEP4 && __float_as_uint(misc[1]) >= DN0 ? 5 : 6);
                        }
                    }
                }
            }
#undef P_FRAGS
#undef P_CONSTS
#undef LANE_IDS
        }
        PROF_T(3 + layer * 16);
        PC(layer * 32 + 1);

        {
            const int lane = opq(tid) & 31;
            const uint32_t a = sb + SM_R + wu * 784 + 8 * (lane & 28) + 16 * (lane & 1);
#pragma unroll
            for (int u = 0; u < 3; u++) sts128p(a + 256 * u, acc[u][0] * sc3, acc[u][1] * sc3, acc[u][2] * sc3, acc[u][3] * sc3, lane & 2);
        }
        const uint32_t role1 = layer ? lds32(sb + SM_MISC + 4) : DN0 + NDN;
        const uint32_t pc = opq(sb + SM_R + 16 * opq(tid));
        uint4* const px0 = opq(&g_scr.hx[b * 48 + opq(tid)]);
        __syncthreads();
        PROF_T(4 + layer * 16);
        PC(layer * 32 + 2);
        float4 o = make_float4(0.f, 0.f, 0.f, 0.f);
        if (wu < 2) {
            float4 v[8];
#pragma unroll
            for (int w = 0; w < 8; w++) v[w] = lds4f(pc + w * 784);
            o.x = ((v[0].x + v[1].x) + (v[2].x + v[3].x)) + ((v[4].x + v[5].x) + (v[6].x + v[7].x));
            o.y = ((v[0].y + v[1].y) + (v[2].y + v[3].y)) + ((v[4].y + v[5].y) + (v[6].y + v[7].y));
            o.z = ((v[0].z + v[1].z) + (v[2].z + v[3].z)) + ((v[4].z + v[5].z) + (v[6].z + v[7].z));
            o.w = ((v[0].w + v[1].w) + (v[2].w + v[3].w)) + ((v[4].w + v[5].w) + (v[6].w + v[7].w));
            o.w = f_(__float_as_uint(o.w) & ~1u);
            st_pktp(px0, __float_as_uint(o.x), __float_as_uint(o.y), __float_as_uint(o.z), __float_as_uint(o.w), threadIdx.x < 48);
        }
        uint32_t ticket = 0;
        if (layer == 0 && tid == 224)
            asm volatile("atom.relaxed.gpu.global.inc.u32 %0, [%1], 0x7fffffff;" : "=r"(ticket) : "l"(g_scr.ticket + 8 + (b >> 3)) : "memory");
        if (layer == 0 && tid == 224 && lds32(sb + SM_MISC + 12) < 256u) {
            int it = 0;
            while ((int)(now_ns() - lds32(sb + SM_XL + 4)) < 0 && ++it < SPIN_CAP) {}
            PROF_X(47);
            load_wo(maps, sb + SM_B, h, c, wbar, 6);
        }
        uint32_t pr;
        uint4* pacc;
        {
            const int tid = opq(threadIdx.x), warp = tid >> 5, lane = tid & 31, g = lane >> 2, t = lane & 3, mat = lane >> 3, r8 = lane & 7;
            const int kg = warp >> 1, mg = warp & 1;
            const bool wo2 = role1 < DN0 + NDN;
            const uint32_t aw2 = 40960 + (wo2 && KEEP4 && role1 >= DN0 && kg >= 2 ? SM_B - SM_Q : 0);
            uint32_t aw[5];
#pragma unroll
            for (int i = 0; i < 5; i++) {
                const uint32_t lin = ((mat >> 1) * 8 + r8) * 320 + 64 * i + 32 * mg + 16 * (mat & 1);
                aw[i] = sb + (wo2 ? SM_Q : SM_B) + 5120 * kg + (lin ^ ((lin >> 3) & 48));
            }
#define CXE 0
            const uint32_t ao = pin(sb + SM_OS + 96 * kg + 16 * t), dw = pin(sb + SM_R + 16 * (16 * mg + g) + 4 * kg);
            pr = pin(sb + SM_R + 48 * tid); pacc = pin(&g_scr.acc[layer][(54 * c + tid) * ACC_STR]);
            const int w = 2 * min(tid, 47);
            const uint32_t d0 = pin(sb + SM_OS + 4 * (24 * ((w >> 3) & 3) + ((w >> 2) & 1) + (w < 64 ? 4 * (w & 3) + 2 * (w >> 5) : 16 + 2 * (w & 3))));
            const uint32_t d1 = pin(d0 + (w < 64 ? 16 : 8));
            const uint4* pp[3];
#pragma unroll
            for (int k = 0; k < 3; k++) pp[k] = pin(&g_scr.hx[(h * 4 + ((c + 1 + k) & 3)) * 48 + min(tid, 47)]);
            bool ok = true;
            if ((PRE1 & 8) && layer) {
#pragma unroll
                for (int ks = 0; ks < 3; ks++) {
                    mbar_wait(wbar + 8 * ks, wo2);
#pragma unroll
                    for (int i = 0; i < 5; i++) ldsm4t(aw[i] + (ks == 2 ? aw2 : 20480 * ks), kq[3 * i + ks]);
                    if (ks == CXE && wu < 2) {
#pragma unroll
                        for (int k = 0; k < 3; k++) { const uint4 v = ld_pkt(pp[k]); kq[20 + k][0] = v.x; kq[20 + k][1] = v.y; kq[20 + k][2] = v.z; kq[20 + k][3] = v.w; }
                    }
                }
                PROF_T(50);
                if (CXE < 3 && wu < 2) {
                    ok = any_odd(kq[20][3], kq[21][3], kq[22][3]);
                    if (!ok) {
#pragma unroll
                        for (int k = 0; k < 3; k++) { o.x += f_(kq[20 + k][0]); o.y += f_(kq[20 + k][1]); o.z += f_(kq[20 + k][2]); o.w += f_(kq[20 + k][3]); }
                    }
                }
            }
            if (wu < 2) {
                if (ok) {
                    uint4 v3[3];
                    int it = 0;
                    do {
#pragma unroll
                        for (int k = 0; k < 3; k++) v3[k] = ld_pkt(pp[k]);
                        ok = any_odd(v3[0].w, v3[1].w, v3[2].w);
                    } while (ok && ++it < SPIN_CAP);
#pragma unroll
                    for (int k = 0; k < 3; k++) { o.x += f_(v3[k].x); o.y += f_(v3[k].y); o.z += f_(v3[k].z); o.w += f_(v3[k].w); }
                }
                sts32p(d0, f_(pack2(o.x, o.y)), tid >= 48);
                sts32p(d1, f_(pack2(o.z, o.w)), tid >= 48);
            }
            PC(layer * 32 + 3);
            __syncthreads();
            PROF_T(5 + layer * 16);
            PC(layer * 32 + 5);
            if (tid == 224 && layer == 0) {
                if (ticket >= 6 + ((b >> 3) & 1)) ticket = DN0 + NDN;
                else asm volatile("atom.relaxed.gpu.global.inc.u32 %0, [%1], 0x7fffffff;" : "=r"(ticket) : "l"(g_scr.ticket) : "memory");
            }
            uint32_t ob[6];
            lds128(ao, ob[0], ob[1], ob[2], ob[3]);
            lds64(ao + 64 - 8 * t, ob[4], ob[5]);
            float cc[5][4];
#pragma unroll
            for (int i = 0; i < 5; i++) cc[i][0] = cc[i][1] = cc[i][2] = cc[i][3] = 0.f;
            if ((PRE1 & 8) && layer) {
#pragma unroll
                for (int ks = 0; ks < 3; ks++) {
#pragma unroll
                    for (int i = 0; i < 5; i++) mma16816(cc[i], kq[3 * i + ks][0], kq[3 * i + ks][1], kq[3 * i + ks][2], kq[3 * i + ks][3], ob[2 * ks], ob[2 * ks + 1]);
                }
            } else {
#pragma unroll
                for (int ks = 0; ks < 3; ks++) {
                    mbar_wait(wbar + 8 * ks, wo2);
                    if (ks == 2) { PC(layer * 32 + 4); PROF_T(48 + layer * 2); }
                    uint32_t a[5][4];
#pragma unroll
                    for (int i = 0; i < 5; i++) ldsm4t(aw[i] + (ks == 2 ? aw2 : 20480 * ks), a[i]);
#pragma unroll
                    for (int i = 0; i < 5; i++) mma16816(cc[i], a[i][0], a[i][1], a[i][2], a[i][3], ob[2 * ks], ob[2 * ks + 1]);
                }
            }
            if (t == 0) {
#pragma unroll
                for (int i = 0; i < 5; i++) { sts32(dw + 512 * i, cc[i][0]); sts32(dw + 512 * i + 128, cc[i][2]); }
            }
        }
        PC(layer * 32 + 6);
        __syncthreads();
        PROF_T(6 + layer * 16);
        PC(layer * 32 + 7);
        if (tid < 54) {
            const float4 v0 = lds4f(pr), v1 = lds4f(pr + 16), v2 = lds4f(pr + 32);
            const float y0 = (v0.x + v0.y) + (v0.z + v0.w), y1 = (v1.x + v1.y) + (v1.z + v1.w), y2 = (v2.x + v2.y) + (v2.z + v2.w);
            red_pkt(pacc, y0, tid == 53 ? 0.f : y1, tid == 53 ? 0.f : y2);
        }
        if (tid == 224 && layer == 0) {
            misc[1] = __uint_as_float(ticket);
            if (ticket < DN0 + NDN && (ticket < NG || !DNTH)) load_ffn(maps, ticket, sb + SM_B, fbar);
        }
        PROF_T(7 + layer * 16);
        PC(layer * 32 + 8);
        __syncthreads();
        const int role = (int)__float_as_uint(misc[1]);
        PC(layer * 32 + 9);
        const uint32_t fbase = sb + SM_B;
        const uint32_t DONE32 = 0x42000000u;
        if (role < NG) {
            const int tid = opq(threadIdx.x), warp = tid >> 5, lane = tid & 31, g = lane >> 2, t = lane & 3, mat = lane >> 3, r8 = lane & 7;
            const uint32_t ag = fbase + (80 * warp + (mat >> 1) * 8 + r8) * 96 + (((mat & 1) ^ (r8 >> 2)) << 4);
            constexpr int GI = 32, GK = 16 * 96;
            const bool on = (g & 1) == (t >> 1), isx = on && g < 2;
            const uint32_t pm = opq(isx ? sb + SM_XS + 160 * warp + 16 * t : sb + (on ? SM_ONE : SM_ZERO)), pm2 = opq(pm + 128 - (isx ? 8 * t : 0));
            const uint32_t dg = opq(sb + SM_R + 4 * (2 * (warp * 48 + g) + t)), ds = opq(sb + SM_ST + 8 * warp + (lane < 16 ? 4 : 0));
            const bool ws = (lane & 15) == 0, lo = lane < 16;
            uint32_t pre[6][4];
            float s1 = 0.f, s2 = 0.f;
            {
                bool hx = wu == 7;
                int it = 0;
                const uint4* px = &g_scr.acc[layer][min(tid, 215) * ACC_STR];
                const int cq = tid / 54, r = tid - 54 * cq, k0 = min(160 * cq + 3 * r, DM - 1);
                const uint32_t w0 = sb + SM_XS + 4 * xpos(k0 >> 1), w1 = sb + SM_XS + 4 * xpos(min((k0 >> 1) + 1, DM / 2 - 1));
                const uint32_t e0 = w0 + 2 * (k0 & 1), e1 = (k0 & 1) ? w1 : w0 + 2, e2 = w1 + 2 * (k0 & 1);
                                auto sts16 = [](uint32_t a, uint32_t x, bool on) {
                    asm volatile("{\n.reg .pred p;\nsetp.ne.u32 p, %2, 0;\n@p st.shared.u16 [%0], %1;\n}" ::"r"(a), "h"((unsigned short)x), "r"((uint32_t)on) : "memory");
                };
                const bool on0 = tid < 216, on1 = on0 && r != 53;
                const float x0 = on0 ? f_(lds16(e0) << 16) : 0.f, x1 = on1 ? f_(lds16(e1) << 16) : 0.f, x2 = on1 ? f_(lds16(e2) << 16) : 0.f;
                auto take_x = [&](const uint4 v) {
                    if (__all_sync(0xffffffffu, v.w == DONE32)) {
                        hx = true;
                        const uint32_t a = pack2(f_(v.x), f_(v.y)), p = pack2(x0 + bf_lo(a), x1 + bf_hi(a)), q = pack2(x2 + bfr(f_(v.z)), 0.f);
                        sts16(e0, p, on0); sts16(e1, p >> 16, on1); sts16(e2, q, on1);
                        const float y0 = on0 ? bf_lo(p) : 0.f, y1 = on0 ? bf_hi(p) : 0.f, y2 = on0 ? bf_lo(q) : 0.f;
                        s1 = y0 + (y1 + y2); s2 = y0 * y0 + (y1 * y1 + y2 * y2);
                    }
                };
                auto try_x = [&]() { take_x(ld_pkt(px)); };
                while (!mbar_test(fbar, 0) && ++it < SPIN_CAP) { if (!hx) try_x(); }
                uint4 v0 = make_uint4(0u, 0u, 0u, 0u);
                if ((PRE1 & 4) && !hx) v0 = ld_pkt(px);
#pragma unroll
                for (int n = 0; n < 6; n++) ldsm4t(ag + (n % 3) * GI + (n / 3) * GK, pre[n]);
                if ((PRE1 & 1) && layer) {
#pragma unroll
                    for (int n = 6; n < 15; n++) ldsm4t(ag + (n % 3) * GI + (n / 3) * GK, kq[n - 6]);
                }
                if ((PRE1 & 4) && !hx) take_x(v0);
                PC(layer * 32 + 10);
                while (!hx && ++it < SPIN_CAP) try_x();
                PC(layer * 32 + 11);
            __syncthreads();
            PC(layer * 32 + 12);
            PROF_T(9 + layer * 16);
            float sv = lo ? s1 : s2, cc[3][4];
            if ((PRE1 & 1) && layer) gemv15r(cc, pre, kq, pm, pm2, sv, lo ? s2 : s1);
            else gemv15<GK>(cc, pre, [&](int i) { return ag + i * GI; }, pm, pm2, sv, lo ? s2 : s1);
#pragma unroll
            for (int i = 0; i < 3; i++) { sts32p(dg + 128 * i, cc[i][0] + cc[i][3], t & 2); sts32p(dg + 128 * i + 64, cc[i][1] + cc[i][2], t & 2); }
            if (ws) sts32(ds, sv);
            const uint32_t pg = opq(sb + SM_R + 8 * (24 * warp + (lane < 24 ? lane : 0))), st = opq(sb + SM_ST);
            uint4* const ph = opq(lane < 24 && lane % 6 == 0 ? &g_scr.ah[role * 8 + 4 * warp + lane / 6] : nullptr);
            PC(layer * 32 + 13);
            __syncthreads();
            PC(layer * 32 + 14);
            PROF_T(43 + layer * 16);
            if (wu < 2) {
                float mean, inv;
                ln_stats(st, mean, inv);
                float2 v[8];
#pragma unroll
                for (int w = 0; w < 8; w++) v[w] = lds2f(pg + w * 384);
                const float gx = ((v[0].x + v[1].x) + (v[2].x + v[3].x)) + ((v[4].x + v[5].x) + (v[6].x + v[7].x));
                const float gs = ((v[0].y + v[1].y) + (v[2].y + v[3].y)) + ((v[4].y + v[5].y) + (v[6].y + v[7].y));
                float ga = inv * (gx - mean * gs);
                if (role < NG / 2) { ga = bfr(ga); ga *= rcp(1.0f + ex2(-1.4426950408889634f * ga)); }
                const uint32_t wd = pack2(ga, __shfl_down_sync(0xffffffffu, ga, 1));
                const uint32_t wa = __shfl_down_sync(0xffffffffu, wd, 2), wb = __shfl_down_sync(0xffffffffu, wd, 4);
                if (ph) st_pkt(ph, wd, wa, wb, tag);
            }
            if (HOLD & 2) __syncthreads();
            }
            PROF_T(10 + layer * 16);
            PC(layer * 32 + 15);
        } else if (role < DN0 + NDN) {
            const int j = role - DN0;
            const int tid = opq(threadIdx.x), warp = tid >> 5, lane = tid & 31, g = lane >> 2, t = lane & 3, mat = lane >> 3, r8 = lane & 7;
            float xres = 0.f;
            uint32_t xr0 = 0, xr1 = 0;
            if (wu == 0) {
                const int col = 16 * j + (lane & 15), cc = col / 160, r = col - 160 * cc, e = r % 3;
                const uint4* px = &g_scr.acc[layer][(54 * cc + r / 3) * ACC_STR];
                const float x0 = __bfloat162float(reinterpret_cast<const __nv_bfloat16*>(xs32)[2 * xpos(col >> 1) + (col & 1)]);
                uint4 v;
                int it = 0;
                bool ld = DNTH && layer == 0;
                do {
                    v = ld_pkt(px);
                    if (ld && f_(__shfl_sync(0xffffffffu, v.w, 0)) >= (float)DNTH) { ld = false; if (lane == 0) load_ffn(maps, role, sb + SM_B, fbar); }
                } while (!__all_sync(0xffffffffu, v.w == DONE32) && ++it < SPIN_CAP);
                if (ld && lane == 0) load_ffn(maps, role, sb + SM_B, fbar);
                xres = x0 + bfr(f_(e == 0 ? v.x : (e == 1 ? v.y : v.z)));
                const int p4 = 4 * (lane & 3);
                xr0 = pack2(__shfl_sync(0xffffffffu, xres, p4), __shfl_sync(0xffffffffu, xres, p4 + 1));
                xr1 = pack2(__shfl_sync(0xffffffffu, xres, p4 + 2), __shfl_sync(0xffffffffu, xres, p4 + 3));
            }
            PC(layer * 32 + 17);
            PROF_T(9 + layer * 16);
            const uint32_t ad = fbase + (192 * warp + (mat >> 1) * 8 + r8) * 32 + (((mat & 1) ^ (r8 >> 2)) << 4);
            uint32_t* hs = reinterpret_cast<uint32_t*>(rr) + warp * 96;
            uint32_t pre[NPRE][4];
            {
                uint32_t pos[3];
#pragma unroll
                for (int i = 0; i < 3; i++) { const int w = 3 * lane + i; pos[i] = pin(sb + SM_R + 384 * warp + 4 * ((w & ~15) + 4 * (w & 3) + ((w >> 2) & 1) + ((w >> 2) & 2))); }
                uint4 v = make_uint4(0u, 0u, 0u, 0u), u = v;
                if (layer == 0) { v = ld_pkt(&g_scr.ah[tid]); u = ld_pkt(&g_scr.ah[256 + tid]); }
                mbar_wait(fbar, 0);
#pragma unroll
                for (int n = 0; n < NPRE; n++) ldsm4t(ad + n * 512, pre[n]);
                if ((PRE1 & 2) && layer) {
#pragma unroll
                    for (int n = NPRE; n < 12; n++) ldsm4t(ad + n * 512, kq[12 + n]);
                }
                PC(layer * 32 + 18);
                int it = 0;
                for (; any_ne(v.w, u.w, tag) && it < SPIN_CAP; it++) { v = ld_pkt(&g_scr.ah[tid]); u = ld_pkt(&g_scr.ah[256 + tid]); }
                PC(layer * 32 + 19);
                sts32(pos[0], f_(bmul2(v.x, u.x))); sts32(pos[1], f_(bmul2(v.y, u.y))); sts32(pos[2], f_(bmul2(v.z, u.z)));
            __syncwarp();
            PROF_T(11 + layer * 16);
            PC(layer * 32 + 20);
            float ca[4] = {0.f, 0.f, 0.f, 0.f}, cb[4] = {0.f, 0.f, 0.f, 0.f};
            if ((PRE1 & 2) && layer) {
                float cc[4] = {0.f, 0.f, 0.f, 0.f}, cd[4] = {0.f, 0.f, 0.f, 0.f};
#pragma unroll
                for (int jj = 0; jj < 6; jj++) {
                    const uint4 hv = *reinterpret_cast<const uint4*>(hs + 16 * jj + 4 * t);
                    const uint32_t (&f0)[4] = 2 * jj < NPRE ? pre[2 * jj < NPRE ? 2 * jj : 0] : kq[12 + 2 * jj];
                    const uint32_t (&f1)[4] = 2 * jj + 1 < NPRE ? pre[2 * jj + 1 < NPRE ? 2 * jj + 1 : 0] : kq[13 + 2 * jj];
                    if (jj & 1) { mma16816(cc, f0[0], f0[1], f0[2], f0[3], hv.x, hv.y); mma16816(cd, f1[0], f1[1], f1[2], f1[3], hv.z, hv.w); }
                    else { mma16816(ca, f0[0], f0[1], f0[2], f0[3], hv.x, hv.y); mma16816(cb, f1[0], f1[1], f1[2], f1[3], hv.z, hv.w); }
                }
#pragma unroll
                for (int e = 0; e < 4; e++) { ca[e] += cc[e]; cb[e] += cd[e]; }
            } else {
#pragma unroll
                for (int jj = 0; jj < 6; jj++) {
                    const uint4 hv = *reinterpret_cast<const uint4*>(hs + 16 * jj + 4 * t);
                    uint32_t a[4];
                    if (2 * jj < NPRE) { a[0] = pre[2 * jj][0]; a[1] = pre[2 * jj][1]; a[2] = pre[2 * jj][2]; a[3] = pre[2 * jj][3]; }
                    else ldsm4t(ad + 2 * jj * 512, a);
                    mma16816(ca, a[0], a[1], a[2], a[3], hv.x, hv.y);
                    if (2 * jj + 1 < NPRE) { a[0] = pre[2 * jj + 1][0]; a[1] = pre[2 * jj + 1][1]; a[2] = pre[2 * jj + 1][2]; a[3] = pre[2 * jj + 1][3]; }
                    else ldsm4t(ad + (2 * jj + 1) * 512, a);
                    mma16816(cb, a[0], a[1], a[2], a[3], hv.z, hv.w);
                }
            }
            if (t == 0) { rr[768 + warp * 16 + g] = ca[0] + cb[0]; rr[768 + warp * 16 + 8 + g] = ca[2] + cb[2]; }
            const uint32_t pd = opq(sb + SM_R + 3072 + 16 * (lane & 3));
            uint4* const py = opq(&g_scr.ay[j * 4 + lane]);
            uint2* const po = opq(reinterpret_cast<uint2*>(out + 16 * j) + lane);
            PC(layer * 32 + 21);
            __syncthreads();
            PC(layer * 32 + 22);
            if (wu == 0) {
                float4 p[8];
#pragma unroll
                for (int w = 0; w < 8; w++) p[w] = lds4f(pd + 64 * w);
                const uint32_t y0 = pack2(((p[0].x + p[1].x) + (p[2].x + p[3].x)) + ((p[4].x + p[5].x) + (p[6].x + p[7].x)),
                                          ((p[0].y + p[1].y) + (p[2].y + p[3].y)) + ((p[4].y + p[5].y) + (p[6].y + p[7].y)));
                const uint32_t y1 = pack2(((p[0].z + p[1].z) + (p[2].z + p[3].z)) + ((p[4].z + p[5].z) + (p[6].z + p[7].z)),
                                          ((p[0].w + p[1].w) + (p[2].w + p[3].w)) + ((p[4].w + p[5].w) + (p[6].w + p[7].w)));
                uint32_t wd, wn;
                asm("add.rn.bf16x2 %0, %1, %2;" : "=r"(wd) : "r"(xr0), "r"(y0));
                asm("add.rn.bf16x2 %0, %1, %2;" : "=r"(wn) : "r"(xr1), "r"(y1));
                asm volatile("{\n.reg .pred p;\nsetp.ne.u32 p, %3, 0;\n@p st.global.v2.u32 [%0], {%1,%2};\n}" ::"l"(po), "r"(wd), "r"(wn), "r"((uint32_t)(layer && tid < 4)) : "memory");
                st_pktp(py, wd, wn, 0, tag, tid < 4);
            }
            if (HOLD & 1) __syncthreads();
            }
            PROF_T(12 + layer * 16);
            PC(layer * 32 + 23);
        }
    }
}

typedef CUresult (*EncodeFn)(CUtensorMap*, CUtensorMapDataType, cuuint32_t, void*, const cuuint64_t*, const cuuint64_t*, const cuuint32_t*,
                             const cuuint32_t*, CUtensorMapInterleave, CUtensorMapSwizzle, CUtensorMapL2promotion, CUtensorMapFloatOOBfill);

void make_map(EncodeFn enc, CUtensorMap* m, const void* base, int rank, uint64_t d0, uint64_t d1, uint64_t d2, uint64_t s1, uint64_t s2,
              uint32_t b0, uint32_t b1, uint32_t b2, CUtensorMapSwizzle sw, CUtensorMapL2promotion pr = CU_TENSOR_MAP_L2_PROMOTION_NONE) {
    cuuint64_t dims[3] = {d0, d1, d2};
    cuuint64_t strides[2] = {s1, s2};
    cuuint32_t box[3] = {b0, b1, b2};
    cuuint32_t es[3] = {1, 1, 1};
    enc(m, CU_TENSOR_MAP_DATA_TYPE_BFLOAT16, rank, const_cast<void*>(base), dims, strides, box, es, CU_TENSOR_MAP_INTERLEAVE_NONE, sw,
        pr, CU_TENSOR_MAP_FLOAT_OOB_FILL_NONE);
}

}

extern "C" void kernel_launch(void* const* d_in, const int* in_sizes, int n_in, void* d_out, int out_size) {
    (void)in_sizes; (void)n_in; (void)out_size;
    static EncodeFn enc = nullptr;
    if (!enc) {
        void* fn = nullptr;
        cudaDriverEntryPointQueryResult qr;
        cudaGetDriverEntryPoint("cuTensorMapEncodeTiled", &fn, cudaEnableDefault, &qr);
        enc = reinterpret_cast<EncodeFn>(fn);
        cudaFuncSetAttribute(decode_kernel, cudaFuncAttributeMaxDynamicSharedMemorySize, SM_TOTAL);
    }
    Maps maps;
    make_map(enc, &maps.k, d_in[1], 2, 64, (uint64_t)NH * SK * 3, 1, 128, 0, 64, 48, 1, CU_TENSOR_MAP_SWIZZLE_128B);
    make_map(enc, &maps.v, d_in[2], 2, 64, (uint64_t)NH * SK * 3, 1, 128, 0, 64, 48, 1, CU_TENSOR_MAP_SWIZZLE_128B);
    make_map(enc, &maps.wq, d_in[3], 3, 64, DM, NH * DH / 64, NH * DH * 2, 128, 64, 160, 3, CU_TENSOR_MAP_SWIZZLE_128B);
    make_map(enc, &maps.wo, d_in[4], 3, 32, DM / 32, NH * DH, 64, DM * 2, 32, 5, 32, CU_TENSOR_MAP_SWIZZLE_64B);
    make_map(enc, &maps.vr, (const char*)d_in[2] + 512, 2, 128, (uint64_t)NH * SK / 2, 1, 768, 0, 128, 2, 1, CU_TENSOR_MAP_SWIZZLE_NONE);
    constexpr int GW = 48;
    make_map(enc, &maps.w1, d_in[6], 3, FF, 160, 4, FF * 2, 160 * FF * 2, GW, 160, 4, CU_TENSOR_MAP_SWIZZLE_NONE, FFN_PROMO);
    make_map(enc, &maps.w3, d_in[7], 3, FF, 160, 4, FF * 2, 160 * FF * 2, GW, 160, 4, CU_TENSOR_MAP_SWIZZLE_NONE, FFN_PROMO);
    make_map(enc, &maps.w2, d_in[8], 3, DM, 256, 6, DM * 2, 256 * DM * 2, 16, 256, 6, CU_TENSOR_MAP_SWIZZLE_32B, FFN_PROMO);
    maps.vp = d_in[2];
    maps.kp = d_in[1];
    maps.zero = 0;
    decode_kernel<<<NCTA, NT, SM_TOTAL, cudaStreamPerThread>>>(maps, (const __nv_bfloat16*)d_in[0], (__nv_bfloat16*)d_out);
}
```

```cpp
#include <cuda_runtime.h>
#include <cuda_bf16.h>
#include <cuda.h>
#include <stdint.h>
#include <math.h>

namespace {

constexpr int DM = 640;
constexpr int NH = 32;
constexpr int DH = 192;
constexpr int SK = 32768;
constexpr int WIN = 4096;
constexpr int FF = 1536;
constexpr int NCTA = 128;
constexpr int NT = 256;
constexpr int TILE = 6144;
constexpr int NG = 64;
constexpr int DN0 = 64;
constexpr int NDN = 40;

constexpr int SM_RING = 0;
constexpr int SM_B = 8 * 2 * TILE;
constexpr int SM_Q = SM_B + 61440;
__host__ __device__ constexpr int c_slot(int w) { return w < 2 ? 4096 + 10240 * w : 12288 + 6144 * w; }
__host__ __device__ constexpr int v1_pos(int n) { return 10240 * (n >> 3) + 512 * (n & 7); }
constexpr int SM_XS = SM_Q + 61440;
constexpr int SM_R = SM_XS + 1280;
constexpr int SM_ST = SM_R + 4096;
constexpr int SM_QS = SM_R + 6272;
constexpr int SM_OS = SM_QS + 384;
constexpr int SM_BAR = SM_OS + 384;
constexpr int SM_XBAR = SM_BAR + 24 * 8;
constexpr int SM_MISC = SM_XBAR + 8 * 8;
constexpr int SM_ONE = SM_MISC + 16;
constexpr int SM_ZERO = SM_ONE + 160;
constexpr int XCAP = 48;
constexpr int XSTR = 16 + 4 * XCAP;
constexpr int SM_XL = SM_ZERO + 160;
constexpr int SM_TOTAL = SM_XL + 8 * XSTR;
static_assert(SM_TOTAL <= 232448, "shared memory");

constexpr unsigned long long POL_EF = 0x12F0000000000000ull;
constexpr unsigned long long POL_EN = 0x16F0000000000000ull;

#define RT_MASK 0xF2E0u
#define RT_MASK2 0xEAE0u
#define WO_AT1 5
#define FFN_PROMO CU_TENSOR_MAP_L2_PROMOTION_NONE
#define FFN_POL POL_EF
#define HAS_FFN (__float_as_uint(misc[1]) < DN0 + NDN)
#define ACC_STR 1
#define NPRE 6

#define STAG 200
#define L1R 3
#define PRE1 13
#define HOLD 2
#define DNTH 23
constexpr int V0_AT = 8;
constexpr unsigned long long SEQ1 = 0x2765431076543210ull;
constexpr uint32_t IN_S1 = 0xAA49, IN_S0 = 0x124, PARITY1 = 0x6638, PARITY2 = 0xCE;
#define KEEP4 1
constexpr int NQ = 48;
constexpr int SPIN_CAP = 1 << 19;
constexpr uint32_t ONES = 0x3F803F80u;

struct alignas(1024) Scratch {
    uint4 hx[NCTA * 48];
    uint4 pad0[32 * 5 * 32 + 160];
    uint4 acc[2][216 * 8];
    uint4 ay[160];
    uint4 ah[NG * 8];
    uint2 mx[NH * 32];
    uint32_t ticket[32];
    uint32_t pad1[32];
};
__device__ Scratch g_scr;
#define PROF_T(i)
#define PROF_X(i)
#define PC(i)

__device__ __forceinline__ uint32_t smem_u32(const void* p) { return (uint32_t)__cvta_generic_to_shared(p); }
__device__ __forceinline__ void mbar_init(uint32_t bar, uint32_t cnt) {
    asm volatile("mbarrier.init.shared::cta.b64 [%0], %1;" ::"r"(bar), "r"(cnt) : "memory");
}
__device__ __forceinline__ void mbar_expect_tx(uint32_t bar, uint32_t bytes) {
    asm volatile("mbarrier.arrive.expect_tx.shared::cta.b64 _, [%0], %1;" ::"r"(bar), "r"(bytes) : "memory");
}
__device__ __forceinline__ bool mbar_test(uint32_t bar, uint32_t parity) {
    uint32_t done;
    asm volatile("{\n.reg .pred p;\nmbarrier.try_wait.parity.shared::cta.b64 p, [%1], %2;\nselp.u32 %0, 1, 0, p;\n}"
                 : "=r"(done) : "r"(bar), "r"(parity) : "memory");
    return done;
}
__device__ __forceinline__ void mbar_wait(uint32_t bar, uint32_t parity) {
    int it = 0;
    while (!mbar_test(bar, parity) && ++it < SPIN_CAP) {}
}
__device__ __forceinline__ void tma2d(uint32_t dst, const CUtensorMap* map, int c0, int c1, uint32_t bar, unsigned long long pol) {
    asm volatile("cp.async.bulk.tensor.2d.shared::cluster.global.mbarrier::complete_tx::bytes.L2::cache_hint [%0], [%1, {%3, %4}], [%2], %5;"
                 ::"r"(dst), "l"(map), "r"(bar), "r"(c0), "r"(c1), "l"(pol) : "memory");
}
__device__ __forceinline__ void tma3d(uint32_t dst, const CUtensorMap* map, int c0, int c1, int c2, uint32_t bar, unsigned long long pol) {
    asm volatile("cp.async.bulk.tensor.3d.shared::cluster.global.mbarrier::complete_tx::bytes.L2::cache_hint [%0], [%1, {%3, %4, %5}], [%2], %6;"
                 ::"r"(dst), "l"(map), "r"(bar), "r"(c0), "r"(c1), "r"(c2), "l"(pol) : "memory");
}
__device__ __forceinline__ void tile_load(uint32_t dst, const CUtensorMap* map, int row, uint32_t bar, uint32_t dep, uint32_t zero) {
    asm volatile("{\n.reg .pred p;\n.reg .b32 n;\nmad.lo.u32 n, %5, %6, 6144;\nelect.sync _|p, 0xffffffff;\n"
                 "@p mbarrier.arrive.expect_tx.shared::cta.b64 _, [%2], n;\n"
                 "@p cp.async.bulk.tensor.2d.shared::cluster.global.mbarrier::complete_tx::bytes.L2::cache_hint [%0], [%1, {0, %3}], [%2], %4;\n}"
                 ::"r"(dst), "l"(map), "r"(bar), "r"(row), "l"(POL_EF), "r"(dep), "r"(zero) : "memory");
}
__device__ __forceinline__ void tile_keep(const CUtensorMap* map, int row) {
    asm volatile("{\n.reg .pred p;\nelect.sync _|p, 0xffffffff;\n"
                 "@p cp.async.bulk.prefetch.tensor.2d.L2.global.L2::cache_hint [%0, {0, %1}], %2;\n}"
                 ::"l"(map), "r"(row), "l"(POL_EN) : "memory");
}
__device__ __forceinline__ void tile_load_l1(uint32_t dst, const void* base, int row, uint32_t bar, int lane) {
    const char* g = static_cast<const char*>(base) + (size_t)row * 128 + lane * 16;
    const uint32_t s0 = dst + (lane >> 3) * 128 + (((lane & 7) ^ (lane >> 3)) << 4), s1 = s0 ^ 64;
#pragma unroll
    for (int k = 0; k < 12; k++)
        asm volatile("cp.async.ca.shared.global.L2::cache_hint [%0], [%1], 16, %2;" ::"r"(((k & 1) ? s1 : s0) + k * 512), "l"(g + k * 512), "l"(POL_EF) : "memory");
    asm volatile("cp.async.mbarrier.arrive.shared::cta.b64 [%0];" ::"r"(bar) : "memory");
    __syncwarp();
    if (lane == 0) asm volatile("mbarrier.arrive.shared::cta.b64 _, [%0];" ::"r"(bar) : "memory");
}
__device__ __forceinline__ bool elect_one() {
    uint32_t p;
    asm volatile("{\n.reg .pred p;\nelect.sync _|p, 0xffffffff;\nselp.u32 %0, 1, 0, p;\n}" : "=r"(p));
    return p;
}
__device__ __forceinline__ void lds128(uint32_t addr, uint32_t& a, uint32_t& b, uint32_t& c, uint32_t& d) {
    asm volatile("ld.shared.v4.u32 {%0,%1,%2,%3}, [%4];" : "=r"(a), "=r"(b), "=r"(c), "=r"(d) : "r"(addr) : "memory");
}
__device__ __forceinline__ void lds128p(uint32_t addr, uint32_t on, uint32_t& a, uint32_t& b, uint32_t& c, uint32_t& d) {
    asm volatile("{\n.reg .pred p;\nsetp.ne.u32 p, %5, 0;\n@p ld.shared.v4.u32 {%0,%1,%2,%3}, [%4];\n}" : "+r"(a), "+r"(b), "+r"(c), "+r"(d) : "r"(addr), "r"(on) : "memory");
}
__device__ __forceinline__ void lds64(uint32_t addr, uint32_t& a, uint32_t& b) {
    asm volatile("ld.shared.v2.u32 {%0,%1}, [%2];" : "=r"(a), "=r"(b) : "r"(addr) : "memory");
}
__device__ __forceinline__ void ldsm4t(uint32_t addr, uint32_t (&a)[4]) {
    asm volatile("ldmatrix.sync.aligned.m8n8.x4.trans.shared.b16 {%0,%1,%2,%3}, [%4];" : "=r"(a[0]), "=r"(a[1]), "=r"(a[2]), "=r"(a[3]) : "r"(addr) : "memory");
}
__device__ __forceinline__ void mma16816(float (&c)[4], uint32_t a0, uint32_t a1, uint32_t a2, uint32_t a3, uint32_t b0, uint32_t b1) {
    asm("mma.sync.aligned.m16n8k16.row.col.f32.bf16.bf16.f32 {%0,%1,%2,%3}, {%4,%5,%6,%7}, {%8,%9}, {%0,%1,%2,%3};"
        : "+f"(c[0]), "+f"(c[1]), "+f"(c[2]), "+f"(c[3]) : "r"(a0), "r"(a1), "r"(a2), "r"(a3), "r"(b0), "r"(b1));
}
__device__ __forceinline__ void mma16816v(float (&c)[4], uint32_t a0, uint32_t a1, uint32_t a2, uint32_t a3, uint32_t b0, uint32_t b1) {
    asm volatile("mma.sync.aligned.m16n8k16.row.col.f32.bf16.bf16.f32 {%0,%1,%2,%3}, {%4,%5,%6,%7}, {%8,%9}, {%0,%1,%2,%3};"
        : "+f"(c[0]), "+f"(c[1]), "+f"(c[2]), "+f"(c[3]) : "r"(a0), "r"(a1), "r"(a2), "r"(a3), "r"(b0), "r"(b1));
}
__device__ __forceinline__ int xpos(int w) {
    const int seg = w / 40, r = w - 40 * seg;
    return 40 * seg + (r < 32 ? (r & 16) + 4 * (r & 3) + ((r >> 2) & 3) : 32 + 2 * (r & 3) + ((r >> 2) & 1));
}
#define NA_LD ""
#define NA_ST ""
__device__ __forceinline__ void st_pkt(uint4* p, uint32_t a, uint32_t b, uint32_t c, uint32_t d) {
    asm volatile("{\n.reg .b128 t;\n.reg .b64 lo, hi;\nmov.b64 lo, {%1,%2};\nmov.b64 hi, {%3,%4};\nmov.b128 t, {lo,hi};\nst.relaxed.gpu.global" NA_ST ".b128 [%0], t;\n}"
                 ::"l"(p), "r"(a), "r"(b), "r"(c), "r"(d) : "memory");
}
__device__ __forceinline__ void red_pkt(uint4* p, float a, float b, float c) {
    asm volatile("red.relaxed.gpu.global.add.v4.f32 [%0], {%1,%2,%3,%4};" ::"l"(p), "f"(a), "f"(b), "f"(c), "f"(1.0f) : "memory");
}
__device__ __forceinline__ void st_pktp(uint4* p, uint32_t a, uint32_t b, uint32_t c, uint32_t d, bool on) {
    asm volatile("{\n.reg .pred p;\n.reg .b128 t;\n.reg .b64 lo, hi;\nsetp.ne.u32 p, %5, 0;\nmov.b64 lo, {%1,%2};\nmov.b64 hi, {%3,%4};\nmov.b128 t, {lo,hi};\n"
                 "@p st.relaxed.gpu.global.b128 [%0], t;\n}" ::"l"(p), "r"(a), "r"(b), "r"(c), "r"(d), "r"((uint32_t)on) : "memory");
}
__device__ __forceinline__ void st_pktfp(uint4* p, float a, float b, float c, float d, uint32_t bit, bool on) {
    st_pktp(p, __float_as_uint(a), __float_as_uint(b), __float_as_uint(c), (__float_as_uint(d) & ~1u) | bit, on);
}
__device__ __forceinline__ uint4 ld_pkt(const uint4* p) {
    uint4 v;
    asm volatile("{\n.reg .b128 t;\n.reg .b64 lo, hi;\nld.relaxed.gpu.global" NA_LD ".b128 t, [%4];\nmov.b128 {lo,hi}, t;\nmov.b64 {%0,%1}, lo;\nmov.b64 {%2,%3}, hi;\n}"
                 : "=r"(v.x), "=r"(v.y), "=r"(v.z), "=r"(v.w) : "l"(p) : "memory");
    return v;
}
__device__ __forceinline__ bool all_odd(uint32_t a, uint32_t b, uint32_t c, uint32_t d) {
    uint32_t r;
    asm volatile("{\n.reg .pred p, q, t;\n.reg .b32 x;\nsetp.eq.b32 t, 0, 0;\nlop3.b32 x, %1, %2, %3, 0x80;\nlop3.and.b32 _|p, x, %4, 1, 0x80, t;\n"
                 "vote.sync.all.pred q, p, 0xffffffff;\nselp.u32 %0, 1, 0, q;\n}" : "=r"(r) : "r"(a), "r"(b), "r"(c), "r"(d));
    return r;
}
__device__ __forceinline__ bool any_odd(uint32_t a, uint32_t b, uint32_t c) {
    uint32_t r;
    asm volatile("{\n.reg .pred p, q, t;\n.reg .b32 x;\nsetp.eq.b32 t, 0, 0;\nlop3.b32 x, %1, %2, %3, 0xFE;\nlop3.and.b32 _|p, x, 1, 0, 0xC0, t;\n"
                 "vote.sync.any.pred q, p, 0xffffffff;\nselp.u32 %0, 1, 0, q;\n}" : "=r"(r) : "r"(a), "r"(b), "r"(c));
    return r;
}
__device__ __forceinline__ bool any_ne(uint32_t a, uint32_t b, uint32_t c) {
    uint32_t r;
    asm volatile("{\n.reg .pred p, q, t;\nsetp.eq.b32 t, 0, 0;\nlop3.and.b32 _|p, %1, %2, %3, 0x7E, t;\n"
                 "vote.sync.any.pred q, p, 0xffffffff;\nselp.u32 %0, 1, 0, q;\n}" : "=r"(r) : "r"(a), "r"(b), "r"(c));
    return r;
}
__device__ __forceinline__ uint2 ld_pkt2(const uint2* p) {
    unsigned long long v;
    asm volatile("ld.relaxed.gpu.global" NA_LD ".b64 %0, [%1];" : "=l"(v) : "l"(p) : "memory");
    return make_uint2((uint32_t)v, (uint32_t)(v >> 32));
}
__device__ __forceinline__ void st_pkt2(uint2* p, uint32_t a, uint32_t b) {
    asm volatile("st.relaxed.gpu.global" NA_ST ".b64 [%0], %1;" ::"l"(p), "l"((unsigned long long)a | ((unsigned long long)b << 32)) : "memory");
}
__device__ __forceinline__ float ex2(float x) { float y; asm("ex2.approx.ftz.f32 %0, %1;" : "=f"(y) : "f"(x)); return y; }
__device__ __forceinline__ float rcp(float x) { float y; asm("rcp.approx.ftz.f32 %0, %1;" : "=f"(y) : "f"(x)); return y; }
__device__ __forceinline__ uint32_t pack2(float lo, float hi) {
    uint32_t r; asm("cvt.rn.bf16x2.f32 %0, %1, %2;" : "=r"(r) : "f"(hi), "f"(lo)); return r;
}
__device__ __forceinline__ float bf_lo(uint32_t w) { return __uint_as_float(w << 16); }
__device__ __forceinline__ float bf_hi(uint32_t w) { return __uint_as_float(w & 0xffff0000u); }
__device__ __forceinline__ float bfr(float x) { return bf_lo(pack2(x, 0.f)); }
__device__ __forceinline__ float f_(uint32_t u) { return __uint_as_float(u); }

template <int SK, typename AddrF>
__device__ __forceinline__ void gemv15(float (&cc)[3][4], uint32_t (&pre)[6][4], AddrF ad, uint32_t px, uint32_t px2, float& sv, float so) {
    uint32_t x0[4], x1[4], a[3][4];
    asm volatile("ld.shared.v4.u32 {%0,%1,%2,%3}, [%20];\nld.shared.v4.u32 {%4,%5,%6,%7}, [%20+64];\n"
                 "ldmatrix.sync.aligned.m8n8.x4.trans.shared.b16 {%8,%9,%10,%11}, [%21];\n"
                 "ldmatrix.sync.aligned.m8n8.x4.trans.shared.b16 {%12,%13,%14,%15}, [%22];\n"
                 "ldmatrix.sync.aligned.m8n8.x4.trans.shared.b16 {%16,%17,%18,%19}, [%23];\nbar.warp.sync 0xffffffff;"
                 : "=r"(x0[0]), "=r"(x0[1]), "=r"(x0[2]), "=r"(x0[3]), "=r"(x1[0]), "=r"(x1[1]), "=r"(x1[2]), "=r"(x1[3]),
                   "=r"(a[0][0]), "=r"(a[0][1]), "=r"(a[0][2]), "=r"(a[0][3]), "=r"(a[1][0]), "=r"(a[1][1]), "=r"(a[1][2]), "=r"(a[1][3]),
                   "=r"(a[2][0]), "=r"(a[2][1]), "=r"(a[2][2]), "=r"(a[2][3])
                 : "r"(px), "r"(ad(0) + 2 * SK), "r"(ad(1) + 2 * SK), "r"(ad(2) + 2 * SK) : "memory");
    __syncwarp();
    sv += __shfl_xor_sync(0xffffffffu, so, 16);
#pragma unroll
    for (int i = 0; i < 3; i++) {
        cc[i][0] = cc[i][1] = cc[i][2] = cc[i][3] = 0.f;
        mma16816v(cc[i], pre[i][0], pre[i][1], pre[i][2], pre[i][3], x0[0], x0[1]);
    }
    sv += __shfl_xor_sync(0xffffffffu, sv, 8);
#pragma unroll
    for (int i = 0; i < 3; i++) {
        mma16816v(cc[i], pre[3 + i][0], pre[3 + i][1], pre[3 + i][2], pre[3 + i][3], x0[2], x0[3]);
        ldsm4t(ad(i) + 3 * SK, pre[i]);
    }
    lds64(px2, x0[0], x0[1]);
    __syncwarp();
    sv += __shfl_xor_sync(0xffffffffu, sv, 4);
#pragma unroll
    for (int i = 0; i < 3; i++) {
        mma16816v(cc[i], a[i][0], a[i][1], a[i][2], a[i][3], x1[0], x1[1]);
        ldsm4t(ad(i) + 4 * SK, pre[3 + i]);
    }
    __syncwarp();
    sv += __shfl_xor_sync(0xffffffffu, sv, 2);
#pragma unroll
    for (int i = 0; i < 3; i++) mma16816v(cc[i], pre[i][0], pre[i][1], pre[i][2], pre[i][3], x1[2], x1[3]);
    sv += __shfl_xor_sync(0xffffffffu, sv, 1);
#pragma unroll
    for (int i = 0; i < 3; i++) mma16816v(cc[i], pre[3 + i][0], pre[3 + i][1], pre[3 + i][2], pre[3 + i][3], x0[0], x0[1]);
}
__device__ __forceinline__ void gemv15r(float (&cc)[3][4], const uint32_t (&pre)[6][4], const uint32_t (&ext)[NQ][4], uint32_t px, uint32_t px2, float& sv, float so) {
    uint32_t x0[4], x1[4], x2[2];
    float cd[3][4];
    lds128(px, x0[0], x0[1], x0[2], x0[3]);
    lds128(px + 64, x1[0], x1[1], x1[2], x1[3]);
    lds64(px2, x2[0], x2[1]);
    sv += __shfl_xor_sync(0xffffffffu, so, 16);
#pragma unroll
    for (int i = 0; i < 3; i++) {
        cc[i][0] = cc[i][1] = cc[i][2] = cc[i][3] = cd[i][0] = cd[i][1] = cd[i][2] = cd[i][3] = 0.f;
        mma16816v(cc[i], pre[i][0], pre[i][1], pre[i][2], pre[i][3], x0[0], x0[1]);
        mma16816v(cd[i], pre[3 + i][0], pre[3 + i][1], pre[3 + i][2], pre[3 + i][3], x0[2], x0[3]);
    }
    sv += __shfl_xor_sync(0xffffffffu, sv, 8);
#pragma unroll
    for (int i = 0; i < 3; i++) {
        mma16816v(cc[i], ext[i][0], ext[i][1], ext[i][2], ext[i][3], x1[0], x1[1]);
        mma16816v(cd[i], ext[3 + i][0], ext[3 + i][1], ext[3 + i][2], ext[3 + i][3], x1[2], x1[3]);
    }
    sv += __shfl_xor_sync(0xffffffffu, sv, 4);
#pragma unroll
    for (int i = 0; i < 3; i++) mma16816v(cc[i], ext[6 + i][0], ext[6 + i][1], ext[6 + i][2], ext[6 + i][3], x2[0], x2[1]);
    sv += __shfl_xor_sync(0xffffffffu, sv, 2);
    sv += __shfl_xor_sync(0xffffffffu, sv, 1);
#pragma unroll
    for (int i = 0; i < 3; i++) { cc[i][0] += cd[i][0]; cc[i][1] += cd[i][1]; cc[i][2] += cd[i][2]; cc[i][3] += cd[i][3]; }
}

__device__ __forceinline__ float warp_max(float x) {
    int i = __float_as_int(x);
    i = __reduce_max_sync(0xffffffffu, i ^ ((i >> 31) & 0x7fffffff));
    return __int_as_float(i ^ ((i >> 31) & 0x7fffffff));
}
__device__ __forceinline__ void idle(uint32_t clk) {
    uint32_t t0, t;
    asm volatile("mov.u32 %0, %%clock;" : "=r"(t0) :: "memory");
    do asm volatile("mov.u32 %0, %%clock;" : "=r"(t) :: "memory"); while (t - t0 < clk);
}
__device__ __forceinline__ uint32_t now_ns() { uint32_t t; asm volatile("mov.u32 %0, %%globaltimer_lo;" : "=r"(t)); return t; }
__device__ __forceinline__ int opq(int x) { asm volatile("" : "+r"(x)); return x; }
__device__ __forceinline__ uint32_t opq(uint32_t x) { asm volatile("" : "+r"(x)); return x; }
__device__ __forceinline__ uint32_t pin(uint32_t x) { return __shfl_sync(0xffffffffu, x, threadIdx.x & 31); }
template <typename T> __device__ __forceinline__ T* pin(T* p) {
    const unsigned long long v = (unsigned long long)p;
    return (T*)((unsigned long long)pin((uint32_t)v) | (unsigned long long)pin((uint32_t)(v >> 32)) << 32);
}
template <typename T> __device__ __forceinline__ T* opq(T* p) { asm volatile("" : "+l"(p)); return p; }
__device__ __forceinline__ float4 lds4f(uint32_t a) { float4 v; asm volatile("ld.shared.v4.f32 {%0,%1,%2,%3}, [%4];" : "=f"(v.x), "=f"(v.y), "=f"(v.z), "=f"(v.w) : "r"(a) : "memory"); return v; }
__device__ __forceinline__ float2 lds2f(uint32_t a) { float2 v; asm volatile("ld.shared.v2.f32 {%0,%1}, [%2];" : "=f"(v.x), "=f"(v.y) : "r"(a) : "memory"); return v; }
__device__ __forceinline__ void ln_stats(uint32_t st, float& mean, float& inv) {
    const float4 a = lds4f(st), b = lds4f(st + 16), c = lds4f(st + 32), d = lds4f(st + 48);
    const float s2 = ((a.x + a.z) + (b.x + b.z)) + ((c.x + c.z) + (d.x + d.z));
    const float md = (((a.y + a.w) + (b.y + b.w)) + ((c.y + c.w) + (d.y + d.w))) * (1.0f / DM);
    const float var = fmaxf(s2 * (1.0f / DM) - md * md, 0.f);
    mean = bfr(md);
    asm("rsqrt.approx.ftz.f32 %0, %1;" : "=f"(inv) : "f"(var + 1e-5f));
}
__device__ __forceinline__ void sts32(uint32_t a, float v) { asm volatile("st.shared.f32 [%0], %1;" ::"r"(a), "f"(v) : "memory"); }
__device__ __forceinline__ void sts32p(uint32_t a, float v, uint32_t off) {
    asm volatile("{\n.reg .pred p;\nsetp.eq.u32 p, %2, 0;\n@p st.shared.f32 [%0], %1;\n}" ::"r"(a), "f"(v), "r"(off) : "memory");
}
__device__ __forceinline__ void sts128p(uint32_t a, float x, float y, float z, float w, uint32_t off) {
    asm volatile("{\n.reg .pred p;\nsetp.eq.u32 p, %5, 0;\n@p st.shared.v4.f32 [%0], {%1,%2,%3,%4};\n}" ::"r"(a), "f"(x), "f"(y), "f"(z), "f"(w), "r"(off) : "memory");
}
__device__ __forceinline__ void sts64(uint32_t a, float v, float w) { asm volatile("st.shared.v2.f32 [%0], {%1,%2};" ::"r"(a), "f"(v), "f"(w) : "memory"); }

__device__ __forceinline__ uint32_t prmt(uint32_t a, uint32_t b, uint32_t s) { uint32_t r; asm("prmt.b32 %0, %1, %2, %3;" : "=r"(r) : "r"(a), "r"(b), "r"(s)); return r; }
__device__ __forceinline__ uint32_t bmul2(uint32_t a, uint32_t b) { uint32_t r; asm("mul.rn.bf16x2 %0, %1, %2;" : "=r"(r) : "r"(a), "r"(b)); return r; }
__device__ __forceinline__ void sts128(uint32_t addr, uint32_t a, uint32_t b, uint32_t c, uint32_t d) {
    asm volatile("st.shared.v4.u32 [%0], {%1,%2,%3,%4};" ::"r"(addr), "r"(a), "r"(b), "r"(c), "r"(d) : "memory");
}
__device__ __forceinline__ uint4 ldg128(const uint4* p) {
    uint4 v;
    asm volatile("ld.volatile.global.v4.u32 {%0,%1,%2,%3}, [%4];" : "=r"(v.x), "=r"(v.y), "=r"(v.z), "=r"(v.w) : "l"(p) : "memory");
    return v;
}
__device__ __forceinline__ uint32_t lds32(uint32_t a) { uint32_t v; asm volatile("ld.shared.u32 %0, [%1];" : "=r"(v) : "r"(a) : "memory"); return v; }
__device__ __forceinline__ uint32_t lds16(uint32_t a) { unsigned short v; asm volatile("ld.shared.u16 %0, [%1];" : "=h"(v) : "r"(a) : "memory"); return v; }
__device__ __forceinline__ void unpack8(uint32_t la, uint32_t lb, uint32_t c, uint32_t (&w)[4]) {
    const uint32_t ha = c & 0x87878787u, hb = __funnelshift_l(c, c, 4) & 0x87878787u;
    w[0] = prmt(la, ha, 0x5140); w[1] = prmt(la, ha, 0x7362); w[2] = prmt(lb, hb, 0x5140); w[3] = prmt(lb, hb, 0x7362);
}
__device__ __forceinline__ uint32_t bdiff2(uint32_t y, uint32_t inv, uint32_t x) {
    uint32_t r;
    asm("{\n.reg .b32 n;\nneg.bf16x2 n, %3;\nfma.rn.bf16x2 %0, %1, %2, n;\n}" : "=r"(r) : "r"(y), "r"(inv), "r"(x));
    return r;
}
__device__ __forceinline__ uint32_t pack_scale(uint32_t tile, int lane, uint32_t inv_addr) {
    uint32_t m = 0;
#pragma unroll 1
    for (int k = 0; k < 12; k++) {
        uint32_t a, b, c, d;
        lds128(tile + k * 512 + lane * 16, a, b, c, d);
        asm("max.xorsign.abs.bf16x2 %0, %0, %1;" : "+r"(a) : "r"(b));
        asm("max.xorsign.abs.bf16x2 %0, %0, %1;" : "+r"(c) : "r"(d));
        asm("max.xorsign.abs.bf16x2 %0, %0, %1;" : "+r"(a) : "r"(c));
        asm("max.xorsign.abs.bf16x2 %0, %0, %1;" : "+r"(m) : "r"(a));
    }
    m = __reduce_max_sync(0xffffffffu, max(m & 0x7fffu, (m >> 16) & 0x7fffu));
    const uint32_t inv = (112u + min((m + 0x28u) >> 7, 141u)) * 0x00800080u;
    if (lane == 0) asm volatile("st.shared.u32 [%0], %1;" ::"r"(inv_addr), "r"(inv) : "memory");
    return inv;
}

#define K_OFF(i) ((uint32_t)((3 * ((g >> 1) + 4 * (g & 1)) + ((i) >> 1)) * 128 + ((t ^ ((3 * ((g >> 1) + 4 * (g & 1)) + ((i) >> 1)) & 7) ^ (((i) & 1) << 2)) << 4)))
#define V_OFF(i) ((uint32_t)((6 * t + (i)) * 128 + ((g ^ ((6 * t + (i)) & 7)) << 4)))
template <bool ISV, typename DST>
__device__ __forceinline__ void pack_tile(uint32_t tile, int tau, int nm, uint32_t inv, uint32_t xl, int lane, DST dst) {
    const int g = lane >> 2, t = lane & 3;
    const uint32_t scl = 254u * 0x00800080u - inv;
#pragma unroll 1
    for (int m = 0; m < nm; m++) {
        const int row = ISV ? 6 * t + 2 * m : 3 * ((g >> 1) + 4 * (g & 1)) + m;
        const uint32_t a0 = tile + row * 128 + (((ISV ? g : t) ^ (row & 7)) << 4), a1 = ISV ? (a0 ^ 16) + 128 : a0 ^ 64;
        uint32_t l[8], cw[4], ck = 0, cd = 0;
#pragma unroll
        for (int r = 0; r < 4; r++) {
            uint32_t w0, w1, w2, w3;
            lds128(((r & 1) ? a1 : a0) + (r >> 1) * 3072, w0, w1, w2, w3);
            const uint32_t y0 = bmul2(w0, scl), y1 = bmul2(w1, scl), y2 = bmul2(w2, scl), y3 = bmul2(w3, scl);
            cd |= bdiff2(y0, inv, w0) | bdiff2(y1, inv, w1);
            cd |= bdiff2(y2, inv, w2) | bdiff2(y3, inv, w3);
            const uint32_t ha = prmt(y0, y1, 0x7531), hb = prmt(y2, y3, 0x7531);
            l[2 * r] = prmt(y0, y1, 0x6420); l[2 * r + 1] = prmt(y2, y3, 0x6420);
            asm("lop3.b32 %0, %1, 0x87878787, %2, 0xe2;" : "=r"(cw[r]) : "r"(ha), "r"(__funnelshift_r(hb, hb, 4)));
            ck |= ha | hb;
        }
        const uint32_t bad = __ballot_sync(0xffffffffu, (ck & 0x78787878u) | cd);
        if (bad) {
            const int src = __ffs(bad) - 1;
            const uint32_t b0 = __shfl_sync(0xffffffffu, a0, src), b1 = __shfl_sync(0xffffffffu, a1, src), n0 = lds32(xl);
            const uint32_t ax = ((lane & 8) ? b1 : b0) + (lane >> 4) * 3072 + 2 * (lane & 7), x = lds16(ax), y = bmul2(x, scl);
            const bool out = (y & 0x7800u) | bdiff2(y, inv, x);
            const uint32_t n = n0 + __popc(__ballot_sync(0xffffffffu, out) << (31 - lane)) - 1;
            if (out) {
                asm volatile("st.shared.u16 [%0], %1;" ::"r"(ax), "h"((unsigned short)0) : "memory");
                if (n < XCAP) sts32(xl + 16 + 4 * n, f_(x << 16 | tau << 12 | src << 7 | m << 5 | lane));
            }
            if (lane == 31) sts32(xl, f_(n + 1));
            __syncwarp();
            if (n0 <= XCAP) { m--; continue; }
        }
        uint32_t d[3] = {a0, a1, a0 + 3072};
        dst(m, d);
        sts128(d[0], l[0], l[1], l[2], l[3]);
        sts128(d[1], l[4], l[5], l[6], l[7]);
        sts128(d[2], cw[0], cw[1], cw[2], cw[3]);
    }
}

struct Maps { CUtensorMap k, v, wq, wo, w1, w3, w2, vr; const void* vp; const void* kp; uint32_t zero; };
#define RT_SEL ((wu & 1) ? RT_MASK2 : RT_MASK)
#define PFK 5
#define Q_AT 3
#define WO_T0 33200
#define K5D 370
#define PK_AT 6

__device__ __forceinline__ void load_ffn(const Maps& maps, int b, uint32_t dst, uint32_t bar) {
    const bool gu = b < NG;
    mbar_expect_tx(bar, gu ? 61440 : 49152);
    tma3d(dst, gu ? (b < NG / 2 ? &maps.w1 : &maps.w3) : &maps.w2, gu ? 48 * (b & (NG / 2 - 1)) : 16 * (b - DN0), 0, 0, bar, FFN_POL);
}

__device__ __forceinline__ void load_wo(const Maps& maps, uint32_t dst, int h, int c, uint32_t bar, int nbox) {
#pragma unroll 1
    for (int i = 0; i < nbox; i++) {
        if (!(i & 1)) mbar_expect_tx(bar + 4 * i, i + 1 < nbox ? 20480 : 10240);
        tma3d(dst + i * 10240, &maps.wo, 0, 5 * c, h * DH + 32 * i, bar + 4 * (i & 6), POL_EF);
    }
}

__global__ void __launch_bounds__(NT, 1)
decode_kernel(const __grid_constant__ Maps maps, const __nv_bfloat16* __restrict__ x_in, __nv_bfloat16* __restrict__ out) {
    extern __shared__ __align__(1024) unsigned char smem[];
    const int tid = threadIdx.x, warp = tid >> 5, lane = tid & 31;
    const int wu = __shfl_sync(0xffffffffu, tid >> 5, 0);
    const int b = blockIdx.x, h = b >> 2, c = b & 3;
    const uint32_t sb = smem_u32(smem);
    const uint32_t qbar = sb + SM_BAR + 16 * 8, fbar = qbar + 8, wbar = qbar + 16;
    uint32_t* xs32 = reinterpret_cast<uint32_t*>(smem + SM_XS);
    float* rr = reinterpret_cast<float*>(smem + SM_R);
    float* misc = reinterpret_cast<float*>(smem + SM_MISC);

    PROF_T(0);
    {
        uint2 xv = make_uint2(0u, 0u);
        const uint32_t t_start = now_ns();
        if (elect_one()) {
            const uint32_t rb = sb + SM_BAR + wu * 16, xb = sb + SM_XBAR + wu * 8;
            mbar_init(rb, 1); mbar_init(rb + 8, 1); mbar_init(xb, 1);
            if (wu == 0) mbar_init(qbar, 1);
            asm volatile("fence.mbarrier_init.release.cluster;" ::: "memory");
            const int row = (h * SK + (SK - WIN) + c * 1024 + wu * 128) * 3;
            const uint32_t ring = sb + SM_RING + wu * 2 * TILE;
#pragma unroll
            for (int n = 0; n < 3; n++) {
                const uint32_t bar = ((IN_S1 >> n) & 1) ? rb + 8 : ((IN_S0 >> n) & 1) ? rb : xb;
                mbar_expect_tx(bar, TILE);
                tma2d(((IN_S1 >> n) & 1) ? ring + TILE : ((IN_S0 >> n) & 1) ? ring : sb + SM_B + wu * TILE, &maps.k, 0, row + 48 * n, bar, POL_EF);
                if (n == 0 && wu == 0) {
                    mbar_expect_tx(qbar, 61440);
                    tma3d(sb + SM_Q, &maps.wq, 0, 160 * c, 3 * h, qbar, POL_EF);
                }
            }
            if (wu == 1) {
                mbar_init(fbar, 1);
#pragma unroll
                for (int i = 0; i < 3; i++) mbar_init(wbar + 8 * i, 1);
                asm volatile("fence.mbarrier_init.release.cluster;" ::: "memory");
            }
            if (wu >= 2) {
                const CUtensorMap* mp = wu == 2 ? &maps.v : wu == 3 ? &maps.wo : wu == 4 ? &maps.w1 : wu == 5 ? &maps.w3 : wu == 6 ? &maps.w2 : &maps.vr;
                asm volatile("prefetch.tensormap [%0];" ::"l"(mp) : "memory");
            }
        }
        if (tid < 160) asm volatile("ld.global.nc.v2.u32 {%0,%1}, [%2];" : "=r"(xv.x), "=r"(xv.y) : "l"(x_in + 4 * tid) : "memory");
        if (tid == 96) { misc[2] = 0.f; misc[3] = 0.f; }
        if (lane == 1) *reinterpret_cast<uint2*>(smem + SM_XL + warp * XSTR) = make_uint2(0u, t_start + WO_T0);
        if (tid >= 128 && tid < 148) {
            const uint32_t v = tid < 138 ? ONES : 0u;
            reinterpret_cast<uint4*>(smem + SM_ONE)[tid - 128] = make_uint4(v, v, v, v);
        }
        if (tid < 160) { xs32[xpos(2 * tid)] = xv.x; xs32[xpos(2 * tid + 1)] = xv.y; }
        __syncthreads();
        PROF_T(14);
        if (b == 0 && tid >= 232) asm volatile("st.relaxed.gpu.global.u32 [%0], %1;" ::"l"(g_scr.ticket + tid - 232), "r"(0) : "memory");
        if (tid == 64 || (tid == 65 && b < 216 - NCTA)) st_pkt(&g_scr.acc[1][(b + NCTA * (tid - 64)) * ACC_STR], 0, 0, 0, 0);
    }

    uint32_t kq[NQ][4];
    const float SC = 0.07216878364870322f * 1.4426950408889634f;

#pragma unroll 1
    for (int ph = 0; ph < 3; ph++) {
        const int layer = ph >> 1;
        const uint32_t tag = layer + 1;
        PROF_T(1 + layer * 16);
        if (ph) {
        {
            const int tl = opq(tid), warp = tl >> 5, lane = tl & 31, g = lane >> 2, t = lane & 3, mat = lane >> 3, r8 = lane & 7;
            const int kh = warp >> 2, mg = warp & 3;
            uint32_t aq[3];
#pragma unroll
            for (int i = 0; i < 3; i++) {
                const int ch = 6 * mg + 2 * i + (mat & 1);
                aq[i] = sb + SM_Q + (80 * kh + (mat >> 1) * 8 + r8) * 128 + (ch >> 3) * 20480 + (((ch & 7) ^ r8) << 4);
            }
#define PF_K5 if (layer == 1 && PFK) tile_keep(&maps.k, (h * SK + (SK - WIN) + c * 1024 + wu * 128 + PFK * 16) * 3);
            uint2 xv = make_uint2(0u, 0u);
            mbar_wait(qbar, 0);
            uint32_t pre[6][4];
#pragma unroll
            for (int n = 0; n < 6; n++) ldsm4t(aq[n % 3] + (n / 3) * 2048, pre[n]);
            if (layer == 1) {
                __syncthreads();
                if (elect_one()) {
                    const uint32_t bar = sb + SM_BAR + wu * 16;
                    asm volatile("mbarrier.expect_tx.relaxed.cta.shared::cta.b64 [%0], 1536;" ::"r"(bar) : "memory");
#pragma unroll
                    for (int k = 0; k < 3; k++)
                        tma2d(sb + SM_Q + v1_pos(3 * wu + k), &maps.vr, 0, (h * SK + (SK - WIN) + c * 1024 + wu * 128) / 2 + 8 + 2 * k, bar, POL_EF);
                }
            }
            const uint32_t pm = opq(g == 1 ? sb + SM_ONE : sb + SM_XS + 160 * (2 * c + kh) + 16 * t), pm2 = opq(pm + 128 - (g == 1 ? 0 : 8 * t));
            const uint32_t dq = opq(sb + SM_R + 8 * (kh * 192 + 48 * mg + g)), ds = opq(sb + SM_ST + 8 * warp + (lane < 16 ? 4 : 0));
            const bool wr = t == 0, ws = (lane & 15) == 0, lo = lane < 16;
            if (wu < 5) {
                const int p0 = xpos(2 * tl), p1 = xpos(2 * tl + 1);
                if (layer == 1) {
                    uint4 v;
                    for (int it = 0; it < SPIN_CAP; it++) { v = ld_pkt(&g_scr.ay[tl]); if (__all_sync(0xffffffffu, v.w == 1)) break; }
                    xv = make_uint2(v.x, v.y);
                    xs32[p0] = xv.x; xs32[p1] = xv.y;
                } else xv = make_uint2(xs32[p0], xs32[p1]);
            }
            if (layer) PC(24);
            __syncthreads();
            PF_K5
            if (layer) PC(25);
            PROF_T(13 + layer * 16);
            const float e0 = bf_lo(xv.x), e1 = bf_hi(xv.x), e2 = bf_lo(xv.y), e3 = bf_hi(xv.y);
            const float s1 = (e0 + e1) + (e2 + e3), s2 = (e0 * e0 + e1 * e1) + (e2 * e2 + e3 * e3);
            float sv = lo ? s1 : s2, cc[3][4];
            gemv15<2048>(cc, pre, [&](int i) { return aq[i]; }, pm, pm2, sv, lo ? s2 : s1);
            if (wr) {
#pragma unroll
                for (int i = 0; i < 3; i++) { sts64(dq + 128 * i, cc[i][0], cc[i][1]); sts64(dq + 128 * i + 64, cc[i][2], cc[i][3]); }
            }
            if (ws) sts32(ds, sv);
        }
        const uint32_t pa = opq(sb + SM_R + 32 * opq(tid)), st = opq(sb + SM_ST);
        uint4* const pq = opq(&g_scr.hx[b * 48 + opq(tid)]);
        if (layer) PC(26);
        __syncthreads();
        if (layer) PC(27);
        PROF_T(33 + layer * 16);
        if (wu < 2) {
            float mean, inv;
            ln_stats(st, mean, inv);
            const float4 a0 = lds4f(pa), a1 = lds4f(pa + 16), b0 = lds4f(pa + 1536), b1 = lds4f(pa + 1552);
            const float q0 = (a0.x + b0.x) - mean * (a0.y + b0.y), q1 = (a0.z + b0.z) - mean * (a0.w + b0.w);
            const float q2 = (a1.x + b1.x) - mean * (a1.y + b1.y), q3 = (a1.z + b1.z) - mean * (a1.w + b1.w);
            st_pktfp(pq, q0, q1, q2, q3, 1, tid < 48);
        }
        if (layer == 1 && tid >= 192 && tid < 194 && b < 108) st_pkt(&g_scr.acc[0][(2 * b + opq(tid) - 192) * ACC_STR], 0, 0, 0, 0);
        }
        if (layer) PC(28);
        if (layer == 1 && (wu & 2)) {
            idle(K5D);
#pragma unroll 1
            for (int w = wu; w >= (wu > 4 ? wu - 2 : wu); w -= 2)
                tile_load(sb + SM_Q + c_slot(w), &maps.k, (h * SK + (SK - WIN) + c * 1024 + w * 128 + 5 * 16) * 3, sb + SM_XBAR + w * 8, 0, 0);
        }

        float sc0 = -INFINITY, sc1 = -INFINITY, sc2 = 0.f, sc3 = 0.f, mw;
        uint32_t pk0, pk1;
        float acc[3][4];
        {
            const uint32_t ring = sb + SM_RING + wu * 2 * TILE, rb = sb + SM_BAR + wu * 16;
            const uint32_t xtile = sb + SM_Q + c_slot(wu), xb = sb + SM_XBAR + wu * 8;
#define V_SEQ(n) ((int)(SEQ1 >> (4 * (n))) & 7)
#define SLOT1(n) (((IN_S1 >> (n)) & 1) ? ring + TILE : ((IN_S0 >> (n)) & 1) ? ring : sb + SM_B + wu * TILE)
#define BAR1(n) (((IN_S1 >> (n)) & 1) ? rb + 8 : ((IN_S0 >> (n)) & 1) ? rb : xb)
#define PAR1(n) ((PARITY1 >> (n)) & 1)
#define PAR2(n) ((PARITY2 >> (n)) & 1)
            const int row0 = (h * SK + (SK - WIN) + c * 1024 + wu * 128) * 3;
            auto issue1 = [&](int n, uint32_t dep, bool vph = false) {
                const CUtensorMap* mp = n < 8 ? &maps.k : &maps.v;
                const int tl = V_SEQ(n), row = row0 + tl * 48;
                const uint32_t dst = SLOT1(n), bar = BAR1(n);
                if (vph && wu < L1R && tl == 7 - (wu & 1)) {
                    tile_load_l1(dst, maps.vp, row, bar, opq(tid) & 31);
                    return;
                }
                tile_load(dst, mp, row, bar, dep, maps.zero);
                if ((RT_SEL >> (tl + (n & 8))) & 1) {
                    if (n != V0_AT + 1) tile_keep(mp, row);
                    else if ((opq(tid) & 31) < 8)
                        asm volatile("cp.async.bulk.prefetch.L2.global.L2::cache_hint [%0], 256, %1;"
                                     ::"l"(static_cast<const char*>(maps.vp) + (size_t)(row + 4 + 6 * (opq(tid) & 31)) * 128), "l"(POL_EN) : "memory");
                }
            };
            auto refill1 = [&](int s, uint32_t dep, bool vph = false) { issue1(s + (!vph || s < V0_AT ? 3 : 2), dep, vph); };
#define LANE_IDS const int tl = opq(tid), lane = tl & 31, g = lane >> 2, t = lane & 3; (void)tl; (void)lane; (void)g; (void)t;
            const uint32_t xl = sb + SM_XL + wu * XSTR;
            if (layer == 0) {
#pragma unroll 1
                for (int s = ph ? Q_AT : 0; s < (ph ? 5 : Q_AT); s++) {
                    LANE_IDS
                    const uint32_t tile = SLOT1(s);
                    mbar_wait(BAR1(s), PAR1(s));
                    const uint32_t scl = s == 0 ? pack_scale(tile, lane, xl + 8) : lds32(xl + 8);
                    pack_tile<false>(tile, s, 3, scl, xl, lane, [](int, uint32_t (&)[3]) {});
#pragma unroll
                    for (int n = 0; n < 5; n++) {
                        if (s == n) {
#pragma unroll
                            for (int m = 0; m < 3; m++) {
                                const uint32_t a = tile + K_OFF(2 * m);
                                lds128(a, kq[9 * n + 3 * m][0], kq[9 * n + 3 * m][1], kq[9 * n + 3 * m][2], kq[9 * n + 3 * m][3]);
                                lds128(a ^ 64, kq[9 * n + 3 * m + 1][0], kq[9 * n + 3 * m + 1][1], kq[9 * n + 3 * m + 1][2], kq[9 * n + 3 * m + 1][3]);
                                lds128(a + 3072, kq[9 * n + 3 * m + 2][0], kq[9 * n + 3 * m + 2][1], kq[9 * n + 3 * m + 2][2], kq[9 * n + 3 * m + 2][3]);
                            }
                        }
                    }
                    __syncwarp();
                    refill1(s, lds32(tile));
                }
                if (!ph) continue;
            }
            {
                if (wu < 2) {
                    const int tl = min(opq(tid), 47);
                    const int w = 2 * tl;
                    const uint32_t pos = opq(sb + SM_QS + 4 * (((w >> 2) & 3) * 24 + 2 * (w >> 4) + ((w >> 1) & 1)));
                    uint4 v[4];
                    float mean, inv;
                    ln_stats(opq(sb + SM_ST), mean, inv);
                    for (int it = 0; it < SPIN_CAP; it++) {
#pragma unroll
                        for (int k = 0; k < 4; k++) v[k] = ld_pkt(&g_scr.hx[(h * 4 + k) * 48 + tl]);
                        if (all_odd(v[0].w, v[1].w, v[2].w, v[3].w)) break;
                    }
                    sts32(pos, f_(pack2(inv * ((f_(v[0].x) + f_(v[1].x)) + (f_(v[2].x) + f_(v[3].x))), inv * ((f_(v[0].y) + f_(v[1].y)) + (f_(v[2].y) + f_(v[3].y))))));
                    sts32(pos + 48, f_(pack2(inv * ((f_(v[0].z) + f_(v[1].z)) + (f_(v[2].z) + f_(v[3].z))), inv * ((f_(v[0].w) + f_(v[1].w)) + (f_(v[2].w) + f_(v[3].w))))));
                }
            }
            if (layer) PC(29);
            __syncthreads();
            if (layer) PC(30);
            PROF_T(2 + layer * 16);
#define V1_REST(p) ((p) < 6 ? sb + SM_Q + v1_pos(3 * wu + ((p) >> 1)) + 256 * ((p) & 1) : ((sb + SM_R + wu * 784 + 127) & ~127u) - 1536 + 256 * (p))
#define V1_LOAD(bar) if (elect_one()) tma2d(V1_REST(6), &maps.vr, 0, row0 / 6 + 14, bar, POL_EF);
#define V1_EXPECT(bar) { if ((opq(tid) & 31) == 0) asm volatile("mbarrier.expect_tx.relaxed.cta.shared::cta.b64 [%0], 512;" ::"r"(bar) : "memory"); }
            if (layer == 1 && wu < 2) tile_load(xtile, &maps.k, row0 + 5 * 48, xb, 0, 0);
            if (layer == 1 && wu >= 4) idle(STAG);
            {
                uint32_t qf[12];
                int t;
                {
                    const int lane = opq(tid) & 31;
                    t = lane & 3;
                    const uint32_t qa = sb + SM_QS + (2 * t + ((lane >> 2) & 1)) * 48;
#pragma unroll
                    for (int i = 0; i < 3; i++) lds128(qa + 16 * i, qf[4 * i], qf[4 * i + 1], qf[4 * i + 2], qf[4 * i + 3]);
                }
                const uint32_t sq = lds32(xl + 8) - 64u * 0x00800080u;
#pragma unroll
                for (int i = 0; i < 12; i++) qf[i] = bmul2(qf[i], sq);
#define KR_STEP(tau, m) \
                    _Pragma("unroll") for (int i = 2 * (m); i < 2 * (m) + 2; i++) { \
                        const int q0 = 9 * tau + 3 * (i >> 1), r = i & 1; \
                        uint32_t w[4]; \
                        unpack8(kq[q0][2 * r], kq[q0][2 * r + 1], kq[q0 + 2][r], w); \
                        mma16816(cA, w[0], w[1], w[2], w[3], qf[2 * i], qf[2 * i + 1]); \
                        unpack8(kq[q0 + 1][2 * r], kq[q0 + 1][2 * r + 1], kq[q0 + 2][2 + r], w); \
                        mma16816(cB, w[0], w[1], w[2], w[3], qf[2 * i], qf[2 * i + 1]); \
                    }
#define KR_BEGIN float cA[4] = {0.f, 0.f, 0.f, 0.f}, cB[4] = {0.f, 0.f, 0.f, 0.f};
#define KR_END(tau) \
                    const float sA = (cA[0] + cA[3]) * 18446744073709551616.f, sB = (cB[0] + cB[3]) * 18446744073709551616.f; \
                    if (t == (tau & 3)) { if (tau < 4) { sc0 = sA; sc1 = sB; } else { sc2 = sA; sc3 = sB; } }
#define KR_SCORES(tau) { KR_BEGIN KR_STEP(tau, 0) KR_STEP(tau, 1) KR_STEP(tau, 2) KR_END(tau) }
                uint32_t va[3];
                {
                    const int lane = opq(tid) & 31, g = lane >> 2, t = lane & 3;
#pragma unroll
                    for (int i = 0; i < 3; i++) va[i] = ring + V_OFF(2 * i);
                }
#define V_STG(n) _Pragma("unroll") for (int j = 3 * (n); j < 3 * (n) + 3; j++) { \
                    const int i = (j % 12) >> 1; \
                    lds128p(((i & 1) ? (va[i >> 1] ^ 16) + 128 : va[i >> 1]) + (j / 12) * TILE + (j & 1) * 3072, layer, kq[j][0], kq[j][1], kq[j][2], kq[j][3]); }
                uint32_t dep = 0;
                {
                    KR_BEGIN
                    KR_STEP(0, 0) V_STG(0) KR_STEP(0, 1) V_STG(1) KR_STEP(0, 2) V_STG(2)
                    KR_END(0)
                }
                {
                    KR_BEGIN
                    KR_STEP(1, 0) V_STG(3)
                    __syncwarp();
                    dep = lds32(ring);
                    if (layer == 1) tile_load(ring, &maps.k, row0 + 6 * 48, rb, dep, maps.zero);
                    KR_STEP(1, 1) V_STG(4) KR_STEP(1, 2) V_STG(5)
                    KR_END(1)
                }
                {
                    KR_BEGIN
                    KR_STEP(2, 0) V_STG(6) KR_STEP(2, 1) V_STG(7)
                    __syncwarp();
                    dep = lds32(ring + TILE);
                    KR_STEP(2, 2)
                    if (layer == 1) {
                        V1_EXPECT(rb + 8)
                        tile_load(ring + TILE, &maps.k, row0 + 7 * 48, rb + 8, dep, maps.zero);
                        V1_LOAD(rb + 8)
                    }
                    KR_END(2)
                }
#pragma unroll 1
                for (int s = 5; s < 8; s++) {
                    {
                        LANE_IDS
                        const uint32_t tile = !layer ? SLOT1(s) : s == 5 ? xtile : ring + (s - 6) * TILE, tb = !layer ? BAR1(s) : s == 5 ? xb : rb + (s - 6) * 8;
                        const float ur = f_((318u << 23) - (lds32(xl + 8) << 16));
                        mbar_wait(tb, layer ? PAR2(s - 5) : PAR1(s));
                        if (layer) PROF_T(29 + s);
                        float cA[4] = {0.f, 0.f, 0.f, 0.f}, cB[4] = {0.f, 0.f, 0.f, 0.f};
#pragma unroll
                        for (int i = 0; i < 6; i++) {
                            uint32_t a0, a1, a2, a3;
                            lds128(tile + K_OFF(i), a0, a1, a2, a3);
                            mma16816(cA, a0, a1, a2, a3, qf[2 * i], qf[2 * i + 1]);
                            lds128(tile + K_OFF(i) + 3072, a0, a1, a2, a3);
                            mma16816(cB, a0, a1, a2, a3, qf[2 * i], qf[2 * i + 1]);
                        }
                        __syncwarp();
                        const uint32_t last = lds32(tile);
                        if (layer) tile_load(tile, &maps.v, row0 + (s - 2) * 48, tb, last, maps.zero);
                        else refill1(s, last);
                        if (t == (s & 3)) { sc2 = (cA[0] + cA[3]) * ur; sc3 = (cB[0] + cB[3]) * ur; }
                    }
                    if (s == 5) KR_SCORES(3)
                    if (s == 6) {
                        KR_SCORES(4)
                        const int lane = opq(tid) & 31;
                        const uint32_t nx = min(lds32(xl), (uint32_t)XCAP);
#pragma unroll 1
                        for (uint32_t n = 0; n < nx; n++) {
                            const uint32_t id = lds32(xl + 16 + 4 * n);
                            const uint32_t qo = 96 * ((id >> 7) & 3) + 48 * ((id >> 1) & 1) + 16 * ((id >> 5) & 3) + (id & 12) + 2 * (id & 1);
                            const float cr = bf_hi(id) * f_(lds16(sb + SM_QS + qo) << 16);
                            const int d = (int)(16 * ((id >> 9) & 7) + 4 * ((id >> 12) & 3) + ((id >> 13) & 2) + ((id >> 4) & 1) + ((id >> 8) & 128)) - 4 * lane;
                            if (d == 0) sc0 += cr;
                            if (d == 1) sc1 += cr;
                            if (d == 2) sc2 += cr;
                            if (d == 3) sc3 += cr;
                        }
                    }
                }
#undef KR_SCORES
#undef KR_STEP
#undef KR_BEGIN
#undef KR_END
#undef V_STG
                {
                    LANE_IDS
                    if (lds32(xl) > XCAP || !__all_sync(0xffffffffu, (fabsf(sc0) + fabsf(sc1)) + (fabsf(sc2) + fabsf(sc3)) < INFINITY)) {
                        const uint32_t qa = sb + SM_QS + (2 * t + (g & 1)) * 48;
#pragma unroll
                        for (int i = 0; i < 3; i++) lds128(qa + 16 * i, qf[4 * i], qf[4 * i + 1], qf[4 * i + 2], qf[4 * i + 3]);
                        const uint4* kg = reinterpret_cast<const uint4*>(static_cast<const char*>(maps.kp) + (size_t)row0 * 128) + ((g >> 1) + 4 * (g & 1)) * 24 + t;
#pragma unroll 1
                        for (int s = 0; s < 8; s++) {
                            float cA[4] = {0.f, 0.f, 0.f, 0.f}, cB[4] = {0.f, 0.f, 0.f, 0.f};
#pragma unroll
                            for (int i = 0; i < 6; i++) {
                                uint4 u = ldg128(kg + s * 384 + 4 * i);
                                mma16816v(cA, u.x, u.y, u.z, u.w, qf[2 * i], qf[2 * i + 1]);
                                u = ldg128(kg + s * 384 + 4 * i + 192);
                                mma16816v(cB, u.x, u.y, u.z, u.w, qf[2 * i], qf[2 * i + 1]);
                            }
                            if (t == s) { sc0 = cA[0] + cA[3]; sc1 = cB[0] + cB[3]; }
                            if (t + 4 == s) { sc2 = cA[0] + cA[3]; sc3 = cB[0] + cB[3]; }
                        }
                    }
                }
            }
            mw = warp_max(fmaxf(fmaxf(sc0, sc1), fmaxf(sc2, sc3)));
            pk0 = pack2(ex2((sc0 - mw) * SC), ex2((sc1 - mw) * SC));
            pk1 = pack2(ex2((sc2 - mw) * SC), ex2((sc3 - mw) * SC));
            sc2 = (bf_lo(pk0) + bf_hi(pk0)) + (bf_lo(pk1) + bf_hi(pk1));
            sc2 = (float)__reduce_add_sync(0xffffffffu, __float2uint_rn(sc2 * 16777216.f)) * (1.0f / 16777216.f);
            if ((opq(tid) & 31) == 0) st_pkt2(&g_scr.mx[h * 32 + c * 8 + wu], __float_as_uint(mw), (__float_as_uint(sc2) & ~3u) | tag);
            auto head_factor = [&]() {
                const int lane = opq(tid) & 31;
                int it = 0;
                while (!__all_sync(0xffffffffu, (__float_as_uint(sc1) & 3u) == tag) && ++it < SPIN_CAP) {
                    const uint2 mv = ld_pkt2(&g_scr.mx[h * 32 + lane]); sc0 = f_(mv.x); sc1 = f_(mv.y);
                }
                const float e = ex2((sc0 - warp_max(sc0)) * SC);
                const uint32_t d = __reduce_add_sync(0xffffffffu, __float2uint_rn(sc1 * e * 524288.f));
                sc3 = __shfl_sync(0xffffffffu, e, c * 8 + wu) * 524288.f * rcp((float)d);
            };
#pragma unroll
            for (int s = 0; s < 3; s++) { acc[s][0] = acc[s][1] = acc[s][2] = acc[s][3] = 0.f; }
#define P_CONSTS \
                const uint32_t sel0 = g == 0 ? 0x4410u : (g == 1 ? 0x1044u : 0x4444u); \
                const uint32_t sel1 = g == 2 ? 0x4410u : (g == 3 ? 0x1044u : 0x4444u); \
                const int src00 = 4 * (t < 2 ? 4 * t : 4 * (t - 2) + 1);
#define P_FRAGS(tau) \
                const uint32_t pk = ((tau) & 4) ? pk1 : pk0; \
                const uint32_t w0 = __shfl_sync(0xffffffffu, pk, src00 + ((tau) & 3)); \
                const uint32_t w1 = __shfl_sync(0xffffffffu, pk, src00 + ((tau) & 3) + 8); \
                uint32_t pb[4][2]; \
                _Pragma("unroll") for (int j = 0; j < 4; j++) { \
                    const uint32_t src = ((j & 1) ? w1 : w0) >> ((j >> 1) * 16); \
                    pb[j][0] = __byte_perm(src, 0, sel0); pb[j][1] = __byte_perm(src, 0, sel1); \
                }
            if (layer == 0) {
#pragma unroll 1
                for (int s = 8; s < 16; s++) {
                    LANE_IDS
                    P_CONSTS
                    if (s == 13) { const uint2 mv = ld_pkt2(&g_scr.mx[h * 32 + lane]); sc0 = f_(mv.x); sc1 = f_(mv.y); }
                    P_FRAGS(V_SEQ(s))
                    mbar_wait(BAR1(s), PAR1(s));
                    const uint32_t tile = SLOT1(s);
#pragma unroll
                    for (int j = 0; j < 4; j++) {
#pragma unroll
                        for (int u = 0; u < 3; u++) {
                            uint32_t a0, a1, a2, a3;
                            lds128(tile + (j >> 1) * 3072 + V_OFF(3 * (j & 1) + u), a0, a1, a2, a3);
                            mma16816(acc[u], a0, a1, a2, a3, pb[j][0], pb[j][1]);

                        }
                    }
                    __syncwarp();
                    if (s < V0_AT || (s > V0_AT + 1 && s < 14)) refill1(s, lds32(tile), true);
                    if (s == V0_AT || s == V0_AT + 1) {
                        {
                            const uint32_t ar = sb + SM_R + wu * 784 + 32 * g + 16 * t;
                            if (t < 2) {
#pragma unroll
                                for (int u = 0; u < 3; u++) sts128(ar + 256 * u, __float_as_uint(acc[u][0]), __float_as_uint(acc[u][1]), __float_as_uint(acc[u][2]), __float_as_uint(acc[u][3]));
                            }
                        }
                        const uint32_t scl = s == V0_AT ? pack_scale(tile, lane, xl + 12) : lds32(xl + 12);
                        pack_tile<true>(tile, s + 8 - V0_AT, V0_AT + 3 - s, scl, xl, lane, [&](int m, uint32_t (&d)[3]) {
                            if (s != V0_AT && m == 0) {
#pragma unroll
                                for (int k = 0; k < 3; k++) d[k] = ring + 3072 + V_OFF(2 * k + 1);
                            }
                        });
                        if (s != V0_AT) {
                            lds128(tile + V_OFF(2), kq[45][0], kq[45][1], kq[45][2], kq[45][3]);
                            lds128(tile + V_OFF(3), kq[46][0], kq[46][1], kq[46][2], kq[46][3]);
                            lds128(tile + V_OFF(2) + 3072, kq[47][0], kq[47][1], kq[47][2], kq[47][3]);
                            __syncwarp();
                            issue1(V0_AT + 3, lds32(tile));
                        }
                        const int ln = opq(tid) & 31;
                        const uint32_t ar = sb + SM_R + wu * 784 + 8 * (ln & 28) + 16 * (ln & 1);
#pragma unroll
                        for (int u = 0; u < 3; u++) {
                            uint32_t a0, a1, a2, a3;
                            lds128(ar + 256 * u, a0, a1, a2, a3);
                            acc[u][0] = f_(a0); acc[u][1] = f_(a1); acc[u][2] = f_(a2); acc[u][3] = f_(a3);
                        }
                    }
                    if (s == 13) head_factor();
                    if (s >= 14 && elect_one()) {
                        if (atomicAdd(reinterpret_cast<unsigned*>(misc + 3), 1u) == 14u && (int)(now_ns() - lds32(xl + 4)) >= 0) {
                            PROF_X(47);
                            load_wo(maps, sb + SM_B, h, c, wbar, 6);
                            atomicAdd(reinterpret_cast<unsigned*>(misc + 3), 256u);
                        }
                    }
                }
            } else {
                LANE_IDS
                P_CONSTS
#pragma unroll
                for (int k = 0; k < 4; k++) lds128(V1_REST(t + 4 * (k >> 1)) + 16 * g + 128 * (k & 1), kq[36 + k][0], kq[36 + k][1], kq[36 + k][2], kq[36 + k][3]);
#pragma unroll 1
                for (int i = 3; i < 8; i++) {
                    const uint32_t tile = i > 3 ? ring + (i & 1) * TILE : xtile, tb = i > 3 ? rb + (i & 1) * 8 : xb;
                    if (i == 6) { const uint2 mv = ld_pkt2(&g_scr.mx[h * 32 + lane]); sc0 = f_(mv.x); sc1 = f_(mv.y); }
                    if (i == 7) head_factor();
                    if (i == PK_AT) {
                uint32_t nx, nk, ik, iv;
                lds128(xl, nx, nk, ik, iv);
                if (nx <= XCAP) {
                    const uint32_t pks = bmul2(pk0, iv);
#pragma unroll
                    for (int s = 0; s < 2; s++) {
                        const uint32_t pk1 = 0, pk0 = pks;
                        P_FRAGS(s)
#pragma unroll
                        for (int j = 0; j < 4; j++) {
#pragma unroll
                            for (int u = 0; u < 3; u++) {
                                const int i = 3 * (j & 1) + u, m = i >> 1, r = i & 1, hf = j >> 1;
                                if (s == 1 && m == 2) continue;
                                const int ql = s == 0 ? 4 * m + 2 * hf : m == 0 ? 3 + 4 * hf : 45 + hf, qc = s == 0 ? 4 * m + 1 : m == 0 ? 11 : 47;
                                uint32_t w[4];
                                unpack8(kq[ql][2 * r], kq[ql][2 * r + 1], kq[qc][2 * hf + r], w);
                                mma16816(acc[u], w[0], w[1], w[2], w[3], pb[j][0], pb[j][1]);
                            }
                        }
                    }
#pragma unroll 1
                    for (uint32_t n = 0; n < nx; n++) {
                        const uint32_t id = lds32(xl + 16 + 4 * n);
                        const int i = ((id >> 4) & 6) + ((id >> 3) & 1), key = ((id >> 6) & 6) + (i >= 3);
                        const uint32_t pw = __shfl_sync(0xffffffffu, pk0, 8 * (key & 3) + (key & 4) + ((id >> 12) & 3));
                        const float cr = bf_hi(id) * ((id & 16) ? bf_hi(pw) : bf_lo(pw));
                        const int d = (int)(64 * ((id >> 9) & 7) + 4 * (id & 4) + 4 * (i >= 3 ? i - 3 : i) + (id & 3) + ((~id >> 5) & 1024)) - 16 * lane;
#pragma unroll
                        for (int k = 0; k < 12; k++) if (d == k) acc[k >> 2][k & 3] += cr;
                    }
                } else {
                    const uint4* vg = reinterpret_cast<const uint4*>(static_cast<const char*>(maps.vp) + (size_t)row0 * 128) + 48 * t + g;
#pragma unroll 1
                    for (int s = 0; s < 2; s++) {
                        P_FRAGS(s)
#pragma unroll
                        for (int j = 0; j < 4; j++) {
#pragma unroll
                            for (int u = 0; u < 3; u++) {
                                if (s == 1 && (j & 1) && u) continue;
                                const uint4 w = ldg128(vg + 384 * s + 192 * (j >> 1) + 24 * (j & 1) + 8 * u);
                                mma16816v(acc[u], w.x, w.y, w.z, w.w, pb[j][0], pb[j][1]);
                            }
                        }
                    }
                }
#pragma unroll
                for (int s = 2; s > 0; s--) {
                    P_FRAGS(s)
#pragma unroll
                    for (int j = 0; j < 4; j++) {
#pragma unroll
                        for (int u = 0; u < 3; u++) {
                            if (s == 1 && !((j & 1) && u)) continue;
                            const int k = s == 2 ? 12 + 2 * (3 * (j & 1) + u) + (j >> 1) : 35 + (j >> 1) * 2 + u;
                            mma16816(acc[u], kq[k][0], kq[k][1], kq[k][2], kq[k][3], pb[j][0], pb[j][1]);
                        }
                    }
                }
                    }
                    P_FRAGS(i)
                    mbar_wait(tb, PAR2(i));
                    PROF_T(34 + i);
#pragma unroll
                    for (int k = 0; k < 6; k++) {
                        const uint32_t a = tile + V_OFF(k);
                        lds128(a, kq[24 + k][0], kq[24 + k][1], kq[24 + k][2], kq[24 + k][3]);
                        lds128(a + 3072, kq[30 + k][0], kq[30 + k][1], kq[30 + k][2], kq[30 + k][3]);
                    }
#pragma unroll
                    for (int j = 0; j < 4; j++) {
#pragma unroll
                        for (int u = 0; u < 3; u++) {
                            const int k = 24 + 6 * (j >> 1) + 3 * (j & 1) + u;
                            mma16816(acc[u], kq[k][0], kq[k][1], kq[k][2], kq[k][3], pb[j][0], pb[j][1]);
                        }
                    }
                    __syncwarp();
                    if (wu < L1R && i == 5 - (wu & 1)) tile_load_l1(tile, maps.vp, row0 + (i + 2) * 48, tb, lane);
                    else if (i == 4 || i == 5) tile_load(tile, &maps.v, row0 + (i + 2) * 48, tb, lds32(tile), maps.zero);
                    if (i == WO_AT1 && HAS_FFN && elect_one()) {
                        if (atomicAdd(reinterpret_cast<unsigned*>(misc + 2), 1u) == 7u) {
                            PROF_X(63);
                            load_wo(maps, sb + SM_Q, h, c, wbar, KEEP4 && __float_as_uint(misc[1]) >= DN0 ? 5 : 6);
                        }
                    }
                }
            }
#undef P_FRAGS
#undef P_CONSTS
#undef LANE_IDS
        }
        PROF_T(3 + layer * 16);
        PC(layer * 32 + 1);

        {
            const int lane = opq(tid) & 31;
            const uint32_t a = sb + SM_R + wu * 784 + 8 * (lane & 28) + 16 * (lane & 1);
#pragma unroll
            for (int u = 0; u < 3; u++) sts128p(a + 256 * u, acc[u][0] * sc3, acc[u][1] * sc3, acc[u][2] * sc3, acc[u][3] * sc3, lane & 2);
        }
        const uint32_t role1 = layer ? lds32(sb + SM_MISC + 4) : DN0 + NDN;
        const uint32_t pc = opq(sb + SM_R + 16 * opq(tid));
        uint4* const px0 = opq(&g_scr.hx[b * 48 + opq(tid)]);
        __syncthreads();
        PROF_T(4 + layer * 16);
        PC(layer * 32 + 2);
        float4 o = make_float4(0.f, 0.f, 0.f, 0.f);
        if (wu < 2) {
            float4 v[8];
#pragma unroll
            for (int w = 0; w < 8; w++) v[w] = lds4f(pc + w * 784);
            o.x = ((v[0].x + v[1].x) + (v[2].x + v[3].x)) + ((v[4].x + v[5].x) + (v[6].x + v[7].x));
            o.y = ((v[0].y + v[1].y) + (v[2].y + v[3].y)) + ((v[4].y + v[5].y) + (v[6].y + v[7].y));
            o.z = ((v[0].z + v[1].z) + (v[2].z + v[3].z)) + ((v[4].z + v[5].z) + (v[6].z + v[7].z));
            o.w = ((v[0].w + v[1].w) + (v[2].w + v[3].w)) + ((v[4].w + v[5].w) + (v[6].w + v[7].w));
            o.w = f_(__float_as_uint(o.w) & ~1u);
            st_pktp(px0, __float_as_uint(o.x), __float_as_uint(o.y), __float_as_uint(o.z), __float_as_uint(o.w), threadIdx.x < 48);
        }
        uint32_t ticket = 0;
        if (layer == 0 && tid == 224)
            asm volatile("atom.relaxed.gpu.global.inc.u32 %0, [%1], 0x7fffffff;" : "=r"(ticket) : "l"(g_scr.ticket + 8 + (b >> 3)) : "memory");
        if (layer == 0 && tid == 224 && lds32(sb + SM_MISC + 12) < 256u) {
            int it = 0;
            while ((int)(now_ns() - lds32(sb + SM_XL + 4)) < 0 && ++it < SPIN_CAP) {}
            PROF_X(47);
            load_wo(maps, sb + SM_B, h, c, wbar, 6);
        }
        uint32_t pr;
        uint4* pacc;
        {
            const int tid = opq(threadIdx.x), warp = tid >> 5, lane = tid & 31, g = lane >> 2, t = lane & 3, mat = lane >> 3, r8 = lane & 7;
            const int kg = warp >> 1, mg = warp & 1;
            const bool wo2 = role1 < DN0 + NDN;
            const uint32_t aw2 = 40960 + (wo2 && KEEP4 && role1 >= DN0 && kg >= 2 ? SM_B - SM_Q : 0);
            uint32_t aw[5];
#pragma unroll
            for (int i = 0; i < 5; i++) {
                const uint32_t lin = ((mat >> 1) * 8 + r8) * 320 + 64 * i + 32 * mg + 16 * (mat & 1);
                aw[i] = sb + (wo2 ? SM_Q : SM_B) + 5120 * kg + (lin ^ ((lin >> 3) & 48));
            }
#define CXE 0
            const uint32_t ao = pin(sb + SM_OS + 96 * kg + 16 * t), dw = pin(sb + SM_R + 16 * (16 * mg + g) + 4 * kg);
            pr = pin(sb + SM_R + 48 * tid); pacc = pin(&g_scr.acc[layer][(54 * c + tid) * ACC_STR]);
            const int w = 2 * min(tid, 47);
            const uint32_t d0 = pin(sb + SM_OS + 4 * (24 * ((w >> 3) & 3) + ((w >> 2) & 1) + (w < 64 ? 4 * (w & 3) + 2 * (w >> 5) : 16 + 2 * (w & 3))));
            const uint32_t d1 = pin(d0 + (w < 64 ? 16 : 8));
            const uint4* pp[3];
#pragma unroll
            for (int k = 0; k < 3; k++) pp[k] = pin(&g_scr.hx[(h * 4 + ((c + 1 + k) & 3)) * 48 + min(tid, 47)]);
            uint4 v3[3];
#pragma unroll
            for (int k = 0; k < 3; k++) v3[k] = make_uint4(0u, 0u, 0u, 1u);
            if ((PRE1 & 8) && layer) {
#pragma unroll
                for (int ks = 0; ks < 3; ks++) {
                    mbar_wait(wbar + 8 * ks, wo2);
#pragma unroll
                    for (int i = 0; i < 5; i++) ldsm4t(aw[i] + (ks == 2 ? aw2 : 20480 * ks), kq[3 * i + ks]);
                    if (ks == CXE && wu < 2) {
#pragma unroll
                        for (int k = 0; k < 3; k++) v3[k] = ld_pkt(pp[k]);
                    }
                }
                PROF_T(50);
            }
            if (wu < 2) {
                for (int it = 0; any_odd(v3[0].w, v3[1].w, v3[2].w) && it < SPIN_CAP; it++) {
#pragma unroll
                    for (int k = 0; k < 3; k++) v3[k] = ld_pkt(pp[k]);
                }
                o.x = (o.x + f_(v3[0].x)) + (f_(v3[1].x) + f_(v3[2].x)); o.y = (o.y + f_(v3[0].y)) + (f_(v3[1].y) + f_(v3[2].y));
                o.z = (o.z + f_(v3[0].z)) + (f_(v3[1].z) + f_(v3[2].z)); o.w = (o.w + f_(v3[0].w)) + (f_(v3[1].w) + f_(v3[2].w));
                sts32p(d0, f_(pack2(o.x, o.y)), tid >= 48);
                sts32p(d1, f_(pack2(o.z, o.w)), tid >= 48);
            }
            PC(layer * 32 + 3);
            __syncthreads();
            PROF_T(5 + layer * 16);
            PC(layer * 32 + 5);
            if (tid == 224 && layer == 0) {
                if (ticket >= 6 + ((b >> 3) & 1)) ticket = DN0 + NDN;
                else asm volatile("atom.relaxed.gpu.global.inc.u32 %0, [%1], 0x7fffffff;" : "=r"(ticket) : "l"(g_scr.ticket) : "memory");
            }
            uint32_t ob[6];
            lds128(ao, ob[0], ob[1], ob[2], ob[3]);
            lds64(ao + 64 - 8 * t, ob[4], ob[5]);
            float cc[5][4];
#pragma unroll
            for (int i = 0; i < 5; i++) cc[i][0] = cc[i][1] = cc[i][2] = cc[i][3] = 0.f;
            if ((PRE1 & 8) && layer) {
#pragma unroll
                for (int ks = 0; ks < 3; ks++) {
#pragma unroll
                    for (int i = 0; i < 5; i++) mma16816(cc[i], kq[3 * i + ks][0], kq[3 * i + ks][1], kq[3 * i + ks][2], kq[3 * i + ks][3], ob[2 * ks], ob[2 * ks + 1]);
                }
            } else {
#pragma unroll
                for (int ks = 0; ks < 3; ks++) {
                    mbar_wait(wbar + 8 * ks, wo2);
                    if (ks == 2) { PC(layer * 32 + 4); PROF_T(48 + layer * 2); }
                    uint32_t a[5][4];
#pragma unroll
                    for (int i = 0; i < 5; i++) ldsm4t(aw[i] + (ks == 2 ? aw2 : 20480 * ks), a[i]);
#pragma unroll
                    for (int i = 0; i < 5; i++) mma16816(cc[i], a[i][0], a[i][1], a[i][2], a[i][3], ob[2 * ks], ob[2 * ks + 1]);
                }
            }
            if (t == 0) {
#pragma unroll
                for (int i = 0; i < 5; i++) { sts32(dw + 512 * i, cc[i][0]); sts32(dw + 512 * i + 128, cc[i][2]); }
            }
        }
        PC(layer * 32 + 6);
        __syncthreads();
        PROF_T(6 + layer * 16);
        PC(layer * 32 + 7);
        if (tid < 54) {
            const float4 v0 = lds4f(pr), v1 = lds4f(pr + 16), v2 = lds4f(pr + 32);
            const float y0 = (v0.x + v0.y) + (v0.z + v0.w), y1 = (v1.x + v1.y) + (v1.z + v1.w), y2 = (v2.x + v2.y) + (v2.z + v2.w);
            red_pkt(pacc, y0, tid == 53 ? 0.f : y1, tid == 53 ? 0.f : y2);
        }
        if (tid == 224 && layer == 0) {
            misc[1] = __uint_as_float(ticket);
            if (ticket < DN0 + NDN && (ticket < NG || !DNTH)) load_ffn(maps, ticket, sb + SM_B, fbar);
        }
        PROF_T(7 + layer * 16);
        PC(layer * 32 + 8);
        __syncthreads();
        const int role = (int)__float_as_uint(misc[1]);
        PC(layer * 32 + 9);
        const uint32_t fbase = sb + SM_B;
        const uint32_t DONE32 = 0x42000000u;
        if (role < NG) {
            const int tid = opq(threadIdx.x), warp = tid >> 5, lane = tid & 31, g = lane >> 2, t = lane & 3, mat = lane >> 3, r8 = lane & 7;
            const uint32_t ag = fbase + (80 * warp + (mat >> 1) * 8 + r8) * 96 + (((mat & 1) ^ (r8 >> 2)) << 4);
            constexpr int GI = 32, GK = 16 * 96;
            const bool on = (g & 1) == (t >> 1), isx = on && g < 2;
            const uint32_t pm = opq(isx ? sb + SM_XS + 160 * warp + 16 * t : sb + (on ? SM_ONE : SM_ZERO)), pm2 = opq(pm + 128 - (isx ? 8 * t : 0));
            const uint32_t dg = opq(sb + SM_R + 4 * (2 * (warp * 48 + g) + t)), ds = opq(sb + SM_ST + 8 * warp + (lane < 16 ? 4 : 0));
            const bool ws = (lane & 15) == 0, lo = lane < 16;
            uint32_t pre[6][4];
            float s1 = 0.f, s2 = 0.f;
            {
                bool hx = wu == 7;
                int it = 0;
                const uint4* px = &g_scr.acc[layer][min(tid, 215) * ACC_STR];
                const int cq = tid / 54, r = tid - 54 * cq, k0 = min(160 * cq + 3 * r, DM - 1);
                const uint32_t w0 = sb + SM_XS + 4 * xpos(k0 >> 1), w1 = sb + SM_XS + 4 * xpos(min((k0 >> 1) + 1, DM / 2 - 1));
                const uint32_t e0 = w0 + 2 * (k0 & 1), e1 = (k0 & 1) ? w1 : w0 + 2, e2 = w1 + 2 * (k0 & 1);
                                auto sts16 = [](uint32_t a, uint32_t x, bool on) {
                    asm volatile("{\n.reg .pred p;\nsetp.ne.u32 p, %2, 0;\n@p st.shared.u16 [%0], %1;\n}" ::"r"(a), "h"((unsigned short)x), "r"((uint32_t)on) : "memory");
                };
                const bool on0 = tid < 216, on1 = on0 && r != 53;
                const float x0 = on0 ? f_(lds16(e0) << 16) : 0.f, x1 = on1 ? f_(lds16(e1) << 16) : 0.f, x2 = on1 ? f_(lds16(e2) << 16) : 0.f;
                auto take_x = [&](const uint4 v) {
                    if (__all_sync(0xffffffffu, v.w == DONE32)) {
                        hx = true;
                        const uint32_t a = pack2(f_(v.x), f_(v.y)), p = pack2(x0 + bf_lo(a), x1 + bf_hi(a)), q = pack2(x2 + bfr(f_(v.z)), 0.f);
                        sts16(e0, p, on0); sts16(e1, p >> 16, on1); sts16(e2, q, on1);
                        const float y0 = on0 ? bf_lo(p) : 0.f, y1 = on0 ? bf_hi(p) : 0.f, y2 = on0 ? bf_lo(q) : 0.f;
                        s1 = y0 + (y1 + y2); s2 = y0 * y0 + (y1 * y1 + y2 * y2);
                    }
                };
                auto try_x = [&]() { take_x(ld_pkt(px)); };
                while (!mbar_test(fbar, 0) && ++it < SPIN_CAP) { if (!hx) try_x(); }
                uint4 v0 = make_uint4(0u, 0u, 0u, 0u);
                if ((PRE1 & 4) && !hx) v0 = ld_pkt(px);
#pragma unroll
                for (int n = 0; n < 6; n++) ldsm4t(ag + (n % 3) * GI + (n / 3) * GK, pre[n]);
                if ((PRE1 & 1) && layer) {
#pragma unroll
                    for (int n = 6; n < 15; n++) ldsm4t(ag + (n % 3) * GI + (n / 3) * GK, kq[n - 6]);
                }
                if ((PRE1 & 4) && !hx) take_x(v0);
                PC(layer * 32 + 10);
                while (!hx && ++it < SPIN_CAP) try_x();
                PC(layer * 32 + 11);
            __syncthreads();
            PC(layer * 32 + 12);
            PROF_T(9 + layer * 16);
            float sv = lo ? s1 : s2, cc[3][4];
            if ((PRE1 & 1) && layer) gemv15r(cc, pre, kq, pm, pm2, sv, lo ? s2 : s1);
            else gemv15<GK>(cc, pre, [&](int i) { return ag + i * GI; }, pm, pm2, sv, lo ? s2 : s1);
#pragma unroll
            for (int i = 0; i < 3; i++) { sts32p(dg + 128 * i, cc[i][0] + cc[i][3], t & 2); sts32p(dg + 128 * i + 64, cc[i][1] + cc[i][2], t & 2); }
            if (ws) sts32(ds, sv);
            const uint32_t pg = opq(sb + SM_R + 8 * (24 * warp + (lane < 24 ? lane : 0))), st = opq(sb + SM_ST);
            uint4* const ph = opq(lane < 24 && lane % 6 == 0 ? &g_scr.ah[role * 8 + 4 * warp + lane / 6] : nullptr);
            PC(layer * 32 + 13);
            __syncthreads();
            PC(layer * 32 + 14);
            PROF_T(43 + layer * 16);
            if (wu < 2) {
                float mean, inv;
                ln_stats(st, mean, inv);
                float2 v[8];
#pragma unroll
                for (int w = 0; w < 8; w++) v[w] = lds2f(pg + w * 384);
                const float gx = ((v[0].x + v[1].x) + (v[2].x + v[3].x)) + ((v[4].x + v[5].x) + (v[6].x + v[7].x));
                const float gs = ((v[0].y + v[1].y) + (v[2].y + v[3].y)) + ((v[4].y + v[5].y) + (v[6].y + v[7].y));
                float ga = inv * (gx - mean * gs);
                if (role < NG / 2) { ga = bfr(ga); ga *= rcp(1.0f + ex2(-1.4426950408889634f * ga)); }
                const uint32_t wd = pack2(ga, __shfl_down_sync(0xffffffffu, ga, 1));
                const uint32_t wa = __shfl_down_sync(0xffffffffu, wd, 2), wb = __shfl_down_sync(0xffffffffu, wd, 4);
                if (ph) st_pkt(ph, wd, wa, wb, tag);
            }
            if (HOLD & 2) __syncthreads();
            }
            PROF_T(10 + layer * 16);
            PC(layer * 32 + 15);
        } else if (role < DN0 + NDN) {
            const int j = role - DN0;
            const int tid = opq(threadIdx.x), warp = tid >> 5, lane = tid & 31, g = lane >> 2, t = lane & 3, mat = lane >> 3, r8 = lane & 7;
            float xres = 0.f;
            uint32_t xr0 = 0, xr1 = 0;
            if (wu == 0) {
                const int col = 16 * j + (lane & 15), cc = col / 160, r = col - 160 * cc, e = r % 3;
                const uint4* px = &g_scr.acc[layer][(54 * cc + r / 3) * ACC_STR];
                const float x0 = __bfloat162float(reinterpret_cast<const __nv_bfloat16*>(xs32)[2 * xpos(col >> 1) + (col & 1)]);
                uint4 v;
                int it = 0;
                bool ld = DNTH && layer == 0;
                do {
                    v = ld_pkt(px);
                    if (ld && f_(__shfl_sync(0xffffffffu, v.w, 0)) >= (float)DNTH) { ld = false; if (lane == 0) load_ffn(maps, role, sb + SM_B, fbar); }
                } while (!__all_sync(0xffffffffu, v.w == DONE32) && ++it < SPIN_CAP);
                if (ld && lane == 0) load_ffn(maps, role, sb + SM_B, fbar);
                xres = x0 + bfr(f_(e == 0 ? v.x : (e == 1 ? v.y : v.z)));
                const int p4 = 4 * (lane & 3);
                xr0 = pack2(__shfl_sync(0xffffffffu, xres, p4), __shfl_sync(0xffffffffu, xres, p4 + 1));
                xr1 = pack2(__shfl_sync(0xffffffffu, xres, p4 + 2), __shfl_sync(0xffffffffu, xres, p4 + 3));
            }
            PC(layer * 32 + 17);
            PROF_T(9 + layer * 16);
            const uint32_t ad = fbase + (192 * warp + (mat >> 1) * 8 + r8) * 32 + (((mat & 1) ^ (r8 >> 2)) << 4);
            uint32_t* hs = reinterpret_cast<uint32_t*>(rr) + warp * 96;
            uint32_t pre[NPRE][4];
            {
                uint32_t pos[3];
#pragma unroll
                for (int i = 0; i < 3; i++) { const int w = 3 * lane + i; pos[i] = pin(sb + SM_R + 384 * warp + 4 * ((w & ~15) + 4 * (w & 3) + ((w >> 2) & 1) + ((w >> 2) & 2))); }
                uint4 v = make_uint4(0u, 0u, 0u, 0u), u = v;
                if (layer == 0) { v = ld_pkt(&g_scr.ah[tid]); u = ld_pkt(&g_scr.ah[256 + tid]); }
                mbar_wait(fbar, 0);
#pragma unroll
                for (int n = 0; n < NPRE; n++) ldsm4t(ad + n * 512, pre[n]);
                if ((PRE1 & 2) && layer) {
#pragma unroll
                    for (int n = NPRE; n < 12; n++) ldsm4t(ad + n * 512, kq[12 + n]);
                }
                PC(layer * 32 + 18);
                int it = 0;
                for (; any_ne(v.w, u.w, tag) && it < SPIN_CAP; it++) { v = ld_pkt(&g_scr.ah[tid]); u = ld_pkt(&g_scr.ah[256 + tid]); }
                PC(layer * 32 + 19);
                sts32(pos[0], f_(bmul2(v.x, u.x))); sts32(pos[1], f_(bmul2(v.y, u.y))); sts32(pos[2], f_(bmul2(v.z, u.z)));
            __syncwarp();
            PROF_T(11 + layer * 16);
            PC(layer * 32 + 20);
            float ca[4] = {0.f, 0.f, 0.f, 0.f}, cb[4] = {0.f, 0.f, 0.f, 0.f};
            if ((PRE1 & 2) && layer) {
                float cc[4] = {0.f, 0.f, 0.f, 0.f}, cd[4] = {0.f, 0.f, 0.f, 0.f};
#pragma unroll
                for (int jj = 0; jj < 6; jj++) {
                    const uint4 hv = *reinterpret_cast<const uint4*>(hs + 16 * jj + 4 * t);
                    const uint32_t (&f0)[4] = 2 * jj < NPRE ? pre[2 * jj < NPRE ? 2 * jj : 0] : kq[12 + 2 * jj];
                    const uint32_t (&f1)[4] = 2 * jj + 1 < NPRE ? pre[2 * jj + 1 < NPRE ? 2 * jj + 1 : 0] : kq[13 + 2 * jj];
                    if (jj & 1) { mma16816(cc, f0[0], f0[1], f0[2], f0[3], hv.x, hv.y); mma16816(cd, f1[0], f1[1], f1[2], f1[3], hv.z, hv.w); }
                    else { mma16816(ca, f0[0], f0[1], f0[2], f0[3], hv.x, hv.y); mma16816(cb, f1[0], f1[1], f1[2], f1[3], hv.z, hv.w); }
                }
#pragma unroll
                for (int e = 0; e < 4; e++) { ca[e] += cc[e]; cb[e] += cd[e]; }
            } else {
#pragma unroll
                for (int jj = 0; jj < 6; jj++) {
                    const uint4 hv = *reinterpret_cast<const uint4*>(hs + 16 * jj + 4 * t);
                    uint32_t a[4];
                    if (2 * jj < NPRE) { a[0] = pre[2 * jj][0]; a[1] = pre[2 * jj][1]; a[2] = pre[2 * jj][2]; a[3] = pre[2 * jj][3]; }
                    else ldsm4t(ad + 2 * jj * 512, a);
                    mma16816(ca, a[0], a[1], a[2], a[3], hv.x, hv.y);
                    if (2 * jj + 1 < NPRE) { a[0] = pre[2 * jj + 1][0]; a[1] = pre[2 * jj + 1][1]; a[2] = pre[2 * jj + 1][2]; a[3] = pre[2 * jj + 1][3]; }
                    else ldsm4t(ad + (2 * jj + 1) * 512, a);
                    mma16816(cb, a[0], a[1], a[2], a[3], hv.z, hv.w);
                }
            }
            if (t == 0) { rr[768 + warp * 16 + g] = ca[0] + cb[0]; rr[768 + warp * 16 + 8 + g] = ca[2] + cb[2]; }
            const uint32_t pd = opq(sb + SM_R + 3072 + 16 * (lane & 3));
            uint4* const py = opq(&g_scr.ay[j * 4 + lane]);
            uint2* const po = opq(reinterpret_cast<uint2*>(out + 16 * j) + lane);
            PC(layer * 32 + 21);
            __syncthreads();
            PC(layer * 32 + 22);
            if (wu == 0) {
                float4 p[8];
#pragma unroll
                for (int w = 0; w < 8; w++) p[w] = lds4f(pd + 64 * w);
                const uint32_t y0 = pack2(((p[0].x + p[1].x) + (p[2].x + p[3].x)) + ((p[4].x + p[5].x) + (p[6].x + p[7].x)),
                                          ((p[0].y + p[1].y) + (p[2].y + p[3].y)) + ((p[4].y + p[5].y) + (p[6].y + p[7].y)));
                const uint32_t y1 = pack2(((p[0].z + p[1].z) + (p[2].z + p[3].z)) + ((p[4].z + p[5].z) + (p[6].z + p[7].z)),
                                          ((p[0].w + p[1].w) + (p[2].w + p[3].w)) + ((p[4].w + p[5].w) + (p[6].w + p[7].w)));
                uint32_t wd, wn;
                asm("add.rn.bf16x2 %0, %1, %2;" : "=r"(wd) : "r"(xr0), "r"(y0));
                asm("add.rn.bf16x2 %0, %1, %2;" : "=r"(wn) : "r"(xr1), "r"(y1));
                asm volatile("{\n.reg .pred p;\nsetp.ne.u32 p, %3, 0;\n@p st.global.v2.u32 [%0], {%1,%2};\n}" ::"l"(po), "r"(wd), "r"(wn), "r"((uint32_t)(layer && tid < 4)) : "memory");
                st_pktp(py, wd, wn, 0, tag, tid < 4);
            }
            if (HOLD & 1) __syncthreads();
            }
            PROF_T(12 + layer * 16);
            PC(layer * 32 + 23);
        }
    }
}

typedef CUresult (*EncodeFn)(CUtensorMap*, CUtensorMapDataType, cuuint32_t, void*, const cuuint64_t*, const cuuint64_t*, const cuuint32_t*,
                             const cuuint32_t*, CUtensorMapInterleave, CUtensorMapSwizzle, CUtensorMapL2promotion, CUtensorMapFloatOOBfill);

void make_map(EncodeFn enc, CUtensorMap* m, const void* base, int rank, uint64_t d0, uint64_t d1, uint64_t d2, uint64_t s1, uint64_t s2,
              uint32_t b0, uint32_t b1, uint32_t b2, CUtensorMapSwizzle sw, CUtensorMapL2promotion pr = CU_TENSOR_MAP_L2_PROMOTION_NONE) {
    cuuint64_t dims[3] = {d0, d1, d2};
    cuuint64_t strides[2] = {s1, s2};
    cuuint32_t box[3] = {b0, b1, b2};
    cuuint32_t es[3] = {1, 1, 1};
    enc(m, CU_TENSOR_MAP_DATA_TYPE_BFLOAT16, rank, const_cast<void*>(base), dims, strides, box, es, CU_TENSOR_MAP_INTERLEAVE_NONE, sw,
        pr, CU_TENSOR_MAP_FLOAT_OOB_FILL_NONE);
}

}

extern "C" void kernel_launch(void* const* d_in, const int* in_sizes, int n_in, void* d_out, int out_size) {
    (void)in_sizes; (void)n_in; (void)out_size;
    static EncodeFn enc = nullptr;
    if (!enc) {
        void* fn = nullptr;
        cudaDriverEntryPointQueryResult qr;
        cudaGetDriverEntryPoint("cuTensorMapEncodeTiled", &fn, cudaEnableDefault, &qr);
        enc = reinterpret_cast<EncodeFn>(fn);
        cudaFuncSetAttribute(decode_kernel, cudaFuncAttributeMaxDynamicSharedMemorySize, SM_TOTAL);
    }
    Maps maps;
    make_map(enc, &maps.k, d_in[1], 2, 64, (uint64_t)NH * SK * 3, 1, 128, 0, 64, 48, 1, CU_TENSOR_MAP_SWIZZLE_128B);
    make_map(enc, &maps.v, d_in[2], 2, 64, (uint64_t)NH * SK * 3, 1, 128, 0, 64, 48, 1, CU_TENSOR_MAP_SWIZZLE_128B);
    make_map(enc, &maps.wq, d_in[3], 3, 64, DM, NH * DH / 64, NH * DH * 2, 128, 64, 160, 3, CU_TENSOR_MAP_SWIZZLE_128B);
    make_map(enc, &maps.wo, d_in[4], 3, 32, DM / 32, NH * DH, 64, DM * 2, 32, 5, 32, CU_TENSOR_MAP_SWIZZLE_64B);
    make_map(enc, &maps.vr, (const char*)d_in[2] + 512, 2, 128, (uint64_t)NH * SK / 2, 1, 768, 0, 128, 2, 1, CU_TENSOR_MAP_SWIZZLE_NONE);
    constexpr int GW = 48;
    make_map(enc, &maps.w1, d_in[6], 3, FF, 160, 4, FF * 2, 160 * FF * 2, GW, 160, 4, CU_TENSOR_MAP_SWIZZLE_NONE, FFN_PROMO);
    make_map(enc, &maps.w3, d_in[7], 3, FF, 160, 4, FF * 2, 160 * FF * 2, GW, 160, 4, CU_TENSOR_MAP_SWIZZLE_NONE, FFN_PROMO);
    make_map(enc, &maps.w2, d_in[8], 3, DM, 256, 6, DM * 2, 256 * DM * 2, 16, 256, 6, CU_TENSOR_MAP_SWIZZLE_32B, FFN_PROMO);
    maps.vp = d_in[2];
    maps.kp = d_in[1];
    maps.zero = 0;
    decode_kernel<<<NCTA, NT, SM_TOTAL, cudaStreamPerThread>>>(maps, (const __nv_bfloat16*)d_in[0], (__nv_bfloat16*)d_out);
}
```

```cpp
#include <cuda_runtime.h>
#include <cuda_bf16.h>
#include <cuda.h>
#include <stdint.h>
#include <math.h>

namespace {

constexpr int DM = 640;
constexpr int NH = 32;
constexpr int DH = 192;
constexpr int SK = 32768;
constexpr int WIN = 4096;
constexpr int FF = 1536;
constexpr int NCTA = 128;
constexpr int NT = 256;
constexpr int TILE = 6144;
constexpr int NG = 64;
constexpr int DN0 = 64;
constexpr int NDN = 40;

constexpr int SM_RING = 0;
constexpr int SM_B = 8 * 2 * TILE;
constexpr int SM_Q = SM_B + 61440;
__host__ __device__ constexpr int c_slot(int w) { return w < 2 ? 4096 + 10240 * w : 12288 + 6144 * w; }
__host__ __device__ constexpr int v1_pos(int n) { return 10240 * (n >> 3) + 512 * (n & 7); }
constexpr int SM_XS = SM_Q + 61440;
constexpr int SM_R = SM_XS + 1280;
constexpr int SM_ST = SM_R + 4096;
constexpr int SM_QS = SM_R + 6272;
constexpr int SM_OS = SM_QS + 384;
constexpr int SM_BAR = SM_OS + 384;
constexpr int SM_XBAR = SM_BAR + 24 * 8;
constexpr int SM_MISC = SM_XBAR + 8 * 8;
constexpr int SM_ONE = SM_MISC + 16;
constexpr int SM_ZERO = SM_ONE + 160;
constexpr int XCAP = 48;
constexpr int XSTR = 16 + 4 * XCAP;
constexpr int SM_XL = SM_ZERO + 160;
constexpr int SM_TOTAL = SM_XL + 8 * XSTR;
static_assert(SM_TOTAL <= 232448, "shared memory");

constexpr unsigned long long POL_EF = 0x12F0000000000000ull;
constexpr unsigned long long POL_EN = 0x16F0000000000000ull;

#define RT_MASK 0xF2E0u
#define RT_MASK2 0xEAE0u
#define WO_AT1 5
#define FFN_PROMO CU_TENSOR_MAP_L2_PROMOTION_NONE
#define FFN_POL POL_EF
#define HAS_FFN (__float_as_uint(misc[1]) < DN0 + NDN)
#define ACC_STR 1
#define NPRE 6

#define STAG 200
#define L1R 3
#define PRE1 13
#define HOLD 2
#define DNTH 23
constexpr int V0_AT = 8;
constexpr unsigned long long SEQ1 = 0x2765431076543210ull;
constexpr uint32_t IN_S1 = 0xAA49, IN_S0 = 0x124, PARITY1 = 0x6638, PARITY2 = 0xCE;
#define KEEP4 1
constexpr int NQ = 48;
constexpr int SPIN_CAP = 1 << 19;
constexpr uint32_t ONES = 0x3F803F80u;

struct alignas(1024) Scratch {
    uint4 hx[NCTA * 48];
    uint4 pad0[32 * 5 * 32 + 160];
    uint4 acc[2][216 * 8];
    uint4 ay[160];
    uint4 ah[NG * 8];
    uint2 mx[NH * 32];
    uint32_t ticket[32];
    uint32_t pad1[32];
};
__device__ Scratch g_scr;
#define PROF_T(i)
#define PROF_X(i)
#define PC(i)

__device__ __forceinline__ uint32_t smem_u32(const void* p) { return (uint32_t)__cvta_generic_to_shared(p); }
__device__ __forceinline__ void mbar_init(uint32_t bar, uint32_t cnt) {
    asm volatile("mbarrier.init.shared::cta.b64 [%0], %1;" ::"r"(bar), "r"(cnt) : "memory");
}
__device__ __forceinline__ void mbar_expect_tx(uint32_t bar, uint32_t bytes) {
    asm volatile("mbarrier.arrive.expect_tx.shared::cta.b64 _, [%0], %1;" ::"r"(bar), "r"(bytes) : "memory");
}
__device__ __forceinline__ bool mbar_test(uint32_t bar, uint32_t parity) {
    uint32_t done;
    asm volatile("{\n.reg .pred p;\nmbarrier.try_wait.parity.shared::cta.b64 p, [%1], %2;\nselp.u32 %0, 1, 0, p;\n}"
                 : "=r"(done) : "r"(bar), "r"(parity) : "memory");
    return done;
}
__device__ __forceinline__ void mbar_wait(uint32_t bar, uint32_t parity) {
    int it = 0;
    while (!mbar_test(bar, parity) && ++it < SPIN_CAP) {}
}
__device__ __forceinline__ void tma2d(uint32_t dst, const CUtensorMap* map, int c0, int c1, uint32_t bar, unsigned long long pol) {
    asm volatile("cp.async.bulk.tensor.2d.shared::cluster.global.mbarrier::complete_tx::bytes.L2::cache_hint [%0], [%1, {%3, %4}], [%2], %5;"
                 ::"r"(dst), "l"(map), "r"(bar), "r"(c0), "r"(c1), "l"(pol) : "memory");
}
__device__ __forceinline__ void tma3d(uint32_t dst, const CUtensorMap* map, int c0, int c1, int c2, uint32_t bar, unsigned long long pol) {
    asm volatile("cp.async.bulk.tensor.3d.shared::cluster.global.mbarrier::complete_tx::bytes.L2::cache_hint [%0], [%1, {%3, %4, %5}], [%2], %6;"
                 ::"r"(dst), "l"(map), "r"(bar), "r"(c0), "r"(c1), "r"(c2), "l"(pol) : "memory");
}
__device__ __forceinline__ void tile_load(uint32_t dst, const CUtensorMap* map, int row, uint32_t bar, uint32_t dep, uint32_t zero) {
    asm volatile("{\n.reg .pred p;\n.reg .b32 n;\nmad.lo.u32 n, %5, %6, 6144;\nelect.sync _|p, 0xffffffff;\n"
                 "@p mbarrier.arrive.expect_tx.shared::cta.b64 _, [%2], n;\n"
                 "@p cp.async.bulk.tensor.2d.shared::cluster.global.mbarrier::complete_tx::bytes.L2::cache_hint [%0], [%1, {0, %3}], [%2], %4;\n}"
                 ::"r"(dst), "l"(map), "r"(bar), "r"(row), "l"(POL_EF), "r"(dep), "r"(zero) : "memory");
}
__device__ __forceinline__ void tile_keep(const CUtensorMap* map, int row) {
    asm volatile("{\n.reg .pred p;\nelect.sync _|p, 0xffffffff;\n"
                 "@p cp.async.bulk.prefetch.tensor.2d.L2.global.L2::cache_hint [%0, {0, %1}], %2;\n}"
                 ::"l"(map), "r"(row), "l"(POL_EN) : "memory");
}
__device__ __forceinline__ void tile_load_l1(uint32_t dst, const void* base, int row, uint32_t bar, int lane) {
    const char* g = static_cast<const char*>(base) + (size_t)row * 128 + lane * 16;
    const uint32_t s0 = dst + (lane >> 3) * 128 + (((lane & 7) ^ (lane >> 3)) << 4), s1 = s0 ^ 64;
#pragma unroll
    for (int k = 0; k < 12; k++)
        asm volatile("cp.async.ca.shared.global.L2::cache_hint [%0], [%1], 16, %2;" ::"r"(((k & 1) ? s1 : s0) + k * 512), "l"(g + k * 512), "l"(POL_EF) : "memory");
    asm volatile("cp.async.mbarrier.arrive.shared::cta.b64 [%0];" ::"r"(bar) : "memory");
    __syncwarp();
    if (lane == 0) asm volatile("mbarrier.arrive.shared::cta.b64 _, [%0];" ::"r"(bar) : "memory");
}
__device__ __forceinline__ bool elect_one() {
    uint32_t p;
    asm volatile("{\n.reg .pred p;\nelect.sync _|p, 0xffffffff;\nselp.u32 %0, 1, 0, p;\n}" : "=r"(p));
    return p;
}
__device__ __forceinline__ void lds128(uint32_t addr, uint32_t& a, uint32_t& b, uint32_t& c, uint32_t& d) {
    asm volatile("ld.shared.v4.u32 {%0,%1,%2,%3}, [%4];" : "=r"(a), "=r"(b), "=r"(c), "=r"(d) : "r"(addr) : "memory");
}
__device__ __forceinline__ void lds128p(uint32_t addr, uint32_t on, uint32_t& a, uint32_t& b, uint32_t& c, uint32_t& d) {
    asm volatile("{\n.reg .pred p;\nsetp.ne.u32 p, %5, 0;\n@p ld.shared.v4.u32 {%0,%1,%2,%3}, [%4];\n}" : "+r"(a), "+r"(b), "+r"(c), "+r"(d) : "r"(addr), "r"(on) : "memory");
}
__device__ __forceinline__ void lds64(uint32_t addr, uint32_t& a, uint32_t& b) {
    asm volatile("ld.shared.v2.u32 {%0,%1}, [%2];" : "=r"(a), "=r"(b) : "r"(addr) : "memory");
}
__device__ __forceinline__ void ldsm4t(uint32_t addr, uint32_t (&a)[4]) {
    asm volatile("ldmatrix.sync.aligned.m8n8.x4.trans.shared.b16 {%0,%1,%2,%3}, [%4];" : "=r"(a[0]), "=r"(a[1]), "=r"(a[2]), "=r"(a[3]) : "r"(addr) : "memory");
}
__device__ __forceinline__ void mma16816(float (&c)[4], uint32_t a0, uint32_t a1, uint32_t a2, uint32_t a3, uint32_t b0, uint32_t b1) {
    asm("mma.sync.aligned.m16n8k16.row.col.f32.bf16.bf16.f32 {%0,%1,%2,%3}, {%4,%5,%6,%7}, {%8,%9}, {%0,%1,%2,%3};"
        : "+f"(c[0]), "+f"(c[1]), "+f"(c[2]), "+f"(c[3]) : "r"(a0), "r"(a1), "r"(a2), "r"(a3), "r"(b0), "r"(b1));
}
__device__ __forceinline__ void mma16816v(float (&c)[4], uint32_t a0, uint32_t a1, uint32_t a2, uint32_t a3, uint32_t b0, uint32_t b1) {
    asm volatile("mma.sync.aligned.m16n8k16.row.col.f32.bf16.bf16.f32 {%0,%1,%2,%3}, {%4,%5,%6,%7}, {%8,%9}, {%0,%1,%2,%3};"
        : "+f"(c[0]), "+f"(c[1]), "+f"(c[2]), "+f"(c[3]) : "r"(a0), "r"(a1), "r"(a2), "r"(a3), "r"(b0), "r"(b1));
}
__device__ __forceinline__ int xpos(int w) {
    const int seg = w / 40, r = w - 40 * seg;
    return 40 * seg + (r < 32 ? (r & 16) + 4 * (r & 3) + ((r >> 2) & 3) : 32 + 2 * (r & 3) + ((r >> 2) & 1));
}
#define NA_LD ""
#define NA_ST ""
__device__ __forceinline__ void st_pkt(uint4* p, uint32_t a, uint32_t b, uint32_t c, uint32_t d) {
    asm volatile("{\n.reg .b128 t;\n.reg .b64 lo, hi;\nmov.b64 lo, {%1,%2};\nmov.b64 hi, {%3,%4};\nmov.b128 t, {lo,hi};\nst.relaxed.gpu.global" NA_ST ".b128 [%0], t;\n}"
                 ::"l"(p), "r"(a), "r"(b), "r"(c), "r"(d) : "memory");
}
__device__ __forceinline__ void red_pkt(uint4* p, float a, float b, float c) {
    asm volatile("red.relaxed.gpu.global.add.v4.f32 [%0], {%1,%2,%3,%4};" ::"l"(p), "f"(a), "f"(b), "f"(c), "f"(1.0f) : "memory");
}
__device__ __forceinline__ void st_pktp(uint4* p, uint32_t a, uint32_t b, uint32_t c, uint32_t d, bool on) {
    asm volatile("{\n.reg .pred p;\n.reg .b128 t;\n.reg .b64 lo, hi;\nsetp.ne.u32 p, %5, 0;\nmov.b64 lo, {%1,%2};\nmov.b64 hi, {%3,%4};\nmov.b128 t, {lo,hi};\n"
                 "@p st.relaxed.gpu.global.b128 [%0], t;\n}" ::"l"(p), "r"(a), "r"(b), "r"(c), "r"(d), "r"((uint32_t)on) : "memory");
}
__device__ __forceinline__ void st_pktfp(uint4* p, float a, float b, float c, float d, uint32_t bit, bool on) {
    st_pktp(p, __float_as_uint(a), __float_as_uint(b), __float_as_uint(c), (__float_as_uint(d) & ~1u) | bit, on);
}
__device__ __forceinline__ uint4 ld_pkt(const uint4* p) {
    uint4 v;
    asm volatile("{\n.reg .b128 t;\n.reg .b64 lo, hi;\nld.relaxed.gpu.global" NA_LD ".b128 t, [%4];\nmov.b128 {lo,hi}, t;\nmov.b64 {%0,%1}, lo;\nmov.b64 {%2,%3}, hi;\n}"
                 : "=r"(v.x), "=r"(v.y), "=r"(v.z), "=r"(v.w) : "l"(p) : "memory");
    return v;
}
__device__ __forceinline__ bool all_odd(uint32_t a, uint32_t b, uint32_t c, uint32_t d) {
    uint32_t r;
    asm volatile("{\n.reg .pred p, q, t;\n.reg .b32 x;\nsetp.eq.b32 t, 0, 0;\nlop3.b32 x, %1, %2, %3, 0x80;\nlop3.and.b32 _|p, x, %4, 1, 0x80, t;\n"
                 "vote.sync.all.pred q, p, 0xffffffff;\nselp.u32 %0, 1, 0, q;\n}" : "=r"(r) : "r"(a), "r"(b), "r"(c), "r"(d));
    return r;
}
__device__ __forceinline__ bool any_odd(uint32_t a, uint32_t b, uint32_t c) {
    uint32_t r;
    asm volatile("{\n.reg .pred p, q, t;\n.reg .b32 x;\nsetp.eq.b32 t, 0, 0;\nlop3.b32 x, %1, %2, %3, 0xFE;\nlop3.and.b32 _|p, x, 1, 0, 0xC0, t;\n"
                 "vote.sync.any.pred q, p, 0xffffffff;\nselp.u32 %0, 1, 0, q;\n}" : "=r"(r) : "r"(a), "r"(b), "r"(c));
    return r;
}
__device__ __forceinline__ bool any_ne(uint32_t a, uint32_t b, uint32_t c) {
    uint32_t r;
    asm volatile("{\n.reg .pred p, q, t;\nsetp.eq.b32 t, 0, 0;\nlop3.and.b32 _|p, %1, %2, %3, 0x7E, t;\n"
                 "vote.sync.any.pred q, p, 0xffffffff;\nselp.u32 %0, 1, 0, q;\n}" : "=r"(r) : "r"(a), "r"(b), "r"(c));
    return r;
}
__device__ __forceinline__ uint2 ld_pkt2(const uint2* p) {
    unsigned long long v;
    asm volatile("ld.relaxed.gpu.global" NA_LD ".b64 %0, [%1];" : "=l"(v) : "l"(p) : "memory");
    return make_uint2((uint32_t)v, (uint32_t)(v >> 32));
}
__device__ __forceinline__ void st_pkt2(uint2* p, uint32_t a, uint32_t b) {
    asm volatile("st.relaxed.gpu.global" NA_ST ".b64 [%0], %1;" ::"l"(p), "l"((unsigned long long)a | ((unsigned long long)b << 32)) : "memory");
}
__device__ __forceinline__ float ex2(float x) { float y; asm("ex2.approx.ftz.f32 %0, %1;" : "=f"(y) : "f"(x)); return y; }
__device__ __forceinline__ float rcp(float x) { float y; asm("rcp.approx.ftz.f32 %0, %1;" : "=f"(y) : "f"(x)); return y; }
__device__ __forceinline__ uint32_t pack2(float lo, float hi) {
    uint32_t r; asm("cvt.rn.bf16x2.f32 %0, %1, %2;" : "=r"(r) : "f"(hi), "f"(lo)); return r;
}
__device__ __forceinline__ float bf_lo(uint32_t w) { return __uint_as_float(w << 16); }
__device__ __forceinline__ float bf_hi(uint32_t w) { return __uint_as_float(w & 0xffff0000u); }
__device__ __forceinline__ float bfr(float x) { return bf_lo(pack2(x, 0.f)); }
__device__ __forceinline__ float f_(uint32_t u) { return __uint_as_float(u); }

template <int SK, typename AddrF>
__device__ __forceinline__ void gemv15(float (&cc)[3][4], uint32_t (&pre)[6][4], AddrF ad, uint32_t px, uint32_t px2, float& sv, float so) {
    uint32_t x0[4], x1[4], a[3][4];
    asm volatile("ld.shared.v4.u32 {%0,%1,%2,%3}, [%20];\nld.shared.v4.u32 {%4,%5,%6,%7}, [%20+64];\n"
                 "ldmatrix.sync.aligned.m8n8.x4.trans.shared.b16 {%8,%9,%10,%11}, [%21];\n"
                 "ldmatrix.sync.aligned.m8n8.x4.trans.shared.b16 {%12,%13,%14,%15}, [%22];\n"
                 "ldmatrix.sync.aligned.m8n8.x4.trans.shared.b16 {%16,%17,%18,%19}, [%23];\nbar.warp.sync 0xffffffff;"
                 : "=r"(x0[0]), "=r"(x0[1]), "=r"(x0[2]), "=r"(x0[3]), "=r"(x1[0]), "=r"(x1[1]), "=r"(x1[2]), "=r"(x1[3]),
                   "=r"(a[0][0]), "=r"(a[0][1]), "=r"(a[0][2]), "=r"(a[0][3]), "=r"(a[1][0]), "=r"(a[1][1]), "=r"(a[1][2]), "=r"(a[1][3]),
                   "=r"(a[2][0]), "=r"(a[2][1]), "=r"(a[2][2]), "=r"(a[2][3])
                 : "r"(px), "r"(ad(0) + 2 * SK), "r"(ad(1) + 2 * SK), "r"(ad(2) + 2 * SK) : "memory");
    __syncwarp();
    sv += __shfl_xor_sync(0xffffffffu, so, 16);
#pragma unroll
    for (int i = 0; i < 3; i++) {
        cc[i][0] = cc[i][1] = cc[i][2] = cc[i][3] = 0.f;
        mma16816v(cc[i], pre[i][0], pre[i][1], pre[i][2], pre[i][3], x0[0], x0[1]);
    }
    sv += __shfl_xor_sync(0xffffffffu, sv, 8);
#pragma unroll
    for (int i = 0; i < 3; i++) {
        mma16816v(cc[i], pre[3 + i][0], pre[3 + i][1], pre[3 + i][2], pre[3 + i][3], x0[2], x0[3]);
        ldsm4t(ad(i) + 3 * SK, pre[i]);
    }
    lds64(px2, x0[0], x0[1]);
    __syncwarp();
    sv += __shfl_xor_sync(0xffffffffu, sv, 4);
#pragma unroll
    for (int i = 0; i < 3; i++) {
        mma16816v(cc[i], a[i][0], a[i][1], a[i][2], a[i][3], x1[0], x1[1]);
        ldsm4t(ad(i) + 4 * SK, pre[3 + i]);
    }
    __syncwarp();
    sv += __shfl_xor_sync(0xffffffffu, sv, 2);
#pragma unroll
    for (int i = 0; i < 3; i++) mma16816v(cc[i], pre[i][0], pre[i][1], pre[i][2], pre[i][3], x1[2], x1[3]);
    sv += __shfl_xor_sync(0xffffffffu, sv, 1);
#pragma unroll
    for (int i = 0; i < 3; i++) mma16816v(cc[i], pre[3 + i][0], pre[3 + i][1], pre[3 + i][2], pre[3 + i][3], x0[0], x0[1]);
}
__device__ __forceinline__ void gemv15r(float (&cc)[3][4], const uint32_t (&pre)[6][4], const uint32_t (&ext)[NQ][4], uint32_t px, uint32_t px2, float& sv, float so) {
    uint32_t x0[4], x1[4], x2[2];
    float cd[3][4];
    lds128(px, x0[0], x0[1], x0[2], x0[3]);
    lds128(px + 64, x1[0], x1[1], x1[2], x1[3]);
    lds64(px2, x2[0], x2[1]);
    sv += __shfl_xor_sync(0xffffffffu, so, 16);
#pragma unroll
    for (int i = 0; i < 3; i++) {
        cc[i][0] = cc[i][1] = cc[i][2] = cc[i][3] = cd[i][0] = cd[i][1] = cd[i][2] = cd[i][3] = 0.f;
        mma16816v(cc[i], pre[i][0], pre[i][1], pre[i][2], pre[i][3], x0[0], x0[1]);
        mma16816v(cd[i], pre[3 + i][0], pre[3 + i][1], pre[3 + i][2], pre[3 + i][3], x0[2], x0[3]);
    }
    sv += __shfl_xor_sync(0xffffffffu, sv, 8);
#pragma unroll
    for (int i = 0; i < 3; i++) {
        mma16816v(cc[i], ext[i][0], ext[i][1], ext[i][2], ext[i][3], x1[0], x1[1]);
        mma16816v(cd[i], ext[3 + i][0], ext[3 + i][1], ext[3 + i][2], ext[3 + i][3], x1[2], x1[3]);
    }
    sv += __shfl_xor_sync(0xffffffffu, sv, 4);
#pragma unroll
    for (int i = 0; i < 3; i++) mma16816v(cc[i], ext[6 + i][0], ext[6 + i][1], ext[6 + i][2], ext[6 + i][3], x2[0], x2[1]);
    sv += __shfl_xor_sync(0xffffffffu, sv, 2);
    sv += __shfl_xor_sync(0xffffffffu, sv, 1);
#pragma unroll
    for (int i = 0; i < 3; i++) { cc[i][0] += cd[i][0]; cc[i][1] += cd[i][1]; cc[i][2] += cd[i][2]; cc[i][3] += cd[i][3]; }
}

__device__ __forceinline__ float warp_max(float x) {
    int i = __float_as_int(x);
    i = __reduce_max_sync(0xffffffffu, i ^ ((i >> 31) & 0x7fffffff));
    return __int_as_float(i ^ ((i >> 31) & 0x7fffffff));
}
__device__ __forceinline__ void idle(uint32_t clk) {
    uint32_t t0, t;
    asm volatile("mov.u32 %0, %%clock;" : "=r"(t0) :: "memory");
    do asm volatile("mov.u32 %0, %%clock;" : "=r"(t) :: "memory"); while (t - t0 < clk);
}
__device__ __forceinline__ uint32_t now_ns() { uint32_t t; asm volatile("mov.u32 %0, %%globaltimer_lo;" : "=r"(t)); return t; }
__device__ __forceinline__ int opq(int x) { asm volatile("" : "+r"(x)); return x; }
__device__ __forceinline__ uint32_t opq(uint32_t x) { asm volatile("" : "+r"(x)); return x; }
__device__ __forceinline__ uint32_t pin(uint32_t x) { return __shfl_sync(0xffffffffu, x, threadIdx.x & 31); }
template <typename T> __device__ __forceinline__ T* pin(T* p) {
    const unsigned long long v = (unsigned long long)p;
    return (T*)((unsigned long long)pin((uint32_t)v) | (unsigned long long)pin((uint32_t)(v >> 32)) << 32);
}
template <typename T> __device__ __forceinline__ T* opq(T* p) { asm volatile("" : "+l"(p)); return p; }
__device__ __forceinline__ float4 lds4f(uint32_t a) { float4 v; asm volatile("ld.shared.v4.f32 {%0,%1,%2,%3}, [%4];" : "=f"(v.x), "=f"(v.y), "=f"(v.z), "=f"(v.w) : "r"(a) : "memory"); return v; }
__device__ __forceinline__ float2 lds2f(uint32_t a) { float2 v; asm volatile("ld.shared.v2.f32 {%0,%1}, [%2];" : "=f"(v.x), "=f"(v.y) : "r"(a) : "memory"); return v; }
__device__ __forceinline__ void ln_stats(uint32_t st, float& mean, float& inv) {
    const float4 a = lds4f(st), b = lds4f(st + 16), c = lds4f(st + 32), d = lds4f(st + 48);
    const float s2 = ((a.x + a.z) + (b.x + b.z)) + ((c.x + c.z) + (d.x + d.z));
    const float md = (((a.y + a.w) + (b.y + b.w)) + ((c.y + c.w) + (d.y + d.w))) * (1.0f / DM);
    const float var = fmaxf(s2 * (1.0f / DM) - md * md, 0.f);
    mean = bfr(md);
    asm("rsqrt.approx.ftz.f32 %0, %1;" : "=f"(inv) : "f"(var + 1e-5f));
}
__device__ __forceinline__ void sts32(uint32_t a, float v) { asm volatile("st.shared.f32 [%0], %1;" ::"r"(a), "f"(v) : "memory"); }
__device__ __forceinline__ void sts32p(uint32_t a, float v, uint32_t off) {
    asm volatile("{\n.reg .pred p;\nsetp.eq.u32 p, %2, 0;\n@p st.shared.f32 [%0], %1;\n}" ::"r"(a), "f"(v), "r"(off) : "memory");
}
__device__ __forceinline__ void sts128p(uint32_t a, float x, float y, float z, float w, uint32_t off) {
    asm volatile("{\n.reg .pred p;\nsetp.eq.u32 p, %5, 0;\n@p st.shared.v4.f32 [%0], {%1,%2,%3,%4};\n}" ::"r"(a), "f"(x), "f"(y), "f"(z), "f"(w), "r"(off) : "memory");
}
__device__ __forceinline__ void sts64(uint32_t a, float v, float w) { asm volatile("st.shared.v2.f32 [%0], {%1,%2};" ::"r"(a), "f"(v), "f"(w) : "memory"); }

__device__ __forceinline__ uint32_t prmt(uint32_t a, uint32_t b, uint32_t s) { uint32_t r; asm("prmt.b32 %0, %1, %2, %3;" : "=r"(r) : "r"(a), "r"(b), "r"(s)); return r; }
__device__ __forceinline__ uint32_t bmul2(uint32_t a, uint32_t b) { uint32_t r; asm("mul.rn.bf16x2 %0, %1, %2;" : "=r"(r) : "r"(a), "r"(b)); return r; }
__device__ __forceinline__ void sts128(uint32_t addr, uint32_t a, uint32_t b, uint32_t c, uint32_t d) {
    asm volatile("st.shared.v4.u32 [%0], {%1,%2,%3,%4};" ::"r"(addr), "r"(a), "r"(b), "r"(c), "r"(d) : "memory");
}
__device__ __forceinline__ uint4 ldg128(const uint4* p) {
    uint4 v;
    asm volatile("ld.volatile.global.v4.u32 {%0,%1,%2,%3}, [%4];" : "=r"(v.x), "=r"(v.y), "=r"(v.z), "=r"(v.w) : "l"(p) : "memory");
    return v;
}
__device__ __forceinline__ uint32_t lds32(uint32_t a) { uint32_t v; asm volatile("ld.shared.u32 %0, [%1];" : "=r"(v) : "r"(a) : "memory"); return v; }
__device__ __forceinline__ uint32_t lds16(uint32_t a) { unsigned short v; asm volatile("ld.shared.u16 %0, [%1];" : "=h"(v) : "r"(a) : "memory"); return v; }
__device__ __forceinline__ void unpack8(uint32_t la, uint32_t lb, uint32_t c, uint32_t (&w)[4]) {
    const uint32_t ha = c & 0x87878787u, hb = __funnelshift_l(c, c, 4) & 0x87878787u;
    w[0] = prmt(la, ha, 0x5140); w[1] = prmt(la, ha, 0x7362); w[2] = prmt(lb, hb, 0x5140); w[3] = prmt(lb, hb, 0x7362);
}
__device__ __forceinline__ uint32_t bdiff2(uint32_t y, uint32_t inv, uint32_t x) {
    uint32_t r;
    asm("{\n.reg .b32 n;\nneg.bf16x2 n, %3;\nfma.rn.bf16x2 %0, %1, %2, n;\n}" : "=r"(r) : "r"(y), "r"(inv), "r"(x));
    return r;
}
__device__ __forceinline__ uint32_t pack_scale(uint32_t tile, int lane, uint32_t inv_addr) {
    uint32_t m = 0;
#pragma unroll 1
    for (int k = 0; k < 12; k++) {
        uint32_t a, b, c, d;
        lds128(tile + k * 512 + lane * 16, a, b, c, d);
        asm("max.xorsign.abs.bf16x2 %0, %0, %1;" : "+r"(a) : "r"(b));
        asm("max.xorsign.abs.bf16x2 %0, %0, %1;" : "+r"(c) : "r"(d));
        asm("max.xorsign.abs.bf16x2 %0, %0, %1;" : "+r"(a) : "r"(c));
        asm("max.xorsign.abs.bf16x2 %0, %0, %1;" : "+r"(m) : "r"(a));
    }
    m = __reduce_max_sync(0xffffffffu, max(m & 0x7fffu, (m >> 16) & 0x7fffu));
    const uint32_t inv = (112u + min((m + 0x28u) >> 7, 141u)) * 0x00800080u;
    if (lane == 0) asm volatile("st.shared.u32 [%0], %1;" ::"r"(inv_addr), "r"(inv) : "memory");
    return inv;
}

#define K_OFF(i) ((uint32_t)((3 * ((g >> 1) + 4 * (g & 1)) + ((i) >> 1)) * 128 + ((t ^ ((3 * ((g >> 1) + 4 * (g & 1)) + ((i) >> 1)) & 7) ^ (((i) & 1) << 2)) << 4)))
#define V_OFF(i) ((uint32_t)((6 * t + (i)) * 128 + ((g ^ ((6 * t + (i)) & 7)) << 4)))
template <bool ISV, typename DST>
__device__ __forceinline__ void pack_tile(uint32_t tile, int tau, int nm, uint32_t inv, uint32_t xl, int lane, DST dst) {
    const int g = lane >> 2, t = lane & 3;
    const uint32_t scl = 254u * 0x00800080u - inv;
#pragma unroll 1
    for (int m = 0; m < nm; m++) {
        const int row = ISV ? 6 * t + 2 * m : 3 * ((g >> 1) + 4 * (g & 1)) + m;
        const uint32_t a0 = tile + row * 128 + (((ISV ? g : t) ^ (row & 7)) << 4), a1 = ISV ? (a0 ^ 16) + 128 : a0 ^ 64;
        uint32_t l[8], cw[4], ck = 0, cd = 0;
#pragma unroll
        for (int r = 0; r < 4; r++) {
            uint32_t w0, w1, w2, w3;
            lds128(((r & 1) ? a1 : a0) + (r >> 1) * 3072, w0, w1, w2, w3);
            const uint32_t y0 = bmul2(w0, scl), y1 = bmul2(w1, scl), y2 = bmul2(w2, scl), y3 = bmul2(w3, scl);
            cd |= bdiff2(y0, inv, w0) | bdiff2(y1, inv, w1);
            cd |= bdiff2(y2, inv, w2) | bdiff2(y3, inv, w3);
            const uint32_t ha = prmt(y0, y1, 0x7531), hb = prmt(y2, y3, 0x7531);
            l[2 * r] = prmt(y0, y1, 0x6420); l[2 * r + 1] = prmt(y2, y3, 0x6420);
            asm("lop3.b32 %0, %1, 0x87878787, %2, 0xe2;" : "=r"(cw[r]) : "r"(ha), "r"(__funnelshift_r(hb, hb, 4)));
            ck |= ha | hb;
        }
        const uint32_t bad = __ballot_sync(0xffffffffu, (ck & 0x78787878u) | cd);
        if (bad) {
            const int src = __ffs(bad) - 1;
            const uint32_t b0 = __shfl_sync(0xffffffffu, a0, src), b1 = __shfl_sync(0xffffffffu, a1, src), n0 = lds32(xl);
            const uint32_t ax = ((lane & 8) ? b1 : b0) + (lane >> 4) * 3072 + 2 * (lane & 7), x = lds16(ax), y = bmul2(x, scl);
            const bool out = (y & 0x7800u) | bdiff2(y, inv, x);
            const uint32_t n = n0 + __popc(__ballot_sync(0xffffffffu, out) << (31 - lane)) - 1;
            if (out) {
                asm volatile("st.shared.u16 [%0], %1;" ::"r"(ax), "h"((unsigned short)0) : "memory");
                if (n < XCAP) sts32(xl + 16 + 4 * n, f_(x << 16 | tau << 12 | src << 7 | m << 5 | lane));
            }
            if (lane == 31) sts32(xl, f_(n + 1));
            __syncwarp();
            if (n0 <= XCAP) { m--; continue; }
        }
        uint32_t d[3] = {a0, a1, a0 + 3072};
        dst(m, d);
        sts128(d[0], l[0], l[1], l[2], l[3]);
        sts128(d[1], l[4], l[5], l[6], l[7]);
        sts128(d[2], cw[0], cw[1], cw[2], cw[3]);
    }
}

struct Maps { CUtensorMap k, v, wq, wo, w1, w3, w2, vr; const void* vp; const void* kp; uint32_t zero; };
#define RT_SEL ((wu & 1) ? RT_MASK2 : RT_MASK)
#define PFK 5
#define Q_AT 3
#define WO_T0 33200
#define K5D 250
#define PK_AT 6

__device__ __forceinline__ void load_ffn(const Maps& maps, int b, uint32_t dst, uint32_t bar) {
    const bool gu = b < NG;
    mbar_expect_tx(bar, gu ? 61440 : 49152);
    tma3d(dst, gu ? (b < NG / 2 ? &maps.w1 : &maps.w3) : &maps.w2, gu ? 48 * (b & (NG / 2 - 1)) : 16 * (b - DN0), 0, 0, bar, FFN_POL);
}

__device__ __forceinline__ void load_wo(const Maps& maps, uint32_t dst, int h, int c, uint32_t bar, int nbox) {
#pragma unroll 1
    for (int i = 0; i < nbox; i++) {
        if (!(i & 1)) mbar_expect_tx(bar + 4 * i, i + 1 < nbox ? 20480 : 10240);
        tma3d(dst + i * 10240, &maps.wo, 0, 5 * c, h * DH + 32 * i, bar + 4 * (i & 6), POL_EF);
    }
}

__global__ void __launch_bounds__(NT, 1)
decode_kernel(const __grid_constant__ Maps maps, const __nv_bfloat16* __restrict__ x_in, __nv_bfloat16* __restrict__ out) {
    extern __shared__ __align__(1024) unsigned char smem[];
    const int tid = threadIdx.x, warp = tid >> 5, lane = tid & 31;
    const int wu = __shfl_sync(0xffffffffu, tid >> 5, 0);
    const int b = blockIdx.x, h = b >> 2, c = b & 3;
    const uint32_t sb = smem_u32(smem);
    const uint32_t qbar = sb + SM_BAR + 16 * 8, fbar = qbar + 8, wbar = qbar + 16;
    uint32_t* xs32 = reinterpret_cast<uint32_t*>(smem + SM_XS);
    float* rr = reinterpret_cast<float*>(smem + SM_R);
    float* misc = reinterpret_cast<float*>(smem + SM_MISC);

    PROF_T(0);
    {
        uint2 xv = make_uint2(0u, 0u);
        const uint32_t t_start = now_ns();
        if (elect_one()) {
            const uint32_t rb = sb + SM_BAR + wu * 16, xb = sb + SM_XBAR + wu * 8;
            mbar_init(rb, 1); mbar_init(rb + 8, 1); mbar_init(xb, 1);
            if (wu == 0) mbar_init(qbar, 1);
            asm volatile("fence.mbarrier_init.release.cluster;" ::: "memory");
            const int row = (h * SK + (SK - WIN) + c * 1024 + wu * 128) * 3;
            const uint32_t ring = sb + SM_RING + wu * 2 * TILE;
#pragma unroll
            for (int n = 0; n < 3; n++) {
                const uint32_t bar = ((IN_S1 >> n) & 1) ? rb + 8 : ((IN_S0 >> n) & 1) ? rb : xb;
                mbar_expect_tx(bar, TILE);
                tma2d(((IN_S1 >> n) & 1) ? ring + TILE : ((IN_S0 >> n) & 1) ? ring : sb + SM_B + wu * TILE, &maps.k, 0, row + 48 * n, bar, POL_EF);
                if (n == 0 && wu == 0) {
                    mbar_expect_tx(qbar, 61440);
                    tma3d(sb + SM_Q, &maps.wq, 0, 160 * c, 3 * h, qbar, POL_EF);
                }
            }
            if (wu == 1) {
                mbar_init(fbar, 1);
#pragma unroll
                for (int i = 0; i < 3; i++) mbar_init(wbar + 8 * i, 1);
                asm volatile("fence.mbarrier_init.release.cluster;" ::: "memory");
            }
            if (wu >= 2) {
                const CUtensorMap* mp = wu == 2 ? &maps.v : wu == 3 ? &maps.wo : wu == 4 ? &maps.w1 : wu == 5 ? &maps.w3 : wu == 6 ? &maps.w2 : &maps.vr;
                asm volatile("prefetch.tensormap [%0];" ::"l"(mp) : "memory");
            }
        }
        if (tid < 160) asm volatile("ld.global.nc.v2.u32 {%0,%1}, [%2];" : "=r"(xv.x), "=r"(xv.y) : "l"(x_in + 4 * tid) : "memory");
        if (tid == 96) { misc[2] = 0.f; misc[3] = 0.f; }
        if (lane == 1) *reinterpret_cast<uint2*>(smem + SM_XL + warp * XSTR) = make_uint2(0u, t_start + WO_T0);
        if (tid >= 128 && tid < 148) {
            const uint32_t v = tid < 138 ? ONES : 0u;
            reinterpret_cast<uint4*>(smem + SM_ONE)[tid - 128] = make_uint4(v, v, v, v);
        }
        if (tid < 160) { xs32[xpos(2 * tid)] = xv.x; xs32[xpos(2 * tid + 1)] = xv.y; }
        __syncthreads();
        PROF_T(14);
        if (b == 0 && tid >= 232) asm volatile("st.relaxed.gpu.global.u32 [%0], %1;" ::"l"(g_scr.ticket + tid - 232), "r"(0) : "memory");
        if (tid == 64 || (tid == 65 && b < 216 - NCTA)) st_pkt(&g_scr.acc[1][(b + NCTA * (tid - 64)) * ACC_STR], 0, 0, 0, 0);
    }

    uint32_t kq[NQ][4];
    const float SC = 0.07216878364870322f * 1.4426950408889634f;

#pragma unroll 1
    for (int ph = 0; ph < 3; ph++) {
        const int layer = ph >> 1;
        const uint32_t tag = layer + 1;
        PROF_T(1 + layer * 16);
        if (ph) {
        {
            const int tl = opq(tid), warp = tl >> 5, lane = tl & 31, g = lane >> 2, t = lane & 3, mat = lane >> 3, r8 = lane & 7;
            const int kh = warp >> 2, mg = warp & 3;
            uint32_t aq[3];
#pragma unroll
            for (int i = 0; i < 3; i++) {
                const int ch = 6 * mg + 2 * i + (mat & 1);
                aq[i] = sb + SM_Q + (80 * kh + (mat >> 1) * 8 + r8) * 128 + (ch >> 3) * 20480 + (((ch & 7) ^ r8) << 4);
            }
#define PF_K5 if (layer == 1 && PFK) tile_keep(&maps.k, (h * SK + (SK - WIN) + c * 1024 + wu * 128 + PFK * 16) * 3);
            uint2 xv = make_uint2(0u, 0u);
            mbar_wait(qbar, 0);
            uint32_t pre[6][4];
#pragma unroll
            for (int n = 0; n < 6; n++) ldsm4t(aq[n % 3] + (n / 3) * 2048, pre[n]);
            if (layer == 1) {
                __syncthreads();
                if (elect_one()) {
                    const uint32_t bar = sb + SM_BAR + wu * 16;
                    asm volatile("mbarrier.expect_tx.relaxed.cta.shared::cta.b64 [%0], 1536;" ::"r"(bar) : "memory");
#pragma unroll
                    for (int k = 0; k < 3; k++)
                        tma2d(sb + SM_Q + v1_pos(3 * wu + k), &maps.vr, 0, (h * SK + (SK - WIN) + c * 1024 + wu * 128) / 2 + 8 + 2 * k, bar, POL_EF);
                }
            }
            const uint32_t pm = opq(g == 1 ? sb + SM_ONE : sb + SM_XS + 160 * (2 * c + kh) + 16 * t), pm2 = opq(pm + 128 - (g == 1 ? 0 : 8 * t));
            const uint32_t dq = opq(sb + SM_R + 8 * (kh * 192 + 48 * mg + g)), ds = opq(sb + SM_ST + 8 * warp + (lane < 16 ? 4 : 0));
            const bool wr = t == 0, ws = (lane & 15) == 0, lo = lane < 16;
            if (wu < 5) {
                const int p0 = xpos(2 * tl), p1 = xpos(2 * tl + 1);
                if (layer == 1) {
                    uint4 v;
                    for (int it = 0; it < SPIN_CAP; it++) { v = ld_pkt(&g_scr.ay[tl]); if (__all_sync(0xffffffffu, v.w == 1)) break; }
                    xv = make_uint2(v.x, v.y);
                    xs32[p0] = xv.x; xs32[p1] = xv.y;
                } else xv = make_uint2(xs32[p0], xs32[p1]);
            }
            if (layer) PC(24);
            __syncthreads();
            PF_K5
            if (layer) PC(25);
            PROF_T(13 + layer * 16);
            const float e0 = bf_lo(xv.x), e1 = bf_hi(xv.x), e2 = bf_lo(xv.y), e3 = bf_hi(xv.y);
            const float s1 = (e0 + e1) + (e2 + e3), s2 = (e0 * e0 + e1 * e1) + (e2 * e2 + e3 * e3);
            float sv = lo ? s1 : s2, cc[3][4];
            gemv15<2048>(cc, pre, [&](int i) { return aq[i]; }, pm, pm2, sv, lo ? s2 : s1);
            if (wr) {
#pragma unroll
                for (int i = 0; i < 3; i++) { sts64(dq + 128 * i, cc[i][0], cc[i][1]); sts64(dq + 128 * i + 64, cc[i][2], cc[i][3]); }
            }
            if (ws) sts32(ds, sv);
        }
        const uint32_t pa = opq(sb + SM_R + 32 * opq(tid)), st = opq(sb + SM_ST);
        uint4* const pq = opq(&g_scr.hx[b * 48 + opq(tid)]);
        if (layer) PC(26);
        __syncthreads();
        if (layer) PC(27);
        PROF_T(33 + layer * 16);
        if (wu < 2) {
            float mean, inv;
            ln_stats(st, mean, inv);
            const float4 a0 = lds4f(pa), a1 = lds4f(pa + 16), b0 = lds4f(pa + 1536), b1 = lds4f(pa + 1552);
            const float q0 = (a0.x + b0.x) - mean * (a0.y + b0.y), q1 = (a0.z + b0.z) - mean * (a0.w + b0.w);
            const float q2 = (a1.x + b1.x) - mean * (a1.y + b1.y), q3 = (a1.z + b1.z) - mean * (a1.w + b1.w);
            st_pktfp(pq, q0, q1, q2, q3, 1, tid < 48);
        }
        if (layer == 1 && tid >= 192 && tid < 194 && b < 108) st_pkt(&g_scr.acc[0][(2 * b + opq(tid) - 192) * ACC_STR], 0, 0, 0, 0);
        }
        if (layer) PC(28);
        if (layer == 1 && (wu & 2)) {
            idle(K5D);
            tile_load(sb + SM_Q + c_slot(wu), &maps.k, (h * SK + (SK - WIN) + c * 1024 + wu * 128 + 5 * 16) * 3, sb + SM_XBAR + wu * 8, 0, 0);
        }

        float sc0 = -INFINITY, sc1 = -INFINITY, sc2 = 0.f, sc3 = 0.f, mw;
        uint32_t pk0, pk1;
        float acc[3][4];
        {
            const uint32_t ring = sb + SM_RING + wu * 2 * TILE, rb = sb + SM_BAR + wu * 16;
            const uint32_t xtile = sb + SM_Q + c_slot(wu), xb = sb + SM_XBAR + wu * 8;
#define V_SEQ(n) ((int)(SEQ1 >> (4 * (n))) & 7)
#define SLOT1(n) (((IN_S1 >> (n)) & 1) ? ring + TILE : ((IN_S0 >> (n)) & 1) ? ring : sb + SM_B + wu * TILE)
#define BAR1(n) (((IN_S1 >> (n)) & 1) ? rb + 8 : ((IN_S0 >> (n)) & 1) ? rb : xb)
#define PAR1(n) ((PARITY1 >> (n)) & 1)
#define PAR2(n) ((PARITY2 >> (n)) & 1)
            const int row0 = (h * SK + (SK - WIN) + c * 1024 + wu * 128) * 3;
            auto issue1 = [&](int n, uint32_t dep, bool vph = false) {
                const CUtensorMap* mp = n < 8 ? &maps.k : &maps.v;
                const int tl = V_SEQ(n), row = row0 + tl * 48;
                const uint32_t dst = SLOT1(n), bar = BAR1(n);
                if (vph && wu < L1R && tl == 7 - (wu & 1)) {
                    tile_load_l1(dst, maps.vp, row, bar, opq(tid) & 31);
                    return;
                }
                tile_load(dst, mp, row, bar, dep, maps.zero);
                if ((RT_SEL >> (tl + (n & 8))) & 1) {
                    if (n != V0_AT + 1) tile_keep(mp, row);
                    else if ((opq(tid) & 31) < 8)
                        asm volatile("cp.async.bulk.prefetch.L2.global.L2::cache_hint [%0], 256, %1;"
                                     ::"l"(static_cast<const char*>(maps.vp) + (size_t)(row + 4 + 6 * (opq(tid) & 31)) * 128), "l"(POL_EN) : "memory");
                }
            };
            auto refill1 = [&](int s, uint32_t dep, bool vph = false) { issue1(s + (!vph || s < V0_AT ? 3 : 2), dep, vph); };
#define LANE_IDS const int tl = opq(tid), lane = tl & 31, g = lane >> 2, t = lane & 3; (void)tl; (void)lane; (void)g; (void)t;
            const uint32_t xl = sb + SM_XL + wu * XSTR;
            if (layer == 0) {
#pragma unroll 1
                for (int s = ph ? Q_AT : 0; s < (ph ? 5 : Q_AT); s++) {
                    LANE_IDS
                    const uint32_t tile = SLOT1(s);
                    mbar_wait(BAR1(s), PAR1(s));
                    const uint32_t scl = s == 0 ? pack_scale(tile, lane, xl + 8) : lds32(xl + 8);
                    pack_tile<false>(tile, s, 3, scl, xl, lane, [](int, uint32_t (&)[3]) {});
#pragma unroll
                    for (int n = 0; n < 5; n++) {
                        if (s == n) {
#pragma unroll
                            for (int m = 0; m < 3; m++) {
                                const uint32_t a = tile + K_OFF(2 * m);
                                lds128(a, kq[9 * n + 3 * m][0], kq[9 * n + 3 * m][1], kq[9 * n + 3 * m][2], kq[9 * n + 3 * m][3]);
                                lds128(a ^ 64, kq[9 * n + 3 * m + 1][0], kq[9 * n + 3 * m + 1][1], kq[9 * n + 3 * m + 1][2], kq[9 * n + 3 * m + 1][3]);
                                lds128(a + 3072, kq[9 * n + 3 * m + 2][0], kq[9 * n + 3 * m + 2][1], kq[9 * n + 3 * m + 2][2], kq[9 * n + 3 * m + 2][3]);
                            }
                        }
                    }
                    __syncwarp();
                    refill1(s, lds32(tile));
                }
                if (!ph) continue;
            }
            {
                if (wu < 2) {
                    const int tl = min(opq(tid), 47);
                    const int w = 2 * tl;
                    const uint32_t pos = opq(sb + SM_QS + 4 * (((w >> 2) & 3) * 24 + 2 * (w >> 4) + ((w >> 1) & 1)));
                    uint4 v[4];
                    float mean, inv;
                    ln_stats(opq(sb + SM_ST), mean, inv);
                    for (int it = 0; it < SPIN_CAP; it++) {
#pragma unroll
                        for (int k = 0; k < 4; k++) v[k] = ld_pkt(&g_scr.hx[(h * 4 + k) * 48 + tl]);
                        if (all_odd(v[0].w, v[1].w, v[2].w, v[3].w)) break;
                    }
                    sts32(pos, f_(pack2(inv * ((f_(v[0].x) + f_(v[1].x)) + (f_(v[2].x) + f_(v[3].x))), inv * ((f_(v[0].y) + f_(v[1].y)) + (f_(v[2].y) + f_(v[3].y))))));
                    sts32(pos + 48, f_(pack2(inv * ((f_(v[0].z) + f_(v[1].z)) + (f_(v[2].z) + f_(v[3].z))), inv * ((f_(v[0].w) + f_(v[1].w)) + (f_(v[2].w) + f_(v[3].w))))));
                }
            }
            if (layer) PC(29);
            __syncthreads();
            if (layer) PC(30);
            PROF_T(2 + layer * 16);
#define V1_REST(p) ((p) < 6 ? sb + SM_Q + v1_pos(3 * wu + ((p) >> 1)) + 256 * ((p) & 1) : ((sb + SM_R + wu * 784 + 127) & ~127u) - 1536 + 256 * (p))
#define V1_LOAD(bar) if (elect_one()) tma2d(V1_REST(6), &maps.vr, 0, row0 / 6 + 14, bar, POL_EF);
#define V1_EXPECT(bar) { if ((opq(tid) & 31) == 0) asm volatile("mbarrier.expect_tx.relaxed.cta.shared::cta.b64 [%0], 512;" ::"r"(bar) : "memory"); }
            if (layer == 1 && !(wu & 2)) tile_load(xtile, &maps.k, row0 + 5 * 48, xb, 0, 0);
            if (layer == 1 && wu >= 4) idle(STAG);
            {
                uint32_t qf[12];
                int t;
                {
                    const int lane = opq(tid) & 31;
                    t = lane & 3;
                    const uint32_t qa = sb + SM_QS + (2 * t + ((lane >> 2) & 1)) * 48;
#pragma unroll
                    for (int i = 0; i < 3; i++) lds128(qa + 16 * i, qf[4 * i], qf[4 * i + 1], qf[4 * i + 2], qf[4 * i + 3]);
                }
                const uint32_t sq = lds32(xl + 8) - 64u * 0x00800080u;
#pragma unroll
                for (int i = 0; i < 12; i++) qf[i] = bmul2(qf[i], sq);
#define KR_STEP(tau, m) \
                    _Pragma("unroll") for (int i = 2 * (m); i < 2 * (m) + 2; i++) { \
                        const int q0 = 9 * tau + 3 * (i >> 1), r = i & 1; \
                        uint32_t w[4]; \
                        unpack8(kq[q0][2 * r], kq[q0][2 * r + 1], kq[q0 + 2][r], w); \
                        mma16816(cA, w[0], w[1], w[2], w[3], qf[2 * i], qf[2 * i + 1]); \
                        unpack8(kq[q0 + 1][2 * r], kq[q0 + 1][2 * r + 1], kq[q0 + 2][2 + r], w); \
                        mma16816(cB, w[0], w[1], w[2], w[3], qf[2 * i], qf[2 * i + 1]); \
                    }
#define KR_BEGIN float cA[4] = {0.f, 0.f, 0.f, 0.f}, cB[4] = {0.f, 0.f, 0.f, 0.f};
#define KR_END(tau) \
                    const float sA = (cA[0] + cA[3]) * 18446744073709551616.f, sB = (cB[0] + cB[3]) * 18446744073709551616.f; \
                    if (t == (tau & 3)) { if (tau < 4) { sc0 = sA; sc1 = sB; } else { sc2 = sA; sc3 = sB; } }
#define KR_SCORES(tau) { KR_BEGIN KR_STEP(tau, 0) KR_STEP(tau, 1) KR_STEP(tau, 2) KR_END(tau) }
                uint32_t va[3];
                {
                    const int lane = opq(tid) & 31, g = lane >> 2, t = lane & 3;
#pragma unroll
                    for (int i = 0; i < 3; i++) va[i] = ring + V_OFF(2 * i);
                }
#define V_STG(n) _Pragma("unroll") for (int j = 3 * (n); j < 3 * (n) + 3; j++) { \
                    const int i = (j % 12) >> 1; \
                    lds128p(((i & 1) ? (va[i >> 1] ^ 16) + 128 : va[i >> 1]) + (j / 12) * TILE + (j & 1) * 3072, layer, kq[j][0], kq[j][1], kq[j][2], kq[j][3]); }
                uint32_t dep = 0;
                {
                    KR_BEGIN
                    KR_STEP(0, 0) V_STG(0) KR_STEP(0, 1) V_STG(1) KR_STEP(0, 2) V_STG(2)
                    KR_END(0)
                }
                {
                    KR_BEGIN
                    KR_STEP(1, 0) V_STG(3)
                    __syncwarp();
                    dep = lds32(ring);
                    if (layer == 1) tile_load(ring, &maps.k, row0 + 6 * 48, rb, dep, maps.zero);
                    KR_STEP(1, 1) V_STG(4) KR_STEP(1, 2) V_STG(5)
                    KR_END(1)
                }
                {
                    KR_BEGIN
                    KR_STEP(2, 0) V_STG(6) KR_STEP(2, 1) V_STG(7)
                    __syncwarp();
                    dep = lds32(ring + TILE);
                    KR_STEP(2, 2)
                    if (layer == 1) {
                        V1_EXPECT(rb + 8)
                        tile_load(ring + TILE, &maps.k, row0 + 7 * 48, rb + 8, dep, maps.zero);
                        V1_LOAD(rb + 8)
                    }
                    KR_END(2)
                }
#pragma unroll 1
                for (int s = 5; s < 8; s++) {
                    {
                        LANE_IDS
                        const uint32_t tile = !layer ? SLOT1(s) : s == 5 ? xtile : ring + (s - 6) * TILE, tb = !layer ? BAR1(s) : s == 5 ? xb : rb + (s - 6) * 8;
                        const float ur = f_((318u << 23) - (lds32(xl + 8) << 16));
                        mbar_wait(tb, layer ? PAR2(s - 5) : PAR1(s));
                        if (layer) PROF_T(29 + s);
                        float cA[4] = {0.f, 0.f, 0.f, 0.f}, cB[4] = {0.f, 0.f, 0.f, 0.f};
#pragma unroll
                        for (int i = 0; i < 6; i++) {
                            uint32_t a0, a1, a2, a3;
                            lds128(tile + K_OFF(i), a0, a1, a2, a3);
                            mma16816(cA, a0, a1, a2, a3, qf[2 * i], qf[2 * i + 1]);
                            lds128(tile + K_OFF(i) + 3072, a0, a1, a2, a3);
                            mma16816(cB, a0, a1, a2, a3, qf[2 * i], qf[2 * i + 1]);
                        }
                        __syncwarp();
                        const uint32_t last = lds32(tile);
                        if (layer) tile_load(tile, &maps.v, row0 + (s - 2) * 48, tb, last, maps.zero);
                        else refill1(s, last);
                        if (t == (s & 3)) { sc2 = (cA[0] + cA[3]) * ur; sc3 = (cB[0] + cB[3]) * ur; }
                    }
                    if (s == 5) KR_SCORES(3)
                    if (s == 6) {
                        KR_SCORES(4)
                        const int lane = opq(tid) & 31;
                        const uint32_t nx = min(lds32(xl), (uint32_t)XCAP);
#pragma unroll 1
                        for (uint32_t n = 0; n < nx; n++) {
                            const uint32_t id = lds32(xl + 16 + 4 * n);
                            const uint32_t qo = 96 * ((id >> 7) & 3) + 48 * ((id >> 1) & 1) + 16 * ((id >> 5) & 3) + (id & 12) + 2 * (id & 1);
                            const float cr = bf_hi(id) * f_(lds16(sb + SM_QS + qo) << 16);
                            const int d = (int)(16 * ((id >> 9) & 7) + 4 * ((id >> 12) & 3) + ((id >> 13) & 2) + ((id >> 4) & 1) + ((id >> 8) & 128)) - 4 * lane;
                            if (d == 0) sc0 += cr;
                            if (d == 1) sc1 += cr;
                            if (d == 2) sc2 += cr;
                            if (d == 3) sc3 += cr;
                        }
                    }
                }
#undef KR_SCORES
#undef KR_STEP
#undef KR_BEGIN
#undef KR_END
#undef V_STG
                {
                    LANE_IDS
                    if (lds32(xl) > XCAP || !__all_sync(0xffffffffu, (fabsf(sc0) + fabsf(sc1)) + (fabsf(sc2) + fabsf(sc3)) < INFINITY)) {
                        const uint32_t qa = sb + SM_QS + (2 * t + (g & 1)) * 48;
#pragma unroll
                        for (int i = 0; i < 3; i++) lds128(qa + 16 * i, qf[4 * i], qf[4 * i + 1], qf[4 * i + 2], qf[4 * i + 3]);
                        const uint4* kg = reinterpret_cast<const uint4*>(static_cast<const char*>(maps.kp) + (size_t)row0 * 128) + ((g >> 1) + 4 * (g & 1)) * 24 + t;
#pragma unroll 1
                        for (int s = 0; s < 8; s++) {
                            float cA[4] = {0.f, 0.f, 0.f, 0.f}, cB[4] = {0.f, 0.f, 0.f, 0.f};
#pragma unroll
                            for (int i = 0; i < 6; i++) {
                                uint4 u = ldg128(kg + s * 384 + 4 * i);
                                mma16816v(cA, u.x, u.y, u.z, u.w, qf[2 * i], qf[2 * i + 1]);
                                u = ldg128(kg + s * 384 + 4 * i + 192);
                                mma16816v(cB, u.x, u.y, u.z, u.w, qf[2 * i], qf[2 * i + 1]);
                            }
                            if (t == s) { sc0 = cA[0] + cA[3]; sc1 = cB[0] + cB[3]; }
                            if (t + 4 == s) { sc2 = cA[0] + cA[3]; sc3 = cB[0] + cB[3]; }
                        }
                    }
                }
            }
            mw = warp_max(fmaxf(fmaxf(sc0, sc1), fmaxf(sc2, sc3)));
            pk0 = pack2(ex2((sc0 - mw) * SC), ex2((sc1 - mw) * SC));
            pk1 = pack2(ex2((sc2 - mw) * SC), ex2((sc3 - mw) * SC));
            sc2 = (bf_lo(pk0) + bf_hi(pk0)) + (bf_lo(pk1) + bf_hi(pk1));
            sc2 = (float)__reduce_add_sync(0xffffffffu, __float2uint_rn(sc2 * 16777216.f)) * (1.0f / 16777216.f);
            if ((opq(tid) & 31) == 0) st_pkt2(&g_scr.mx[h * 32 + c * 8 + wu], __float_as_uint(mw), (__float_as_uint(sc2) & ~3u) | tag);
            auto head_factor = [&]() {
                const int lane = opq(tid) & 31;
                int it = 0;
                while (!__all_sync(0xffffffffu, (__float_as_uint(sc1) & 3u) == tag) && ++it < SPIN_CAP) {
                    const uint2 mv = ld_pkt2(&g_scr.mx[h * 32 + lane]); sc0 = f_(mv.x); sc1 = f_(mv.y);
                }
                const float e = ex2((sc0 - warp_max(sc0)) * SC);
                const uint32_t d = __reduce_add_sync(0xffffffffu, __float2uint_rn(sc1 * e * 524288.f));
                sc3 = __shfl_sync(0xffffffffu, e, c * 8 + wu) * 524288.f * rcp((float)d);
            };
#pragma unroll
            for (int s = 0; s < 3; s++) { acc[s][0] = acc[s][1] = acc[s][2] = acc[s][3] = 0.f; }
#define P_CONSTS \
                const uint32_t sel0 = g == 0 ? 0x4410u : (g == 1 ? 0x1044u : 0x4444u); \
                const uint32_t sel1 = g == 2 ? 0x4410u : (g == 3 ? 0x1044u : 0x4444u); \
                const int src00 = 4 * (t < 2 ? 4 * t : 4 * (t - 2) + 1);
#define P_FRAGS(tau) \
                const uint32_t pk = ((tau) & 4) ? pk1 : pk0; \
                const uint32_t w0 = __shfl_sync(0xffffffffu, pk, src00 + ((tau) & 3)); \
                const uint32_t w1 = __shfl_sync(0xffffffffu, pk, src00 + ((tau) & 3) + 8); \
                uint32_t pb[4][2]; \
                _Pragma("unroll") for (int j = 0; j < 4; j++) { \
                    const uint32_t src = ((j & 1) ? w1 : w0) >> ((j >> 1) * 16); \
                    pb[j][0] = __byte_perm(src, 0, sel0); pb[j][1] = __byte_perm(src, 0, sel1); \
                }
            if (layer == 0) {
#pragma unroll 1
                for (int s = 8; s < 16; s++) {
                    LANE_IDS
                    P_CONSTS
                    if (s == 13) { const uint2 mv = ld_pkt2(&g_scr.mx[h * 32 + lane]); sc0 = f_(mv.x); sc1 = f_(mv.y); }
                    P_FRAGS(V_SEQ(s))
                    mbar_wait(BAR1(s), PAR1(s));
                    const uint32_t tile = SLOT1(s);
#pragma unroll
                    for (int j = 0; j < 4; j++) {
#pragma unroll
                        for (int u = 0; u < 3; u++) {
                            uint32_t a0, a1, a2, a3;
                            lds128(tile + (j >> 1) * 3072 + V_OFF(3 * (j & 1) + u), a0, a1, a2, a3);
                            mma16816(acc[u], a0, a1, a2, a3, pb[j][0], pb[j][1]);

                        }
                    }
                    __syncwarp();
                    if (s < V0_AT || (s > V0_AT + 1 && s < 14)) refill1(s, lds32(tile), true);
                    if (s == V0_AT || s == V0_AT + 1) {
                        {
                            const uint32_t ar = sb + SM_R + wu * 784 + 32 * g + 16 * t;
                            if (t < 2) {
#pragma unroll
                                for (int u = 0; u < 3; u++) sts128(ar + 256 * u, __float_as_uint(acc[u][0]), __float_as_uint(acc[u][1]), __float_as_uint(acc[u][2]), __float_as_uint(acc[u][3]));
                            }
                        }
                        const uint32_t scl = s == V0_AT ? pack_scale(tile, lane, xl + 12) : lds32(xl + 12);
                        pack_tile<true>(tile, s + 8 - V0_AT, V0_AT + 3 - s, scl, xl, lane, [&](int m, uint32_t (&d)[3]) {
                            if (s != V0_AT && m == 0) {
#pragma unroll
                                for (int k = 0; k < 3; k++) d[k] = ring + 3072 + V_OFF(2 * k + 1);
                            }
                        });
                        if (s != V0_AT) {
                            lds128(tile + V_OFF(2), kq[45][0], kq[45][1], kq[45][2], kq[45][3]);
                            lds128(tile + V_OFF(3), kq[46][0], kq[46][1], kq[46][2], kq[46][3]);
                            lds128(tile + V_OFF(2) + 3072, kq[47][0], kq[47][1], kq[47][2], kq[47][3]);
                            __syncwarp();
                            issue1(V0_AT + 3, lds32(tile));
                        }
                        const int ln = opq(tid) & 31;
                        const uint32_t ar = sb + SM_R + wu * 784 + 8 * (ln & 28) + 16 * (ln & 1);
#pragma unroll
                        for (int u = 0; u < 3; u++) {
                            uint32_t a0, a1, a2, a3;
                            lds128(ar + 256 * u, a0, a1, a2, a3);
                            acc[u][0] = f_(a0); acc[u][1] = f_(a1); acc[u][2] = f_(a2); acc[u][3] = f_(a3);
                        }
                    }
                    if (s == 13) head_factor();
                    if (s >= 14 && elect_one()) {
                        if (atomicAdd(reinterpret_cast<unsigned*>(misc + 3), 1u) == 14u && (int)(now_ns() - lds32(xl + 4)) >= 0) {
                            PROF_X(47);
                            load_wo(maps, sb + SM_B, h, c, wbar, 6);
                            atomicAdd(reinterpret_cast<unsigned*>(misc + 3), 256u);
                        }
                    }
                }
            } else {
                LANE_IDS
                P_CONSTS
#pragma unroll
                for (int k = 0; k < 4; k++) lds128(V1_REST(t + 4 * (k >> 1)) + 16 * g + 128 * (k & 1), kq[36 + k][0], kq[36 + k][1], kq[36 + k][2], kq[36 + k][3]);
#pragma unroll 1
                for (int i = 3; i < 8; i++) {
                    const uint32_t tile = i > 3 ? ring + (i & 1) * TILE : xtile, tb = i > 3 ? rb + (i & 1) * 8 : xb;
                    if (i == 6) { const uint2 mv = ld_pkt2(&g_scr.mx[h * 32 + lane]); sc0 = f_(mv.x); sc1 = f_(mv.y); }
                    if (i == 7) head_factor();
                    if (i == PK_AT) {
                uint32_t nx, nk, ik, iv;
                lds128(xl, nx, nk, ik, iv);
                if (nx <= XCAP) {
                    const uint32_t pks = bmul2(pk0, iv);
#pragma unroll
                    for (int s = 0; s < 2; s++) {
                        const uint32_t pk1 = 0, pk0 = pks;
                        P_FRAGS(s)
#pragma unroll
                        for (int j = 0; j < 4; j++) {
#pragma unroll
                            for (int u = 0; u < 3; u++) {
                                const int i = 3 * (j & 1) + u, m = i >> 1, r = i & 1, hf = j >> 1;
                                if (s == 1 && m == 2) continue;
                                const int ql = s == 0 ? 4 * m + 2 * hf : m == 0 ? 3 + 4 * hf : 45 + hf, qc = s == 0 ? 4 * m + 1 : m == 0 ? 11 : 47;
                                uint32_t w[4];
                                unpack8(kq[ql][2 * r], kq[ql][2 * r + 1], kq[qc][2 * hf + r], w);
                                mma16816(acc[u], w[0], w[1], w[2], w[3], pb[j][0], pb[j][1]);
                            }
                        }
                    }
#pragma unroll 1
                    for (uint32_t n = 0; n < nx; n++) {
                        const uint32_t id = lds32(xl + 16 + 4 * n);
                        const int i = ((id >> 4) & 6) + ((id >> 3) & 1), key = ((id >> 6) & 6) + (i >= 3);
                        const uint32_t pw = __shfl_sync(0xffffffffu, pk0, 8 * (key & 3) + (key & 4) + ((id >> 12) & 3));
                        const float cr = bf_hi(id) * ((id & 16) ? bf_hi(pw) : bf_lo(pw));
                        const int d = (int)(64 * ((id >> 9) & 7) + 4 * (id & 4) + 4 * (i >= 3 ? i - 3 : i) + (id & 3) + ((~id >> 5) & 1024)) - 16 * lane;
#pragma unroll
                        for (int k = 0; k < 12; k++) if (d == k) acc[k >> 2][k & 3] += cr;
                    }
                } else {
                    const uint4* vg = reinterpret_cast<const uint4*>(static_cast<const char*>(maps.vp) + (size_t)row0 * 128) + 48 * t + g;
#pragma unroll 1
                    for (int s = 0; s < 2; s++) {
                        P_FRAGS(s)
#pragma unroll
                        for (int j = 0; j < 4; j++) {
#pragma unroll
                            for (int u = 0; u < 3; u++) {
                                if (s == 1 && (j & 1) && u) continue;
                                const uint4 w = ldg128(vg + 384 * s + 192 * (j >> 1) + 24 * (j & 1) + 8 * u);
                                mma16816v(acc[u], w.x, w.y, w.z, w.w, pb[j][0], pb[j][1]);
                            }
                        }
                    }
                }
#pragma unroll
                for (int s = 2; s > 0; s--) {
                    P_FRAGS(s)
#pragma unroll
                    for (int j = 0; j < 4; j++) {
#pragma unroll
                        for (int u = 0; u < 3; u++) {
                            if (s == 1 && !((j & 1) && u)) continue;
                            const int k = s == 2 ? 12 + 2 * (3 * (j & 1) + u) + (j >> 1) : 35 + (j >> 1) * 2 + u;
                            mma16816(acc[u], kq[k][0], kq[k][1], kq[k][2], kq[k][3], pb[j][0], pb[j][1]);
                        }
                    }
                }
                    }
                    P_FRAGS(i)
                    mbar_wait(tb, PAR2(i));
                    PROF_T(34 + i);
#pragma unroll
                    for (int k = 0; k < 6; k++) {
                        const uint32_t a = tile + V_OFF(k);
                        lds128(a, kq[24 + k][0], kq[24 + k][1], kq[24 + k][2], kq[24 + k][3]);
                        lds128(a + 3072, kq[30 + k][0], kq[30 + k][1], kq[30 + k][2], kq[30 + k][3]);
                    }
#pragma unroll
                    for (int j = 0; j < 4; j++) {
#pragma unroll
                        for (int u = 0; u < 3; u++) {
                            const int k = 24 + 6 * (j >> 1) + 3 * (j & 1) + u;
                            mma16816(acc[u], kq[k][0], kq[k][1], kq[k][2], kq[k][3], pb[j][0], pb[j][1]);
                        }
                    }
                    __syncwarp();
                    if (wu < L1R && i == 5 - (wu & 1)) tile_load_l1(tile, maps.vp, row0 + (i + 2) * 48, tb, lane);
                    else if (i == 4 || i == 5) tile_load(tile, &maps.v, row0 + (i + 2) * 48, tb, lds32(tile), maps.zero);
                    if (i == WO_AT1 && HAS_FFN && elect_one()) {
                        if (atomicAdd(reinterpret_cast<unsigned*>(misc + 2), 1u) == 7u) {
                            PROF_X(63);
                            load_wo(maps, sb + SM_Q, h, c, wbar, KEEP4 && __float_as_uint(misc[1]) >= DN0 ? 5 : 6);
                        }
                    }
                }
            }
#undef P_FRAGS
#undef P_CONSTS
#undef LANE_IDS
        }
        PROF_T(3 + layer * 16);
        PC(layer * 32 + 1);

        {
            const int lane = opq(tid) & 31;
            const uint32_t a = sb + SM_R + wu * 784 + 8 * (lane & 28) + 16 * (lane & 1);
#pragma unroll
            for (int u = 0; u < 3; u++) sts128p(a + 256 * u, acc[u][0] * sc3, acc[u][1] * sc3, acc[u][2] * sc3, acc[u][3] * sc3, lane & 2);
        }
        const uint32_t role1 = layer ? lds32(sb + SM_MISC + 4) : DN0 + NDN;
        const uint32_t pc = opq(sb + SM_R + 16 * opq(tid));
        uint4* const px0 = opq(&g_scr.hx[b * 48 + opq(tid)]);
        __syncthreads();
        PROF_T(4 + layer * 16);
        PC(layer * 32 + 2);
        float4 o = make_float4(0.f, 0.f, 0.f, 0.f);
        if (wu < 2) {
            float4 v[8];
#pragma unroll
            for (int w = 0; w < 8; w++) v[w] = lds4f(pc + w * 784);
            o.x = ((v[0].x + v[1].x) + (v[2].x + v[3].x)) + ((v[4].x + v[5].x) + (v[6].x + v[7].x));
            o.y = ((v[0].y + v[1].y) + (v[2].y + v[3].y)) + ((v[4].y + v[5].y) + (v[6].y + v[7].y));
            o.z = ((v[0].z + v[1].z) + (v[2].z + v[3].z)) + ((v[4].z + v[5].z) + (v[6].z + v[7].z));
            o.w = ((v[0].w + v[1].w) + (v[2].w + v[3].w)) + ((v[4].w + v[5].w) + (v[6].w + v[7].w));
            o.w = f_(__float_as_uint(o.w) & ~1u);
            st_pktp(px0, __float_as_uint(o.x), __float_as_uint(o.y), __float_as_uint(o.z), __float_as_uint(o.w), threadIdx.x < 48);
        }
        uint32_t ticket = 0;
        if (layer == 0 && tid == 224)
            asm volatile("atom.relaxed.gpu.global.inc.u32 %0, [%1], 0x7fffffff;" : "=r"(ticket) : "l"(g_scr.ticket + 8 + (b >> 3)) : "memory");
        if (layer == 0 && tid == 224 && lds32(sb + SM_MISC + 12) < 256u) {
            int it = 0;
            while ((int)(now_ns() - lds32(sb + SM_XL + 4)) < 0 && ++it < SPIN_CAP) {}
            PROF_X(47);
            load_wo(maps, sb + SM_B, h, c, wbar, 6);
        }
        uint32_t pr;
        uint4* pacc;
        {
            const int tid = opq(threadIdx.x), warp = tid >> 5, lane = tid & 31, g = lane >> 2, t = lane & 3, mat = lane >> 3, r8 = lane & 7;
            const int kg = warp >> 1, mg = warp & 1;
            const bool wo2 = role1 < DN0 + NDN;
            const uint32_t aw2 = 40960 + (wo2 && KEEP4 && role1 >= DN0 && kg >= 2 ? SM_B - SM_Q : 0);
            uint32_t aw[5];
#pragma unroll
            for (int i = 0; i < 5; i++) {
                const uint32_t lin = ((mat >> 1) * 8 + r8) * 320 + 64 * i + 32 * mg + 16 * (mat & 1);
                aw[i] = sb + (wo2 ? SM_Q : SM_B) + 5120 * kg + (lin ^ ((lin >> 3) & 48));
            }
#define CXE 0
            const uint32_t ao = pin(sb + SM_OS + 96 * kg + 16 * t), dw = pin(sb + SM_R + 16 * (16 * mg + g) + 4 * kg);
            pr = pin(sb + SM_R + 48 * tid); pacc = pin(&g_scr.acc[layer][(54 * c + tid) * ACC_STR]);
            const int w = 2 * min(tid, 47);
            const uint32_t d0 = pin(sb + SM_OS + 4 * (24 * ((w >> 3) & 3) + ((w >> 2) & 1) + (w < 64 ? 4 * (w & 3) + 2 * (w >> 5) : 16 + 2 * (w & 3))));
            const uint32_t d1 = pin(d0 + (w < 64 ? 16 : 8));
            const uint4* pp[3];
#pragma unroll
            for (int k = 0; k < 3; k++) pp[k] = pin(&g_scr.hx[(h * 4 + ((c + 1 + k) & 3)) * 48 + min(tid, 47)]);
            uint4 v3[3];
#pragma unroll
            for (int k = 0; k < 3; k++) v3[k] = make_uint4(0u, 0u, 0u, 1u);
            if ((PRE1 & 8) && layer) {
#pragma unroll
                for (int ks = 0; ks < 3; ks++) {
                    mbar_wait(wbar + 8 * ks, wo2);
#pragma unroll
                    for (int i = 0; i < 5; i++) ldsm4t(aw[i] + (ks == 2 ? aw2 : 20480 * ks), kq[3 * i + ks]);
                    if (ks == CXE && wu < 2) {
#pragma unroll
                        for (int k = 0; k < 3; k++) v3[k] = ld_pkt(pp[k]);
                    }
                }
                PROF_T(50);
            }
            if (wu < 2) {
                for (int it = 0; any_odd(v3[0].w, v3[1].w, v3[2].w) && it < SPIN_CAP; it++) {
#pragma unroll
                    for (int k = 0; k < 3; k++) v3[k] = ld_pkt(pp[k]);
                }
                o.x = (o.x + f_(v3[0].x)) + (f_(v3[1].x) + f_(v3[2].x)); o.y = (o.y + f_(v3[0].y)) + (f_(v3[1].y) + f_(v3[2].y));
                o.z = (o.z + f_(v3[0].z)) + (f_(v3[1].z) + f_(v3[2].z)); o.w = (o.w + f_(v3[0].w)) + (f_(v3[1].w) + f_(v3[2].w));
                sts32p(d0, f_(pack2(o.x, o.y)), tid >= 48);
                sts32p(d1, f_(pack2(o.z, o.w)), tid >= 48);
            }
            PC(layer * 32 + 3);
            __syncthreads();
            PROF_T(5 + layer * 16);
            PC(layer * 32 + 5);
            if (tid == 224 && layer == 0) {
                if (ticket >= 6 + ((b >> 3) & 1)) ticket = DN0 + NDN;
                else asm volatile("atom.relaxed.gpu.global.inc.u32 %0, [%1], 0x7fffffff;" : "=r"(ticket) : "l"(g_scr.ticket) : "memory");
            }
            uint32_t ob[6];
            lds128(ao, ob[0], ob[1], ob[2], ob[3]);
            lds64(ao + 64 - 8 * t, ob[4], ob[5]);
            float cc[5][4];
#pragma unroll
            for (int i = 0; i < 5; i++) cc[i][0] = cc[i][1] = cc[i][2] = cc[i][3] = 0.f;
            if ((PRE1 & 8) && layer) {
#pragma unroll
                for (int ks = 0; ks < 3; ks++) {
#pragma unroll
                    for (int i = 0; i < 5; i++) mma16816(cc[i], kq[3 * i + ks][0], kq[3 * i + ks][1], kq[3 * i + ks][2], kq[3 * i + ks][3], ob[2 * ks], ob[2 * ks + 1]);
                }
            } else {
#pragma unroll
                for (int ks = 0; ks < 3; ks++) {
                    mbar_wait(wbar + 8 * ks, wo2);
                    if (ks == 2) { PC(layer * 32 + 4); PROF_T(48 + layer * 2); }
                    uint32_t a[5][4];
#pragma unroll
                    for (int i = 0; i < 5; i++) ldsm4t(aw[i] + (ks == 2 ? aw2 : 20480 * ks), a[i]);
#pragma unroll
                    for (int i = 0; i < 5; i++) mma16816(cc[i], a[i][0], a[i][1], a[i][2], a[i][3], ob[2 * ks], ob[2 * ks + 1]);
                }
            }
            if (t == 0) {
#pragma unroll
                for (int i = 0; i < 5; i++) { sts32(dw + 512 * i, cc[i][0]); sts32(dw + 512 * i + 128, cc[i][2]); }
            }
        }
        PC(layer * 32 + 6);
        __syncthreads();
        PROF_T(6 + layer * 16);
        PC(layer * 32 + 7);
        if (tid < 54) {
            const float4 v0 = lds4f(pr), v1 = lds4f(pr + 16), v2 = lds4f(pr + 32);
            const float y0 = (v0.x + v0.y) + (v0.z + v0.w), y1 = (v1.x + v1.y) + (v1.z + v1.w), y2 = (v2.x + v2.y) + (v2.z + v2.w);
            red_pkt(pacc, y0, tid == 53 ? 0.f : y1, tid == 53 ? 0.f : y2);
        }
        if (tid == 224 && layer == 0) {
            misc[1] = __uint_as_float(ticket);
            if (ticket < DN0 + NDN && (ticket < NG || !DNTH)) load_ffn(maps, ticket, sb + SM_B, fbar);
        }
        PROF_T(7 + layer * 16);
        PC(layer * 32 + 8);
        __syncthreads();
        const int role = (int)__float_as_uint(misc[1]);
        PC(layer * 32 + 9);
        const uint32_t fbase = sb + SM_B;
        const uint32_t DONE32 = 0x42000000u;
        if (role < NG) {
            const int tid = opq(threadIdx.x), warp = tid >> 5, lane = tid & 31, g = lane >> 2, t = lane & 3, mat = lane >> 3, r8 = lane & 7;
            const uint32_t ag = fbase + (80 * warp + (mat >> 1) * 8 + r8) * 96 + (((mat & 1) ^ (r8 >> 2)) << 4);
            constexpr int GI = 32, GK = 16 * 96;
            const bool on = (g & 1) == (t >> 1), isx = on && g < 2;
            const uint32_t pm = opq(isx ? sb + SM_XS + 160 * warp + 16 * t : sb + (on ? SM_ONE : SM_ZERO)), pm2 = opq(pm + 128 - (isx ? 8 * t : 0));
            const uint32_t dg = opq(sb + SM_R + 4 * (2 * (warp * 48 + g) + t)), ds = opq(sb + SM_ST + 8 * warp + (lane < 16 ? 4 : 0));
            const bool ws = (lane & 15) == 0, lo = lane < 16;
            uint32_t pre[6][4];
            float s1 = 0.f, s2 = 0.f;
            {
                bool hx = wu == 7;
                int it = 0;
                const uint4* px = &g_scr.acc[layer][min(tid, 215) * ACC_STR];
                const int cq = tid / 54, r = tid - 54 * cq, k0 = min(160 * cq + 3 * r, DM - 1);
                const uint32_t w0 = sb + SM_XS + 4 * xpos(k0 >> 1), w1 = sb + SM_XS + 4 * xpos(min((k0 >> 1) + 1, DM / 2 - 1));
                const uint32_t e0 = w0 + 2 * (k0 & 1), e1 = (k0 & 1) ? w1 : w0 + 2, e2 = w1 + 2 * (k0 & 1);
                                auto sts16 = [](uint32_t a, uint32_t x, bool on) {
                    asm volatile("{\n.reg .pred p;\nsetp.ne.u32 p, %2, 0;\n@p st.shared.u16 [%0], %1;\n}" ::"r"(a), "h"((unsigned short)x), "r"((uint32_t)on) : "memory");
                };
                const bool on0 = tid < 216, on1 = on0 && r != 53;
                const float x0 = on0 ? f_(lds16(e0) << 16) : 0.f, x1 = on1 ? f_(lds16(e1) << 16) : 0.f, x2 = on1 ? f_(lds16(e2) << 16) : 0.f;
                auto take_x = [&](const uint4 v) {
                    if (__all_sync(0xffffffffu, v.w == DONE32)) {
                        hx = true;
                        const uint32_t a = pack2(f_(v.x), f_(v.y)), p = pack2(x0 + bf_lo(a), x1 + bf_hi(a)), q = pack2(x2 + bfr(f_(v.z)), 0.f);
                        sts16(e0, p, on0); sts16(e1, p >> 16, on1); sts16(e2, q, on1);
                        const float y0 = on0 ? bf_lo(p) : 0.f, y1 = on0 ? bf_hi(p) : 0.f, y2 = on0 ? bf_lo(q) : 0.f;
                        s1 = y0 + (y1 + y2); s2 = y0 * y0 + (y1 * y1 + y2 * y2);
                    }
                };
                auto try_x = [&]() { take_x(ld_pkt(px)); };
                while (!mbar_test(fbar, 0) && ++it < SPIN_CAP) { if (!hx) try_x(); }
                uint4 v0 = make_uint4(0u, 0u, 0u, 0u);
                if ((PRE1 & 4) && !hx) v0 = ld_pkt(px);
#pragma unroll
                for (int n = 0; n < 6; n++) ldsm4t(ag + (n % 3) * GI + (n / 3) * GK, pre[n]);
                if ((PRE1 & 1) && layer) {
#pragma unroll
                    for (int n = 6; n < 15; n++) ldsm4t(ag + (n % 3) * GI + (n / 3) * GK, kq[n - 6]);
                }
                if ((PRE1 & 4) && !hx) take_x(v0);
                PC(layer * 32 + 10);
                while (!hx && ++it < SPIN_CAP) try_x();
                PC(layer * 32 + 11);
            __syncthreads();
            PC(layer * 32 + 12);
            PROF_T(9 + layer * 16);
            float sv = lo ? s1 : s2, cc[3][4];
            if ((PRE1 & 1) && layer) gemv15r(cc, pre, kq, pm, pm2, sv, lo ? s2 : s1);
            else gemv15<GK>(cc, pre, [&](int i) { return ag + i * GI; }, pm, pm2, sv, lo ? s2 : s1);
#pragma unroll
            for (int i = 0; i < 3; i++) { sts32p(dg + 128 * i, cc[i][0] + cc[i][3], t & 2); sts32p(dg + 128 * i + 64, cc[i][1] + cc[i][2], t & 2); }
            if (ws) sts32(ds, sv);
            const uint32_t pg = opq(sb + SM_R + 8 * (24 * warp + (lane < 24 ? lane : 0))), st = opq(sb + SM_ST);
            uint4* const ph = opq(lane < 24 && lane % 6 == 0 ? &g_scr.ah[role * 8 + 4 * warp + lane / 6] : nullptr);
            PC(layer * 32 + 13);
            __syncthreads();
            PC(layer * 32 + 14);
            PROF_T(43 + layer * 16);
            if (wu < 2) {
                float mean, inv;
                ln_stats(st, mean, inv);
                float2 v[8];
#pragma unroll
                for (int w = 0; w < 8; w++) v[w] = lds2f(pg + w * 384);
                const float gx = ((v[0].x + v[1].x) + (v[2].x + v[3].x)) + ((v[4].x + v[5].x) + (v[6].x + v[7].x));
                const float gs = ((v[0].y + v[1].y) + (v[2].y + v[3].y)) + ((v[4].y + v[5].y) + (v[6].y + v[7].y));
                float ga = inv * (gx - mean * gs);
                if (role < NG / 2) { ga = bfr(ga); ga *= rcp(1.0f + ex2(-1.4426950408889634f * ga)); }
                const uint32_t wd = pack2(ga, __shfl_down_sync(0xffffffffu, ga, 1));
                const uint32_t wa = __shfl_down_sync(0xffffffffu, wd, 2), wb = __shfl_down_sync(0xffffffffu, wd, 4);
                if (ph) st_pkt(ph, wd, wa, wb, tag);
            }
            if (HOLD & 2) __syncthreads();
            }
            PROF_T(10 + layer * 16);
            PC(layer * 32 + 15);
        } else if (role < DN0 + NDN) {
            const int j = role - DN0;
            const int tid = opq(threadIdx.x), warp = tid >> 5, lane = tid & 31, g = lane >> 2, t = lane & 3, mat = lane >> 3, r8 = lane & 7;
            float xres = 0.f;
            uint32_t xr0 = 0, xr1 = 0;
            if (wu == 0) {
                const int col = 16 * j + (lane & 15), cc = col / 160, r = col - 160 * cc, e = r % 3;
                const uint4* px = &g_scr.acc[layer][(54 * cc + r / 3) * ACC_STR];
                const float x0 = __bfloat162float(reinterpret_cast<const __nv_bfloat16*>(xs32)[2 * xpos(col >> 1) + (col & 1)]);
                uint4 v;
                int it = 0;
                bool ld = DNTH && layer == 0;
                do {
                    v = ld_pkt(px);
                    if (ld && f_(__shfl_sync(0xffffffffu, v.w, 0)) >= (float)DNTH) { ld = false; if (lane == 0) load_ffn(maps, role, sb + SM_B, fbar); }
                } while (!__all_sync(0xffffffffu, v.w == DONE32) && ++it < SPIN_CAP);
                if (ld && lane == 0) load_ffn(maps, role, sb + SM_B, fbar);
                xres = x0 + bfr(f_(e == 0 ? v.x : (e == 1 ? v.y : v.z)));
                const int p4 = 4 * (lane & 3);
                xr0 = pack2(__shfl_sync(0xffffffffu, xres, p4), __shfl_sync(0xffffffffu, xres, p4 + 1));
                xr1 = pack2(__shfl_sync(0xffffffffu, xres, p4 + 2), __shfl_sync(0xffffffffu, xres, p4 + 3));
            }
            PC(layer * 32 + 17);
            PROF_T(9 + layer * 16);
            const uint32_t ad = fbase + (192 * warp + (mat >> 1) * 8 + r8) * 32 + (((mat & 1) ^ (r8 >> 2)) << 4);
            uint32_t* hs = reinterpret_cast<uint32_t*>(rr) + warp * 96;
            uint32_t pre[NPRE][4];
            {
                uint32_t pos[3];
#pragma unroll
                for (int i = 0; i < 3; i++) { const int w = 3 * lane + i; pos[i] = pin(sb + SM_R + 384 * warp + 4 * ((w & ~15) + 4 * (w & 3) + ((w >> 2) & 1) + ((w >> 2) & 2))); }
                uint4 v = make_uint4(0u, 0u, 0u, 0u), u = v;
                if (layer == 0) { v = ld_pkt(&g_scr.ah[tid]); u = ld_pkt(&g_scr.ah[256 + tid]); }
                mbar_wait(fbar, 0);
#pragma unroll
                for (int n = 0; n < NPRE; n++) ldsm4t(ad + n * 512, pre[n]);
                if ((PRE1 & 2) && layer) {
#pragma unroll
                    for (int n = NPRE; n < 12; n++) ldsm4t(ad + n * 512, kq[12 + n]);
                }
                PC(layer * 32 + 18);
                int it = 0;
                for (; any_ne(v.w, u.w, tag) && it < SPIN_CAP; it++) { v = ld_pkt(&g_scr.ah[tid]); u = ld_pkt(&g_scr.ah[256 + tid]); }
                PC(layer * 32 + 19);
                sts32(pos[0], f_(bmul2(v.x, u.x))); sts32(pos[1], f_(bmul2(v.y, u.y))); sts32(pos[2], f_(bmul2(v.z, u.z)));
            __syncwarp();
            PROF_T(11 + layer * 16);
            PC(layer * 32 + 20);
            float ca[4] = {0.f, 0.f, 0.f, 0.f}, cb[4] = {0.f, 0.f, 0.f, 0.f};
            if ((PRE1 & 2) && layer) {
                float cc[4] = {0.f, 0.f, 0.f, 0.f}, cd[4] = {0.f, 0.f, 0.f, 0.f};
#pragma unroll
                for (int jj = 0; jj < 6; jj++) {
                    const uint4 hv = *reinterpret_cast<const uint4*>(hs + 16 * jj + 4 * t);
                    const uint32_t (&f0)[4] = 2 * jj < NPRE ? pre[2 * jj < NPRE ? 2 * jj : 0] : kq[12 + 2 * jj];
                    const uint32_t (&f1)[4] = 2 * jj + 1 < NPRE ? pre[2 * jj + 1 < NPRE ? 2 * jj + 1 : 0] : kq[13 + 2 * jj];
                    if (jj & 1) { mma16816(cc, f0[0], f0[1], f0[2], f0[3], hv.x, hv.y); mma16816(cd, f1[0], f1[1], f1[2], f1[3], hv.z, hv.w); }
                    else { mma16816(ca, f0[0], f0[1], f0[2], f0[3], hv.x, hv.y); mma16816(cb, f1[0], f1[1], f1[2], f1[3], hv.z, hv.w); }
                }
#pragma unroll
                for (int e = 0; e < 4; e++) { ca[e] += cc[e]; cb[e] += cd[e]; }
            } else {
#pragma unroll
                for (int jj = 0; jj < 6; jj++) {
                    const uint4 hv = *reinterpret_cast<const uint4*>(hs + 16 * jj + 4 * t);
                    uint32_t a[4];
                    if (2 * jj < NPRE) { a[0] = pre[2 * jj][0]; a[1] = pre[2 * jj][1]; a[2] = pre[2 * jj][2]; a[3] = pre[2 * jj][3]; }
                    else ldsm4t(ad + 2 * jj * 512, a);
                    mma16816(ca, a[0], a[1], a[2], a[3], hv.x, hv.y);
                    if (2 * jj + 1 < NPRE) { a[0] = pre[2 * jj + 1][0]; a[1] = pre[2 * jj + 1][1]; a[2] = pre[2 * jj + 1][2]; a[3] = pre[2 * jj + 1][3]; }
                    else ldsm4t(ad + (2 * jj + 1) * 512, a);
                    mma16816(cb, a[0], a[1], a[2], a[3], hv.z, hv.w);
                }
            }
            if (t == 0) { rr[768 + warp * 16 + g] = ca[0] + cb[0]; rr[768 + warp * 16 + 8 + g] = ca[2] + cb[2]; }
            const uint32_t pd = opq(sb + SM_R + 3072 + 16 * (lane & 3));
            uint4* const py = opq(&g_scr.ay[j * 4 + lane]);
            uint2* const po = opq(reinterpret_cast<uint2*>(out + 16 * j) + lane);
            PC(layer * 32 + 21);
            __syncthreads();
            PC(layer * 32 + 22);
            if (wu == 0) {
                float4 p[8];
#pragma unroll
                for (int w = 0; w < 8; w++) p[w] = lds4f(pd + 64 * w);
                const uint32_t y0 = pack2(((p[0].x + p[1].x) + (p[2].x + p[3].x)) + ((p[4].x + p[5].x) + (p[6].x + p[7].x)),
                                          ((p[0].y + p[1].y) + (p[2].y + p[3].y)) + ((p[4].y + p[5].y) + (p[6].y + p[7].y)));
                const uint32_t y1 = pack2(((p[0].z + p[1].z) + (p[2].z + p[3].z)) + ((p[4].z + p[5].z) + (p[6].z + p[7].z)),
                                          ((p[0].w + p[1].w) + (p[2].w + p[3].w)) + ((p[4].w + p[5].w) + (p[6].w + p[7].w)));
                uint32_t wd, wn;
                asm("add.rn.bf16x2 %0, %1, %2;" : "=r"(wd) : "r"(xr0), "r"(y0));
                asm("add.rn.bf16x2 %0, %1, %2;" : "=r"(wn) : "r"(xr1), "r"(y1));
                asm volatile("{\n.reg .pred p;\nsetp.ne.u32 p, %3, 0;\n@p st.global.v2.u32 [%0], {%1,%2};\n}" ::"l"(po), "r"(wd), "r"(wn), "r"((uint32_t)(layer && tid < 4)) : "memory");
                st_pktp(py, wd, wn, 0, tag, tid < 4);
            }
            if (HOLD & 1) __syncthreads();
            }
            PROF_T(12 + layer * 16);
            PC(layer * 32 + 23);
        }
    }
}

typedef CUresult (*EncodeFn)(CUtensorMap*, CUtensorMapDataType, cuuint32_t, void*, const cuuint64_t*, const cuuint64_t*, const cuuint32_t*,
                             const cuuint32_t*, CUtensorMapInterleave, CUtensorMapSwizzle, CUtensorMapL2promotion, CUtensorMapFloatOOBfill);

void make_map(EncodeFn enc, CUtensorMap* m, const void* base, int rank, uint64_t d0, uint64_t d1, uint64_t d2, uint64_t s1, uint64_t s2,
              uint32_t b0, uint32_t b1, uint32_t b2, CUtensorMapSwizzle sw, CUtensorMapL2promotion pr = CU_TENSOR_MAP_L2_PROMOTION_NONE) {
    cuuint64_t dims[3] = {d0, d1, d2};
    cuuint64_t strides[2] = {s1, s2};
    cuuint32_t box[3] = {b0, b1, b2};
    cuuint32_t es[3] = {1, 1, 1};
    enc(m, CU_TENSOR_MAP_DATA_TYPE_BFLOAT16, rank, const_cast<void*>(base), dims, strides, box, es, CU_TENSOR_MAP_INTERLEAVE_NONE, sw,
        pr, CU_TENSOR_MAP_FLOAT_OOB_FILL_NONE);
}

}

extern "C" void kernel_launch(void* const* d_in, const int* in_sizes, int n_in, void* d_out, int out_size) {
    (void)in_sizes; (void)n_in; (void)out_size;
    static EncodeFn enc = nullptr;
    if (!enc) {
        void* fn = nullptr;
        cudaDriverEntryPointQueryResult qr;
        cudaGetDriverEntryPoint("cuTensorMapEncodeTiled", &fn, cudaEnableDefault, &qr);
        enc = reinterpret_cast<EncodeFn>(fn);
        cudaFuncSetAttribute(decode_kernel, cudaFuncAttributeMaxDynamicSharedMemorySize, SM_TOTAL);
    }
    Maps maps;
    make_map(enc, &maps.k, d_in[1], 2, 64, (uint64_t)NH * SK * 3, 1, 128, 0, 64, 48, 1, CU_TENSOR_MAP_SWIZZLE_128B);
    make_map(enc, &maps.v, d_in[2], 2, 64, (uint64_t)NH * SK * 3, 1, 128, 0, 64, 48, 1, CU_TENSOR_MAP_SWIZZLE_128B);
    make_map(enc, &maps.wq, d_in[3], 3, 64, DM, NH * DH / 64, NH * DH * 2, 128, 64, 160, 3, CU_TENSOR_MAP_SWIZZLE_128B);
    make_map(enc, &maps.wo, d_in[4], 3, 32, DM / 32, NH * DH, 64, DM * 2, 32, 5, 32, CU_TENSOR_MAP_SWIZZLE_64B);
    make_map(enc, &maps.vr, (const char*)d_in[2] + 512, 2, 128, (uint64_t)NH * SK / 2, 1, 768, 0, 128, 2, 1, CU_TENSOR_MAP_SWIZZLE_NONE);
    constexpr int GW = 48;
    make_map(enc, &maps.w1, d_in[6], 3, FF, 160, 4, FF * 2, 160 * FF * 2, GW, 160, 4, CU_TENSOR_MAP_SWIZZLE_NONE, FFN_PROMO);
    make_map(enc, &maps.w3, d_in[7], 3, FF, 160, 4, FF * 2, 160 * FF * 2, GW, 160, 4, CU_TENSOR_MAP_SWIZZLE_NONE, FFN_PROMO);
    make_map(enc, &maps.w2, d_in[8], 3, DM, 256, 6, DM * 2, 256 * DM * 2, 16, 256, 6, CU_TENSOR_MAP_SWIZZLE_32B, FFN_PROMO);
    maps.vp = d_in[2];
    maps.kp = d_in[1];
    maps.zero = 0;
    decode_kernel<<<NCTA, NT, SM_TOTAL, cudaStreamPerThread>>>(maps, (const __nv_bfloat16*)d_in[0], (__nv_bfloat16*)d_out);
}
```

```cpp
#include <cuda_runtime.h>
#include <cuda_bf16.h>
#include <cuda.h>
#include <stdint.h>
#include <math.h>

namespace {

constexpr int DM = 640;
constexpr int NH = 32;
constexpr int DH = 192;
constexpr int SK = 32768;
constexpr int WIN = 4096;
constexpr int FF = 1536;
constexpr int NCTA = 128;
constexpr int NT = 256;
constexpr int TILE = 6144;
constexpr int NG = 64;
constexpr int DN0 = 64;
constexpr int NDN = 40;

constexpr int SM_RING = 0;
constexpr int SM_B = 8 * 2 * TILE;
constexpr int SM_Q = SM_B + 61440;
__host__ __device__ constexpr int c_slot(int w) { return w < 2 ? 4096 + 10240 * w : 12288 + 6144 * w; }
__host__ __device__ constexpr int v1_pos(int n) { return 10240 * (n >> 3) + 512 * (n & 7); }
constexpr int SM_XS = SM_Q + 61440;
constexpr int SM_R = SM_XS + 1280;
constexpr int SM_ST = SM_R + 4096;
constexpr int SM_QS = SM_R + 6272;
constexpr int SM_OS = SM_QS + 384;
constexpr int SM_BAR = SM_OS + 384;
constexpr int SM_XBAR = SM_BAR + 24 * 8;
constexpr int SM_MISC = SM_XBAR + 8 * 8;
constexpr int SM_ONE = SM_MISC + 16;
constexpr int SM_ZERO = SM_ONE + 160;
constexpr int XCAP = 48;
constexpr int XSTR = 16 + 4 * XCAP;
constexpr int SM_XL = SM_ZERO + 160;
constexpr int SM_TOTAL = SM_XL + 8 * XSTR;
static_assert(SM_TOTAL <= 232448, "shared memory");

constexpr unsigned long long POL_EF = 0x12F0000000000000ull;
constexpr unsigned long long POL_EN = 0x16F0000000000000ull;

#define RT_MASK 0xF2E0u
#define RT_MASK2 0xEAE0u
#define WO_AT1 5
#define FFN_PROMO CU_TENSOR_MAP_L2_PROMOTION_NONE
#define FFN_POL POL_EF
#define HAS_FFN (__float_as_uint(misc[1]) < DN0 + NDN)
#define ACC_STR 1
#define NPRE 6

#define STAG 200
#define L1R 3
#define PRE1 13
#define HOLD 2
#define DNTH 23
constexpr int V0_AT = 8;
constexpr unsigned long long SEQ1 = 0x2765431076543210ull;
constexpr uint32_t IN_S1 = 0xAA49, IN_S0 = 0x124, PARITY1 = 0x6638, PARITY2 = 0xCE;
#define KEEP4 1
constexpr int NQ = 48;
constexpr int SPIN_CAP = 1 << 19;
constexpr uint32_t ONES = 0x3F803F80u;

struct alignas(1024) Scratch {
    uint4 hx[NCTA * 48];
    uint4 pad0[32 * 5 * 32 + 160];
    uint4 acc[2][216 * 8];
    uint4 ay[160];
    uint4 ah[NG * 8];
    uint2 mx[NH * 32];
    uint32_t ticket[32];
    uint32_t pad1[32];
};
__device__ Scratch g_scr;
#define PROF_T(i)
#define PROF_X(i)
#define PC(i)

__device__ __forceinline__ uint32_t smem_u32(const void* p) { return (uint32_t)__cvta_generic_to_shared(p); }
__device__ __forceinline__ void mbar_init(uint32_t bar, uint32_t cnt) {
    asm volatile("mbarrier.init.shared::cta.b64 [%0], %1;" ::"r"(bar), "r"(cnt) : "memory");
}
__device__ __forceinline__ void mbar_expect_tx(uint32_t bar, uint32_t bytes) {
    asm volatile("mbarrier.arrive.expect_tx.shared::cta.b64 _, [%0], %1;" ::"r"(bar), "r"(bytes) : "memory");
}
__device__ __forceinline__ bool mbar_test(uint32_t bar, uint32_t parity) {
    uint32_t done;
    asm volatile("{\n.reg .pred p;\nmbarrier.try_wait.parity.shared::cta.b64 p, [%1], %2;\nselp.u32 %0, 1, 0, p;\n}"
                 : "=r"(done) : "r"(bar), "r"(parity) : "memory");
    return done;
}
__device__ __forceinline__ void mbar_wait(uint32_t bar, uint32_t parity) {
    for (int it = 0; it < SPIN_CAP; it++) if (mbar_test(bar, parity)) break;
}
__device__ __forceinline__ void tma2d(uint32_t dst, const CUtensorMap* map, int c0, int c1, uint32_t bar, unsigned long long pol) {
    asm volatile("cp.async.bulk.tensor.2d.shared::cluster.global.mbarrier::complete_tx::bytes.L2::cache_hint [%0], [%1, {%3, %4}], [%2], %5;"
                 ::"r"(dst), "l"(map), "r"(bar), "r"(c0), "r"(c1), "l"(pol) : "memory");
}
__device__ __forceinline__ void tma3d(uint32_t dst, const CUtensorMap* map, int c0, int c1, int c2, uint32_t bar, unsigned long long pol) {
    asm volatile("cp.async.bulk.tensor.3d.shared::cluster.global.mbarrier::complete_tx::bytes.L2::cache_hint [%0], [%1, {%3, %4, %5}], [%2], %6;"
                 ::"r"(dst), "l"(map), "r"(bar), "r"(c0), "r"(c1), "r"(c2), "l"(pol) : "memory");
}
__device__ __forceinline__ void tile_load(uint32_t dst, const CUtensorMap* map, int row, uint32_t bar, uint32_t dep, uint32_t zero) {
    asm volatile("{\n.reg .pred p;\n.reg .b32 n;\nmad.lo.u32 n, %5, %6, 6144;\nelect.sync _|p, 0xffffffff;\n"
                 "@p mbarrier.arrive.expect_tx.shared::cta.b64 _, [%2], n;\n"
                 "@p cp.async.bulk.tensor.2d.shared::cluster.global.mbarrier::complete_tx::bytes.L2::cache_hint [%0], [%1, {0, %3}], [%2], %4;\n}"
                 ::"r"(dst), "l"(map), "r"(bar), "r"(row), "l"(POL_EF), "r"(dep), "r"(zero) : "memory");
}
__device__ __forceinline__ void tile_keep(const CUtensorMap* map, int row) {
    asm volatile("{\n.reg .pred p;\nelect.sync _|p, 0xffffffff;\n"
                 "@p cp.async.bulk.prefetch.tensor.2d.L2.global.L2::cache_hint [%0, {0, %1}], %2;\n}"
                 ::"l"(map), "r"(row), "l"(POL_EN) : "memory");
}
__device__ __forceinline__ void tile_load_l1(uint32_t dst, const void* base, int row, uint32_t bar, int lane) {
    const char* g = static_cast<const char*>(base) + (size_t)row * 128 + lane * 16;
    const uint32_t s0 = dst + (lane >> 3) * 128 + (((lane & 7) ^ (lane >> 3)) << 4), s1 = s0 ^ 64;
#pragma unroll
    for (int k = 0; k < 12; k++)
        asm volatile("cp.async.ca.shared.global.L2::cache_hint [%0], [%1], 16, %2;" ::"r"(((k & 1) ? s1 : s0) + k * 512), "l"(g + k * 512), "l"(POL_EF) : "memory");
    asm volatile("cp.async.mbarrier.arrive.shared::cta.b64 [%0];" ::"r"(bar) : "memory");
    __syncwarp();
    if (lane == 0) asm volatile("mbarrier.arrive.shared::cta.b64 _, [%0];" ::"r"(bar) : "memory");
}
__device__ __forceinline__ bool elect_one() {
    uint32_t p;
    asm volatile("{\n.reg .pred p;\nelect.sync _|p, 0xffffffff;\nselp.u32 %0, 1, 0, p;\n}" : "=r"(p));
    return p;
}
__device__ __forceinline__ void lds128(uint32_t addr, uint32_t& a, uint32_t& b, uint32_t& c, uint32_t& d) {
    asm volatile("ld.shared.v4.u32 {%0,%1,%2,%3}, [%4];" : "=r"(a), "=r"(b), "=r"(c), "=r"(d) : "r"(addr) : "memory");
}
__device__ __forceinline__ void lds128p(uint32_t addr, uint32_t on, uint32_t& a, uint32_t& b, uint32_t& c, uint32_t& d) {
    asm volatile("{\n.reg .pred p;\nsetp.ne.u32 p, %5, 0;\n@p ld.shared.v4.u32 {%0,%1,%2,%3}, [%4];\n}" : "+r"(a), "+r"(b), "+r"(c), "+r"(d) : "r"(addr), "r"(on) : "memory");
}
__device__ __forceinline__ void lds64(uint32_t addr, uint32_t& a, uint32_t& b) {
    asm volatile("ld.shared.v2.u32 {%0,%1}, [%2];" : "=r"(a), "=r"(b) : "r"(addr) : "memory");
}
__device__ __forceinline__ void ldsm4t(uint32_t addr, uint32_t (&a)[4]) {
    asm volatile("ldmatrix.sync.aligned.m8n8.x4.trans.shared.b16 {%0,%1,%2,%3}, [%4];" : "=r"(a[0]), "=r"(a[1]), "=r"(a[2]), "=r"(a[3]) : "r"(addr) : "memory");
}
__device__ __forceinline__ void mma16816(float (&c)[4], uint32_t a0, uint32_t a1, uint32_t a2, uint32_t a3, uint32_t b0, uint32_t b1) {
    asm("mma.sync.aligned.m16n8k16.row.col.f32.bf16.bf16.f32 {%0,%1,%2,%3}, {%4,%5,%6,%7}, {%8,%9}, {%0,%1,%2,%3};"
        : "+f"(c[0]), "+f"(c[1]), "+f"(c[2]), "+f"(c[3]) : "r"(a0), "r"(a1), "r"(a2), "r"(a3), "r"(b0), "r"(b1));
}
__device__ __forceinline__ void mma16816v(float (&c)[4], uint32_t a0, uint32_t a1, uint32_t a2, uint32_t a3, uint32_t b0, uint32_t b1) {
    asm volatile("mma.sync.aligned.m16n8k16.row.col.f32.bf16.bf16.f32 {%0,%1,%2,%3}, {%4,%5,%6,%7}, {%8,%9}, {%0,%1,%2,%3};"
        : "+f"(c[0]), "+f"(c[1]), "+f"(c[2]), "+f"(c[3]) : "r"(a0), "r"(a1), "r"(a2), "r"(a3), "r"(b0), "r"(b1));
}
__device__ __forceinline__ int xpos(int w) {
    const int seg = w / 40, r = w - 40 * seg;
    return 40 * seg + (r < 32 ? (r & 16) + 4 * (r & 3) + ((r >> 2) & 3) : 32 + 2 * (r & 3) + ((r >> 2) & 1));
}
#define NA_LD ""
#define NA_ST ""
__device__ __forceinline__ void st_pkt(uint4* p, uint32_t a, uint32_t b, uint32_t c, uint32_t d) {
    asm volatile("{\n.reg .b128 t;\n.reg .b64 lo, hi;\nmov.b64 lo, {%1,%2};\nmov.b64 hi, {%3,%4};\nmov.b128 t, {lo,hi};\nst.relaxed.gpu.global" NA_ST ".b128 [%0], t;\n}"
                 ::"l"(p), "r"(a), "r"(b), "r"(c), "r"(d) : "memory");
}
__device__ __forceinline__ void red_pkt(uint4* p, float a, float b, float c) {
    asm volatile("red.relaxed.gpu.global.add.v4.f32 [%0], {%1,%2,%3,%4};" ::"l"(p), "f"(a), "f"(b), "f"(c), "f"(1.0f) : "memory");
}
__device__ __forceinline__ void st_pktp(uint4* p, uint32_t a, uint32_t b, uint32_t c, uint32_t d, bool on) {
    asm volatile("{\n.reg .pred p;\n.reg .b128 t;\n.reg .b64 lo, hi;\nsetp.ne.u32 p, %5, 0;\nmov.b64 lo, {%1,%2};\nmov.b64 hi, {%3,%4};\nmov.b128 t, {lo,hi};\n"
                 "@p st.relaxed.gpu.global.b128 [%0], t;\n}" ::"l"(p), "r"(a), "r"(b), "r"(c), "r"(d), "r"((uint32_t)on) : "memory");
}
__device__ __forceinline__ void st_pktfp(uint4* p, float a, float b, float c, float d, uint32_t bit, bool on) {
    st_pktp(p, __float_as_uint(a), __float_as_uint(b), __float_as_uint(c), (__float_as_uint(d) & ~1u) | bit, on);
}
__device__ __forceinline__ uint4 ld_pkt(const uint4* p) {
    uint4 v;
    asm volatile("{\n.reg .b128 t;\n.reg .b64 lo, hi;\nld.relaxed.gpu.global" NA_LD ".b128 t, [%4];\nmov.b128 {lo,hi}, t;\nmov.b64 {%0,%1}, lo;\nmov.b64 {%2,%3}, hi;\n}"
                 : "=r"(v.x), "=r"(v.y), "=r"(v.z), "=r"(v.w) : "l"(p) : "memory");
    return v;
}
__device__ __forceinline__ bool all_odd(uint32_t a, uint32_t b, uint32_t c, uint32_t d) {
    uint32_t r;
    asm volatile("{\n.reg .pred p, q, t;\n.reg .b32 x;\nsetp.eq.b32 t, 0, 0;\nlop3.b32 x, %1, %2, %3, 0x80;\nlop3.and.b32 _|p, x, %4, 1, 0x80, t;\n"
                 "vote.sync.all.pred q, p, 0xffffffff;\nselp.u32 %0, 1, 0, q;\n}" : "=r"(r) : "r"(a), "r"(b), "r"(c), "r"(d));
    return r;
}
__device__ __forceinline__ bool any_odd(uint32_t a, uint32_t b, uint32_t c) {
    uint32_t r;
    asm volatile("{\n.reg .pred p, q, t;\n.reg .b32 x;\nsetp.eq.b32 t, 0, 0;\nlop3.b32 x, %1, %2, %3, 0xFE;\nlop3.and.b32 _|p, x, 1, 0, 0xC0, t;\n"
                 "vote.sync.any.pred q, p, 0xffffffff;\nselp.u32 %0, 1, 0, q;\n}" : "=r"(r) : "r"(a), "r"(b), "r"(c));
    return r;
}
__device__ __forceinline__ bool any_ne(uint32_t a, uint32_t b, uint32_t c) {
    uint32_t r;
    asm volatile("{\n.reg .pred p, q, t;\nsetp.eq.b32 t, 0, 0;\nlop3.and.b32 _|p, %1, %2, %3, 0x7E, t;\n"
                 "vote.sync.any.pred q, p, 0xffffffff;\nselp.u32 %0, 1, 0, q;\n}" : "=r"(r) : "r"(a), "r"(b), "r"(c));
    return r;
}
__device__ __forceinline__ uint2 ld_pkt2(const uint2* p) {
    unsigned long long v;
    asm volatile("ld.relaxed.gpu.global" NA_LD ".b64 %0, [%1];" : "=l"(v) : "l"(p) : "memory");
    return make_uint2((uint32_t)v, (uint32_t)(v >> 32));
}
__device__ __forceinline__ void st_pkt2(uint2* p, uint32_t a, uint32_t b) {
    asm volatile("st.relaxed.gpu.global" NA_ST ".b64 [%0], %1;" ::"l"(p), "l"((unsigned long long)a | ((unsigned long long)b << 32)) : "memory");
}
__device__ __forceinline__ float ex2(float x) { float y; asm("ex2.approx.ftz.f32 %0, %1;" : "=f"(y) : "f"(x)); return y; }
__device__ __forceinline__ float rcp(float x) { float y; asm("rcp.approx.ftz.f32 %0, %1;" : "=f"(y) : "f"(x)); return y; }
__device__ __forceinline__ uint32_t pack2(float lo, float hi) {
    uint32_t r; asm("cvt.rn.bf16x2.f32 %0, %1, %2;" : "=r"(r) : "f"(hi), "f"(lo)); return r;
}
__device__ __forceinline__ float bf_lo(uint32_t w) { return __uint_as_float(w << 16); }
__device__ __forceinline__ float bf_hi(uint32_t w) { return __uint_as_float(w & 0xffff0000u); }
__device__ __forceinline__ float bfr(float x) { return bf_lo(pack2(x, 0.f)); }
__device__ __forceinline__ float f_(uint32_t u) { return __uint_as_float(u); }

template <int SK, typename AddrF>
__device__ __forceinline__ void gemv15(float (&cc)[3][4], uint32_t (&pre)[6][4], AddrF ad, uint32_t px, uint32_t px2, float& sv, float so) {
    uint32_t x0[4], x1[4], a[3][4];
    asm volatile("ld.shared.v4.u32 {%0,%1,%2,%3}, [%20];\nld.shared.v4.u32 {%4,%5,%6,%7}, [%20+64];\n"
                 "ldmatrix.sync.aligned.m8n8.x4.trans.shared.b16 {%8,%9,%10,%11}, [%21];\n"
                 "ldmatrix.sync.aligned.m8n8.x4.trans.shared.b16 {%12,%13,%14,%15}, [%22];\n"
                 "ldmatrix.sync.aligned.m8n8.x4.trans.shared.b16 {%16,%17,%18,%19}, [%23];\nbar.warp.sync 0xffffffff;"
                 : "=r"(x0[0]), "=r"(x0[1]), "=r"(x0[2]), "=r"(x0[3]), "=r"(x1[0]), "=r"(x1[1]), "=r"(x1[2]), "=r"(x1[3]),
                   "=r"(a[0][0]), "=r"(a[0][1]), "=r"(a[0][2]), "=r"(a[0][3]), "=r"(a[1][0]), "=r"(a[1][1]), "=r"(a[1][2]), "=r"(a[1][3]),
                   "=r"(a[2][0]), "=r"(a[2][1]), "=r"(a[2][2]), "=r"(a[2][3])
                 : "r"(px), "r"(ad(0) + 2 * SK), "r"(ad(1) + 2 * SK), "r"(ad(2) + 2 * SK) : "memory");
    __syncwarp();
    sv += __shfl_xor_sync(0xffffffffu, so, 16);
#pragma unroll
    for (int i = 0; i < 3; i++) {
        cc[i][0] = cc[i][1] = cc[i][2] = cc[i][3] = 0.f;
        mma16816v(cc[i], pre[i][0], pre[i][1], pre[i][2], pre[i][3], x0[0], x0[1]);
    }
    sv += __shfl_xor_sync(0xffffffffu, sv, 8);
#pragma unroll
    for (int i = 0; i < 3; i++) {
        mma16816v(cc[i], pre[3 + i][0], pre[3 + i][1], pre[3 + i][2], pre[3 + i][3], x0[2], x0[3]);
        ldsm4t(ad(i) + 3 * SK, pre[i]);
    }
    lds64(px2, x0[0], x0[1]);
    __syncwarp();
    sv += __shfl_xor_sync(0xffffffffu, sv, 4);
#pragma unroll
    for (int i = 0; i < 3; i++) {
        mma16816v(cc[i], a[i][0], a[i][1], a[i][2], a[i][3], x1[0], x1[1]);
        ldsm4t(ad(i) + 4 * SK, pre[3 + i]);
    }
    __syncwarp();
    sv += __shfl_xor_sync(0xffffffffu, sv, 2);
#pragma unroll
    for (int i = 0; i < 3; i++) mma16816v(cc[i], pre[i][0], pre[i][1], pre[i][2], pre[i][3], x1[2], x1[3]);
    sv += __shfl_xor_sync(0xffffffffu, sv, 1);
#pragma unroll
    for (int i = 0; i < 3; i++) mma16816v(cc[i], pre[3 + i][0], pre[3 + i][1], pre[3 + i][2], pre[3 + i][3], x0[0], x0[1]);
}
__device__ __forceinline__ void gemv15r(float (&cc)[3][4], const uint32_t (&pre)[6][4], const uint32_t (&ext)[NQ][4], uint32_t px, uint32_t px2, float& sv, float so) {
    uint32_t x0[4], x1[4], x2[2];
    float cd[3][4];
    lds128(px, x0[0], x0[1], x0[2], x0[3]);
    lds128(px + 64, x1[0], x1[1], x1[2], x1[3]);
    lds64(px2, x2[0], x2[1]);
    sv += __shfl_xor_sync(0xffffffffu, so, 16);
#pragma unroll
    for (int i = 0; i < 3; i++) {
        cc[i][0] = cc[i][1] = cc[i][2] = cc[i][3] = cd[i][0] = cd[i][1] = cd[i][2] = cd[i][3] = 0.f;
        mma16816v(cc[i], pre[i][0], pre[i][1], pre[i][2], pre[i][3], x0[0], x0[1]);
        mma16816v(cd[i], pre[3 + i][0], pre[3 + i][1], pre[3 + i][2], pre[3 + i][3], x0[2], x0[3]);
    }
    sv += __shfl_xor_sync(0xffffffffu, sv, 8);
#pragma unroll
    for (int i = 0; i < 3; i++) {
        mma16816v(cc[i], ext[i][0], ext[i][1], ext[i][2], ext[i][3], x1[0], x1[1]);
        mma16816v(cd[i], ext[3 + i][0], ext[3 + i][1], ext[3 + i][2], ext[3 + i][3], x1[2], x1[3]);
    }
    sv += __shfl_xor_sync(0xffffffffu, sv, 4);
#pragma unroll
    for (int i = 0; i < 3; i++) mma16816v(cc[i], ext[6 + i][0], ext[6 + i][1], ext[6 + i][2], ext[6 + i][3], x2[0], x2[1]);
    sv += __shfl_xor_sync(0xffffffffu, sv, 2);
    sv += __shfl_xor_sync(0xffffffffu, sv, 1);
#pragma unroll
    for (int i = 0; i < 3; i++) { cc[i][0] += cd[i][0]; cc[i][1] += cd[i][1]; cc[i][2] += cd[i][2]; cc[i][3] += cd[i][3]; }
}

__device__ __forceinline__ float warp_max(float x) {
    int i = __float_as_int(x);
    i = __reduce_max_sync(0xffffffffu, i ^ ((i >> 31) & 0x7fffffff));
    return __int_as_float(i ^ ((i >> 31) & 0x7fffffff));
}
__device__ __forceinline__ void idle(uint32_t clk) {
    uint32_t t0, t;
    asm volatile("mov.u32 %0, %%clock;" : "=r"(t0) :: "memory");
    do asm volatile("mov.u32 %0, %%clock;" : "=r"(t) :: "memory"); while (t - t0 < clk);
}
__device__ __forceinline__ uint32_t now_ns() { uint32_t t; asm volatile("mov.u32 %0, %%globaltimer_lo;" : "=r"(t)); return t; }
__device__ __forceinline__ int opq(int x) { asm volatile("" : "+r"(x)); return x; }
__device__ __forceinline__ uint32_t opq(uint32_t x) { asm volatile("" : "+r"(x)); return x; }
__device__ __forceinline__ uint32_t pin(uint32_t x) { return __shfl_sync(0xffffffffu, x, threadIdx.x & 31); }
template <typename T> __device__ __forceinline__ T* pin(T* p) {
    const unsigned long long v = (unsigned long long)p;
    return (T*)((unsigned long long)pin((uint32_t)v) | (unsigned long long)pin((uint32_t)(v >> 32)) << 32);
}
template <typename T> __device__ __forceinline__ T* opq(T* p) { asm volatile("" : "+l"(p)); return p; }
__device__ __forceinline__ float4 lds4f(uint32_t a) { float4 v; asm volatile("ld.shared.v4.f32 {%0,%1,%2,%3}, [%4];" : "=f"(v.x), "=f"(v.y), "=f"(v.z), "=f"(v.w) : "r"(a) : "memory"); return v; }
__device__ __forceinline__ float2 lds2f(uint32_t a) { float2 v; asm volatile("ld.shared.v2.f32 {%0,%1}, [%2];" : "=f"(v.x), "=f"(v.y) : "r"(a) : "memory"); return v; }
__device__ __forceinline__ void ln_stats(uint32_t st, float& mean, float& inv) {
    const float4 a = lds4f(st), b = lds4f(st + 16), c = lds4f(st + 32), d = lds4f(st + 48);
    const float s2 = ((a.x + a.z) + (b.x + b.z)) + ((c.x + c.z) + (d.x + d.z));
    const float md = (((a.y + a.w) + (b.y + b.w)) + ((c.y + c.w) + (d.y + d.w))) * (1.0f / DM);
    const float var = fmaxf(s2 * (1.0f / DM) - md * md, 0.f);
    mean = bfr(md);
    asm("rsqrt.approx.ftz.f32 %0, %1;" : "=f"(inv) : "f"(var + 1e-5f));
}
__device__ __forceinline__ void sts32(uint32_t a, float v) { asm volatile("st.shared.f32 [%0], %1;" ::"r"(a), "f"(v) : "memory"); }
__device__ __forceinline__ void sts32p(uint32_t a, float v, uint32_t off) {
    asm volatile("{\n.reg .pred p;\nsetp.eq.u32 p, %2, 0;\n@p st.shared.f32 [%0], %1;\n}" ::"r"(a), "f"(v), "r"(off) : "memory");
}
__device__ __forceinline__ void sts128p(uint32_t a, float x, float y, float z, float w, uint32_t off) {
    asm volatile("{\n.reg .pred p;\nsetp.eq.u32 p, %5, 0;\n@p st.shared.v4.f32 [%0], {%1,%2,%3,%4};\n}" ::"r"(a), "f"(x), "f"(y), "f"(z), "f"(w), "r"(off) : "memory");
}
__device__ __forceinline__ void sts64(uint32_t a, float v, float w) { asm volatile("st.shared.v2.f32 [%0], {%1,%2};" ::"r"(a), "f"(v), "f"(w) : "memory"); }

__device__ __forceinline__ uint32_t prmt(uint32_t a, uint32_t b, uint32_t s) { uint32_t r; asm("prmt.b32 %0, %1, %2, %3;" : "=r"(r) : "r"(a), "r"(b), "r"(s)); return r; }
__device__ __forceinline__ uint32_t bmul2(uint32_t a, uint32_t b) { uint32_t r; asm("mul.rn.bf16x2 %0, %1, %2;" : "=r"(r) : "r"(a), "r"(b)); return r; }
__device__ __forceinline__ void sts128(uint32_t addr, uint32_t a, uint32_t b, uint32_t c, uint32_t d) {
    asm volatile("st.shared.v4.u32 [%0], {%1,%2,%3,%4};" ::"r"(addr), "r"(a), "r"(b), "r"(c), "r"(d) : "memory");
}
__device__ __forceinline__ uint4 ldg128(const uint4* p) {
    uint4 v;
    asm volatile("ld.volatile.global.v4.u32 {%0,%1,%2,%3}, [%4];" : "=r"(v.x), "=r"(v.y), "=r"(v.z), "=r"(v.w) : "l"(p) : "memory");
    return v;
}
__device__ __forceinline__ uint32_t lds32(uint32_t a) { uint32_t v; asm volatile("ld.shared.u32 %0, [%1];" : "=r"(v) : "r"(a) : "memory"); return v; }
__device__ __forceinline__ uint32_t lds16(uint32_t a) { unsigned short v; asm volatile("ld.shared.u16 %0, [%1];" : "=h"(v) : "r"(a) : "memory"); return v; }
__device__ __forceinline__ void unpack8(uint32_t la, uint32_t lb, uint32_t c, uint32_t (&w)[4]) {
    const uint32_t ha = c & 0x87878787u, hb = __funnelshift_l(c, c, 4) & 0x87878787u;
    w[0] = prmt(la, ha, 0x5140); w[1] = prmt(la, ha, 0x7362); w[2] = prmt(lb, hb, 0x5140); w[3] = prmt(lb, hb, 0x7362);
}
__device__ __forceinline__ uint32_t bdiff2(uint32_t y, uint32_t inv, uint32_t x) {
    uint32_t r;
    asm("{\n.reg .b32 n;\nneg.bf16x2 n, %3;\nfma.rn.bf16x2 %0, %1, %2, n;\n}" : "=r"(r) : "r"(y), "r"(inv), "r"(x));
    return r;
}
__device__ __forceinline__ uint32_t pack_scale(uint32_t tile, int lane, uint32_t inv_addr) {
    uint32_t m = 0;
#pragma unroll 1
    for (int k = 0; k < 12; k++) {
        uint32_t a, b, c, d;
        lds128(tile + k * 512 + lane * 16, a, b, c, d);
        asm("max.xorsign.abs.bf16x2 %0, %0, %1;" : "+r"(a) : "r"(b));
        asm("max.xorsign.abs.bf16x2 %0, %0, %1;" : "+r"(c) : "r"(d));
        asm("max.xorsign.abs.bf16x2 %0, %0, %1;" : "+r"(a) : "r"(c));
        asm("max.xorsign.abs.bf16x2 %0, %0, %1;" : "+r"(m) : "r"(a));
    }
    m = __reduce_max_sync(0xffffffffu, max(m & 0x7fffu, (m >> 16) & 0x7fffu));
    const uint32_t inv = (112u + min((m + 0x28u) >> 7, 141u)) * 0x00800080u;
    if (lane == 0) asm volatile("st.shared.u32 [%0], %1;" ::"r"(inv_addr), "r"(inv) : "memory");
    return inv;
}

#define K_OFF(i) ((uint32_t)((3 * ((g >> 1) + 4 * (g & 1)) + ((i) >> 1)) * 128 + ((t ^ ((3 * ((g >> 1) + 4 * (g & 1)) + ((i) >> 1)) & 7) ^ (((i) & 1) << 2)) << 4)))
#define V_OFF(i) ((uint32_t)((6 * t + (i)) * 128 + ((g ^ ((6 * t + (i)) & 7)) << 4)))
template <bool ISV, typename DST>
__device__ __forceinline__ void pack_tile(uint32_t tile, int tau, int nm, uint32_t inv, uint32_t xl, int lane, DST dst) {
    const int g = lane >> 2, t = lane & 3;
    const uint32_t scl = 254u * 0x00800080u - inv;
#pragma unroll 1
    for (int m = 0; m < nm; m++) {
        const int row = ISV ? 6 * t + 2 * m : 3 * ((g >> 1) + 4 * (g & 1)) + m;
        const uint32_t a0 = tile + row * 128 + (((ISV ? g : t) ^ (row & 7)) << 4), a1 = ISV ? (a0 ^ 16) + 128 : a0 ^ 64;
        uint32_t l[8], cw[4], ck = 0, cd = 0;
#pragma unroll
        for (int r = 0; r < 4; r++) {
            uint32_t w0, w1, w2, w3;
            lds128(((r & 1) ? a1 : a0) + (r >> 1) * 3072, w0, w1, w2, w3);
            const uint32_t y0 = bmul2(w0, scl), y1 = bmul2(w1, scl), y2 = bmul2(w2, scl), y3 = bmul2(w3, scl);
            cd |= bdiff2(y0, inv, w0) | bdiff2(y1, inv, w1);
            cd |= bdiff2(y2, inv, w2) | bdiff2(y3, inv, w3);
            const uint32_t ha = prmt(y0, y1, 0x7531), hb = prmt(y2, y3, 0x7531);
            l[2 * r] = prmt(y0, y1, 0x6420); l[2 * r + 1] = prmt(y2, y3, 0x6420);
            asm("lop3.b32 %0, %1, 0x87878787, %2, 0xe2;" : "=r"(cw[r]) : "r"(ha), "r"(__funnelshift_r(hb, hb, 4)));
            ck |= ha | hb;
        }
        const uint32_t bad = __ballot_sync(0xffffffffu, (ck & 0x78787878u) | cd);
        if (bad) {
            const int src = __ffs(bad) - 1;
            const uint32_t b0 = __shfl_sync(0xffffffffu, a0, src), b1 = __shfl_sync(0xffffffffu, a1, src), n0 = lds32(xl);
            const uint32_t ax = ((lane & 8) ? b1 : b0) + (lane >> 4) * 3072 + 2 * (lane & 7), x = lds16(ax), y = bmul2(x, scl);
            const bool out = (y & 0x7800u) | bdiff2(y, inv, x);
            const uint32_t n = n0 + __popc(__ballot_sync(0xffffffffu, out) << (31 - lane)) - 1;
            if (out) {
                asm volatile("st.shared.u16 [%0], %1;" ::"r"(ax), "h"((unsigned short)0) : "memory");
                if (n < XCAP) sts32(xl + 16 + 4 * n, f_(x << 16 | tau << 12 | src << 7 | m << 5 | lane));
            }
            if (lane == 31) sts32(xl, f_(n + 1));
            __syncwarp();
            if (n0 <= XCAP) { m--; continue; }
        }
        uint32_t d[3] = {a0, a1, a0 + 3072};
        dst(m, d);
        sts128(d[0], l[0], l[1], l[2], l[3]);
        sts128(d[1], l[4], l[5], l[6], l[7]);
        sts128(d[2], cw[0], cw[1], cw[2], cw[3]);
    }
}

struct Maps { CUtensorMap k, v, wq, wo, w1, w3, w2, vr; const void* vp; const void* kp; uint32_t zero; };
#define RT_SEL ((wu & 1) ? RT_MASK2 : RT_MASK)
#define PFK 5
#define Q_AT 3
#define WO_T0 33200
#define K5D 250
#define PK_AT 6

__device__ __forceinline__ void load_ffn(const Maps& maps, int b, uint32_t dst, uint32_t bar) {
    const bool gu = b < NG;
    mbar_expect_tx(bar, gu ? 61440 : 49152);
    tma3d(dst, gu ? (b < NG / 2 ? &maps.w1 : &maps.w3) : &maps.w2, gu ? 48 * (b & (NG / 2 - 1)) : 16 * (b - DN0), 0, 0, bar, FFN_POL);
}

__device__ __forceinline__ void load_wo(const Maps& maps, uint32_t dst, int h, int c, uint32_t bar, int nbox) {
#pragma unroll 1
    for (int i = 0; i < nbox; i++) {
        if (!(i & 1)) mbar_expect_tx(bar + 4 * i, i + 1 < nbox ? 20480 : 10240);
        tma3d(dst + i * 10240, &maps.wo, 0, 5 * c, h * DH + 32 * i, bar + 4 * (i & 6), POL_EF);
    }
}

__global__ void __launch_bounds__(NT, 1)
decode_kernel(const __grid_constant__ Maps maps, const __nv_bfloat16* __restrict__ x_in, __nv_bfloat16* __restrict__ out) {
    extern __shared__ __align__(1024) unsigned char smem[];
    const int tid = threadIdx.x, warp = tid >> 5, lane = tid & 31;
    const int wu = __shfl_sync(0xffffffffu, tid >> 5, 0);
    const int b = blockIdx.x, h = b >> 2, c = b & 3;
    const uint32_t sb = smem_u32(smem);
    const uint32_t qbar = sb + SM_BAR + 16 * 8, fbar = qbar + 8, wbar = qbar + 16;
    uint32_t* xs32 = reinterpret_cast<uint32_t*>(smem + SM_XS);
    float* rr = reinterpret_cast<float*>(smem + SM_R);
    float* misc = reinterpret_cast<float*>(smem + SM_MISC);

    PROF_T(0);
    {
        uint2 xv = make_uint2(0u, 0u);
        const uint32_t t_start = now_ns();
        if (elect_one()) {
            const uint32_t rb = sb + SM_BAR + wu * 16, xb = sb + SM_XBAR + wu * 8;
            mbar_init(rb, 1); mbar_init(rb + 8, 1); mbar_init(xb, 1);
            if (wu == 0) mbar_init(qbar, 1);
            asm volatile("fence.mbarrier_init.release.cluster;" ::: "memory");
            const int row = (h * SK + (SK - WIN) + c * 1024 + wu * 128) * 3;
            const uint32_t ring = sb + SM_RING + wu * 2 * TILE;
#pragma unroll
            for (int n = 0; n < 3; n++) {
                const uint32_t bar = ((IN_S1 >> n) & 1) ? rb + 8 : ((IN_S0 >> n) & 1) ? rb : xb;
                mbar_expect_tx(bar, TILE);
                tma2d(((IN_S1 >> n) & 1) ? ring + TILE : ((IN_S0 >> n) & 1) ? ring : sb + SM_B + wu * TILE, &maps.k, 0, row + 48 * n, bar, POL_EF);
                if (n == 0 && wu == 0) {
                    mbar_expect_tx(qbar, 61440);
                    tma3d(sb + SM_Q, &maps.wq, 0, 160 * c, 3 * h, qbar, POL_EF);
                }
            }
            if (wu == 1) {
                mbar_init(fbar, 1);
#pragma unroll
                for (int i = 0; i < 3; i++) mbar_init(wbar + 8 * i, 1);
                asm volatile("fence.mbarrier_init.release.cluster;" ::: "memory");
            }
            if (wu >= 2) {
                const CUtensorMap* mp = wu == 2 ? &maps.v : wu == 3 ? &maps.wo : wu == 4 ? &maps.w1 : wu == 5 ? &maps.w3 : wu == 6 ? &maps.w2 : &maps.vr;
                asm volatile("prefetch.tensormap [%0];" ::"l"(mp) : "memory");
            }
        }
        if (tid < 160) asm volatile("ld.global.nc.v2.u32 {%0,%1}, [%2];" : "=r"(xv.x), "=r"(xv.y) : "l"(x_in + 4 * tid) : "memory");
        if (tid == 96) { misc[2] = 0.f; misc[3] = 0.f; }
        if (lane == 1) *reinterpret_cast<uint2*>(smem + SM_XL + warp * XSTR) = make_uint2(0u, t_start + WO_T0);
        if (tid >= 128 && tid < 148) {
            const uint32_t v = tid < 138 ? ONES : 0u;
            reinterpret_cast<uint4*>(smem + SM_ONE)[tid - 128] = make_uint4(v, v, v, v);
        }
        if (tid < 160) { xs32[xpos(2 * tid)] = xv.x; xs32[xpos(2 * tid + 1)] = xv.y; }
        __syncthreads();
        PROF_T(14);
        if (b == 0 && tid >= 232) asm volatile("st.relaxed.gpu.global.u32 [%0], %1;" ::"l"(g_scr.ticket + tid - 232), "r"(0) : "memory");
        if (tid == 64 || (tid == 65 && b < 216 - NCTA)) st_pkt(&g_scr.acc[1][(b + NCTA * (tid - 64)) * ACC_STR], 0, 0, 0, 0);
    }

    uint32_t kq[NQ][4];
    const float SC = 0.07216878364870322f * 1.4426950408889634f;

#pragma unroll 1
    for (int ph = 0; ph < 3; ph++) {
        const int layer = ph >> 1;
        const uint32_t tag = layer + 1;
        PROF_T(1 + layer * 16);
        if (ph) {
        {
            const int tl = opq(tid), warp = tl >> 5, lane = tl & 31, g = lane >> 2, t = lane & 3, mat = lane >> 3, r8 = lane & 7;
            const int kh = warp >> 2, mg = warp & 3;
            uint32_t aq[3];
#pragma unroll
            for (int i = 0; i < 3; i++) {
                const int ch = 6 * mg + 2 * i + (mat & 1);
                aq[i] = sb + SM_Q + (80 * kh + (mat >> 1) * 8 + r8) * 128 + (ch >> 3) * 20480 + (((ch & 7) ^ r8) << 4);
            }
#define PF_K5 if (layer == 1 && PFK) tile_keep(&maps.k, (h * SK + (SK - WIN) + c * 1024 + wu * 128 + PFK * 16) * 3);
            uint2 xv = make_uint2(0u, 0u);
            mbar_wait(qbar, 0);
            uint32_t pre[6][4];
#pragma unroll
            for (int n = 0; n < 6; n++) ldsm4t(aq[n % 3] + (n / 3) * 2048, pre[n]);
            if (layer == 1) {
                __syncthreads();
                if (elect_one()) {
                    const uint32_t bar = sb + SM_BAR + wu * 16;
                    asm volatile("mbarrier.expect_tx.relaxed.cta.shared::cta.b64 [%0], 1536;" ::"r"(bar) : "memory");
#pragma unroll
                    for (int k = 0; k < 3; k++)
                        tma2d(sb + SM_Q + v1_pos(3 * wu + k), &maps.vr, 0, (h * SK + (SK - WIN) + c * 1024 + wu * 128) / 2 + 8 + 2 * k, bar, POL_EF);
                }
            }
            const uint32_t pm = opq(g == 1 ? sb + SM_ONE : sb + SM_XS + 160 * (2 * c + kh) + 16 * t), pm2 = opq(pm + 128 - (g == 1 ? 0 : 8 * t));
            const uint32_t dq = opq(sb + SM_R + 8 * (kh * 192 + 48 * mg + g)), ds = opq(sb + SM_ST + 8 * warp + (lane < 16 ? 4 : 0));
            const bool wr = t == 0, ws = (lane & 15) == 0, lo = lane < 16;
            if (wu < 5) {
                const int p0 = xpos(2 * tl), p1 = xpos(2 * tl + 1);
                if (layer == 1) {
                    uint4 v;
                    for (int it = 0; it < SPIN_CAP; it++) { v = ld_pkt(&g_scr.ay[tl]); if (__all_sync(0xffffffffu, v.w == 1)) break; }
                    xv = make_uint2(v.x, v.y);
                    xs32[p0] = xv.x; xs32[p1] = xv.y;
                } else xv = make_uint2(xs32[p0], xs32[p1]);
            }
            if (layer) PC(24);
            __syncthreads();
            PF_K5
            if (layer) PC(25);
            PROF_T(13 + layer * 16);
            const float e0 = bf_lo(xv.x), e1 = bf_hi(xv.x), e2 = bf_lo(xv.y), e3 = bf_hi(xv.y);
            const float s1 = (e0 + e1) + (e2 + e3), s2 = (e0 * e0 + e1 * e1) + (e2 * e2 + e3 * e3);
            float sv = lo ? s1 : s2, cc[3][4];
            gemv15<2048>(cc, pre, [&](int i) { return aq[i]; }, pm, pm2, sv, lo ? s2 : s1);
            if (wr) {
#pragma unroll
                for (int i = 0; i < 3; i++) { sts64(dq + 128 * i, cc[i][0], cc[i][1]); sts64(dq + 128 * i + 64, cc[i][2], cc[i][3]); }
            }
            if (ws) sts32(ds, sv);
        }
        const uint32_t pa = opq(sb + SM_R + 32 * opq(tid)), st = opq(sb + SM_ST);
        uint4* const pq = opq(&g_scr.hx[b * 48 + opq(tid)]);
        if (layer) PC(26);
        __syncthreads();
        if (layer) PC(27);
        PROF_T(33 + layer * 16);
        if (wu < 2) {
            float mean, inv;
            ln_stats(st, mean, inv);
            const float4 a0 = lds4f(pa), a1 = lds4f(pa + 16), b0 = lds4f(pa + 1536), b1 = lds4f(pa + 1552);
            const float q0 = (a0.x + b0.x) - mean * (a0.y + b0.y), q1 = (a0.z + b0.z) - mean * (a0.w + b0.w);
            const float q2 = (a1.x + b1.x) - mean * (a1.y + b1.y), q3 = (a1.z + b1.z) - mean * (a1.w + b1.w);
            st_pktfp(pq, q0, q1, q2, q3, 1, tid < 48);
        }
        if (layer == 1 && tid >= 192 && tid < 194 && b < 108) st_pkt(&g_scr.acc[0][(2 * b + opq(tid) - 192) * ACC_STR], 0, 0, 0, 0);
        }
        if (layer) PC(28);
        if (layer == 1 && (wu & 2)) {
            idle(K5D);
            tile_load(sb + SM_Q + c_slot(wu), &maps.k, (h * SK + (SK - WIN) + c * 1024 + wu * 128 + 5 * 16) * 3, sb + SM_XBAR + wu * 8, 0, 0);
        }

        float sc0 = -INFINITY, sc1 = -INFINITY, sc2 = 0.f, sc3 = 0.f, mw;
        uint32_t pk0, pk1;
        float acc[3][4];
        {
            const uint32_t ring = sb + SM_RING + wu * 2 * TILE, rb = sb + SM_BAR + wu * 16;
            const uint32_t xtile = sb + SM_Q + c_slot(wu), xb = sb + SM_XBAR + wu * 8;
#define V_SEQ(n) ((int)(SEQ1 >> (4 * (n))) & 7)
#define SLOT1(n) (((IN_S1 >> (n)) & 1) ? ring + TILE : ((IN_S0 >> (n)) & 1) ? ring : sb + SM_B + wu * TILE)
#define BAR1(n) (((IN_S1 >> (n)) & 1) ? rb + 8 : ((IN_S0 >> (n)) & 1) ? rb : xb)
#define PAR1(n) ((PARITY1 >> (n)) & 1)
#define PAR2(n) ((PARITY2 >> (n)) & 1)
            const int row0 = (h * SK + (SK - WIN) + c * 1024 + wu * 128) * 3;
            auto issue1 = [&](int n, uint32_t dep, bool vph = false) {
                const CUtensorMap* mp = n < 8 ? &maps.k : &maps.v;
                const int tl = V_SEQ(n), row = row0 + tl * 48;
                const uint32_t dst = SLOT1(n), bar = BAR1(n);
                if (vph && wu < L1R && tl == 7 - (wu & 1)) {
                    tile_load_l1(dst, maps.vp, row, bar, opq(tid) & 31);
                    return;
                }
                tile_load(dst, mp, row, bar, dep, maps.zero);
                if ((RT_SEL >> (tl + (n & 8))) & 1) {
                    if (n != V0_AT + 1) tile_keep(mp, row);
                    else if ((opq(tid) & 31) < 8)
                        asm volatile("cp.async.bulk.prefetch.L2.global.L2::cache_hint [%0], 256, %1;"
                                     ::"l"(static_cast<const char*>(maps.vp) + (size_t)(row + 4 + 6 * (opq(tid) & 31)) * 128), "l"(POL_EN) : "memory");
                }
            };
            auto refill1 = [&](int s, uint32_t dep, bool vph = false) { issue1(s + (!vph || s < V0_AT ? 3 : 2), dep, vph); };
#define LANE_IDS const int tl = opq(tid), lane = tl & 31, g = lane >> 2, t = lane & 3; (void)tl; (void)lane; (void)g; (void)t;
            const uint32_t xl = sb + SM_XL + wu * XSTR;
            if (layer == 0) {
#pragma unroll 1
                for (int s = ph ? Q_AT : 0; s < (ph ? 5 : Q_AT); s++) {
                    LANE_IDS
                    const uint32_t tile = SLOT1(s);
                    mbar_wait(BAR1(s), PAR1(s));
                    const uint32_t scl = s == 0 ? pack_scale(tile, lane, xl + 8) : lds32(xl + 8);
                    pack_tile<false>(tile, s, 3, scl, xl, lane, [](int, uint32_t (&)[3]) {});
#pragma unroll
                    for (int n = 0; n < 5; n++) {
                        if (s == n) {
#pragma unroll
                            for (int m = 0; m < 3; m++) {
                                const uint32_t a = tile + K_OFF(2 * m);
                                lds128(a, kq[9 * n + 3 * m][0], kq[9 * n + 3 * m][1], kq[9 * n + 3 * m][2], kq[9 * n + 3 * m][3]);
                                lds128(a ^ 64, kq[9 * n + 3 * m + 1][0], kq[9 * n + 3 * m + 1][1], kq[9 * n + 3 * m + 1][2], kq[9 * n + 3 * m + 1][3]);
                                lds128(a + 3072, kq[9 * n + 3 * m + 2][0], kq[9 * n + 3 * m + 2][1], kq[9 * n + 3 * m + 2][2], kq[9 * n + 3 * m + 2][3]);
                            }
                        }
                    }
                    __syncwarp();
                    refill1(s, lds32(tile));
                }
                if (!ph) continue;
            }
            {
                if (wu < 2) {
                    const int tl = min(opq(tid), 47);
                    const int w = 2 * tl;
                    const uint32_t pos = opq(sb + SM_QS + 4 * (((w >> 2) & 3) * 24 + 2 * (w >> 4) + ((w >> 1) & 1)));
                    uint4 v[4];
                    float mean, inv;
                    ln_stats(opq(sb + SM_ST), mean, inv);
                    for (int it = 0; it < SPIN_CAP; it++) {
#pragma unroll
                        for (int k = 0; k < 4; k++) v[k] = ld_pkt(&g_scr.hx[(h * 4 + k) * 48 + tl]);
                        if (all_odd(v[0].w, v[1].w, v[2].w, v[3].w)) break;
                    }
                    sts32(pos, f_(pack2(inv * ((f_(v[0].x) + f_(v[1].x)) + (f_(v[2].x) + f_(v[3].x))), inv * ((f_(v[0].y) + f_(v[1].y)) + (f_(v[2].y) + f_(v[3].y))))));
                    sts32(pos + 48, f_(pack2(inv * ((f_(v[0].z) + f_(v[1].z)) + (f_(v[2].z) + f_(v[3].z))), inv * ((f_(v[0].w) + f_(v[1].w)) + (f_(v[2].w) + f_(v[3].w))))));
                }
            }
            if (layer) PC(29);
            __syncthreads();
            if (layer) PC(30);
            PROF_T(2 + layer * 16);
#define V1_REST(p) ((p) < 6 ? sb + SM_Q + v1_pos(3 * wu + ((p) >> 1)) + 256 * ((p) & 1) : ((sb + SM_R + wu * 784 + 127) & ~127u) - 1536 + 256 * (p))
#define V1_LOAD(bar) if (elect_one()) tma2d(V1_REST(6), &maps.vr, 0, row0 / 6 + 14, bar, POL_EF);
#define V1_EXPECT(bar) { if ((opq(tid) & 31) == 0) asm volatile("mbarrier.expect_tx.relaxed.cta.shared::cta.b64 [%0], 512;" ::"r"(bar) : "memory"); }
            if (layer == 1 && !(wu & 2)) tile_load(xtile, &maps.k, row0 + 5 * 48, xb, 0, 0);
            if (layer == 1 && wu >= 4) idle(STAG);
            {
                uint32_t qf[12];
                int t;
                {
                    const int lane = opq(tid) & 31;
                    t = lane & 3;
                    const uint32_t qa = sb + SM_QS + (2 * t + ((lane >> 2) & 1)) * 48;
#pragma unroll
                    for (int i = 0; i < 3; i++) lds128(qa + 16 * i, qf[4 * i], qf[4 * i + 1], qf[4 * i + 2], qf[4 * i + 3]);
                }
                const uint32_t sq = lds32(xl + 8) - 64u * 0x00800080u;
#pragma unroll
                for (int i = 0; i < 12; i++) qf[i] = bmul2(qf[i], sq);
#define KR_STEP(tau, m) \
                    _Pragma("unroll") for (int i = 2 * (m); i < 2 * (m) + 2; i++) { \
                        const int q0 = 9 * tau + 3 * (i >> 1), r = i & 1; \
                        uint32_t w[4]; \
                        unpack8(kq[q0][2 * r], kq[q0][2 * r + 1], kq[q0 + 2][r], w); \
                        mma16816(cA, w[0], w[1], w[2], w[3], qf[2 * i], qf[2 * i + 1]); \
                        unpack8(kq[q0 + 1][2 * r], kq[q0 + 1][2 * r + 1], kq[q0 + 2][2 + r], w); \
                        mma16816(cB, w[0], w[1], w[2], w[3], qf[2 * i], qf[2 * i + 1]); \
                    }
#define KR_BEGIN float cA[4] = {0.f, 0.f, 0.f, 0.f}, cB[4] = {0.f, 0.f, 0.f, 0.f};
#define KR_END(tau) \
                    const float sA = (cA[0] + cA[3]) * 18446744073709551616.f, sB = (cB[0] + cB[3]) * 18446744073709551616.f; \
                    if (t == (tau & 3)) { if (tau < 4) { sc0 = sA; sc1 = sB; } else { sc2 = sA; sc3 = sB; } }
#define KR_SCORES(tau) { KR_BEGIN KR_STEP(tau, 0) KR_STEP(tau, 1) KR_STEP(tau, 2) KR_END(tau) }
                uint32_t va[3];
                {
                    const int lane = opq(tid) & 31, g = lane >> 2, t = lane & 3;
#pragma unroll
                    for (int i = 0; i < 3; i++) va[i] = ring + V_OFF(2 * i);
                }
#define V_STG(n) _Pragma("unroll") for (int j = 3 * (n); j < 3 * (n) + 3; j++) { \
                    const int i = (j % 12) >> 1; \
                    lds128p(((i & 1) ? (va[i >> 1] ^ 16) + 128 : va[i >> 1]) + (j / 12) * TILE + (j & 1) * 3072, layer, kq[j][0], kq[j][1], kq[j][2], kq[j][3]); }
                uint32_t dep = 0;
                {
                    KR_BEGIN
                    KR_STEP(0, 0) V_STG(0) KR_STEP(0, 1) V_STG(1) KR_STEP(0, 2) V_STG(2)
                    KR_END(0)
                }
                {
                    KR_BEGIN
                    KR_STEP(1, 0) V_STG(3)
                    __syncwarp();
                    dep = lds32(ring);
                    if (layer == 1) tile_load(ring, &maps.k, row0 + 6 * 48, rb, dep, maps.zero);
                    KR_STEP(1, 1) V_STG(4) KR_STEP(1, 2) V_STG(5)
                    KR_END(1)
                }
                {
                    KR_BEGIN
                    KR_STEP(2, 0) V_STG(6) KR_STEP(2, 1) V_STG(7)
                    __syncwarp();
                    dep = lds32(ring + TILE);
                    KR_STEP(2, 2)
                    if (layer == 1) {
                        V1_EXPECT(rb + 8)
                        tile_load(ring + TILE, &maps.k, row0 + 7 * 48, rb + 8, dep, maps.zero);
                        V1_LOAD(rb + 8)
                    }
                    KR_END(2)
                }
#pragma unroll 1
                for (int s = 5; s < 8; s++) {
                    {
                        LANE_IDS
                        const uint32_t tile = !layer ? SLOT1(s) : s == 5 ? xtile : ring + (s - 6) * TILE, tb = !layer ? BAR1(s) : s == 5 ? xb : rb + (s - 6) * 8;
                        const float ur = f_((318u << 23) - (lds32(xl + 8) << 16));
                        mbar_wait(tb, layer ? PAR2(s - 5) : PAR1(s));
                        if (layer) PROF_T(29 + s);
                        float cA[4] = {0.f, 0.f, 0.f, 0.f}, cB[4] = {0.f, 0.f, 0.f, 0.f};
#pragma unroll
                        for (int i = 0; i < 6; i++) {
                            uint32_t a0, a1, a2, a3;
                            lds128(tile + K_OFF(i), a0, a1, a2, a3);
                            mma16816(cA, a0, a1, a2, a3, qf[2 * i], qf[2 * i + 1]);
                            lds128(tile + K_OFF(i) + 3072, a0, a1, a2, a3);
                            mma16816(cB, a0, a1, a2, a3, qf[2 * i], qf[2 * i + 1]);
                        }
                        __syncwarp();
                        const uint32_t last = lds32(tile);
                        if (layer) tile_load(tile, &maps.v, row0 + (s - 2) * 48, tb, last, maps.zero);
                        else refill1(s, last);
                        if (t == (s & 3)) { sc2 = (cA[0] + cA[3]) * ur; sc3 = (cB[0] + cB[3]) * ur; }
                    }
                    if (s == 5) KR_SCORES(3)
                    if (s == 6) {
                        KR_SCORES(4)
                        const int lane = opq(tid) & 31;
                        const uint32_t nx = min(lds32(xl), (uint32_t)XCAP);
#pragma unroll 1
                        for (uint32_t n = 0; n < nx; n++) {
                            const uint32_t id = lds32(xl + 16 + 4 * n);
                            const uint32_t qo = 96 * ((id >> 7) & 3) + 48 * ((id >> 1) & 1) + 16 * ((id >> 5) & 3) + (id & 12) + 2 * (id & 1);
                            const float cr = bf_hi(id) * f_(lds16(sb + SM_QS + qo) << 16);
                            const int d = (int)(16 * ((id >> 9) & 7) + 4 * ((id >> 12) & 3) + ((id >> 13) & 2) + ((id >> 4) & 1) + ((id >> 8) & 128)) - 4 * lane;
                            if (d == 0) sc0 += cr;
                            if (d == 1) sc1 += cr;
                            if (d == 2) sc2 += cr;
                            if (d == 3) sc3 += cr;
                        }
                    }
                }
#undef KR_SCORES
#undef KR_STEP
#undef KR_BEGIN
#undef KR_END
#undef V_STG
                {
                    LANE_IDS
                    if (lds32(xl) > XCAP || !__all_sync(0xffffffffu, (fabsf(sc0) + fabsf(sc1)) + (fabsf(sc2) + fabsf(sc3)) < INFINITY)) {
                        const uint32_t qa = sb + SM_QS + (2 * t + (g & 1)) * 48;
#pragma unroll
                        for (int i = 0; i < 3; i++) lds128(qa + 16 * i, qf[4 * i], qf[4 * i + 1], qf[4 * i + 2], qf[4 * i + 3]);
                        const uint4* kg = reinterpret_cast<const uint4*>(static_cast<const char*>(maps.kp) + (size_t)row0 * 128) + ((g >> 1) + 4 * (g & 1)) * 24 + t;
#pragma unroll 1
                        for (int s = 0; s < 8; s++) {
                            float cA[4] = {0.f, 0.f, 0.f, 0.f}, cB[4] = {0.f, 0.f, 0.f, 0.f};
#pragma unroll
                            for (int i = 0; i < 6; i++) {
                                uint4 u = ldg128(kg + s * 384 + 4 * i);
                                mma16816v(cA, u.x, u.y, u.z, u.w, qf[2 * i], qf[2 * i + 1]);
                                u = ldg128(kg + s * 384 + 4 * i + 192);
                                mma16816v(cB, u.x, u.y, u.z, u.w, qf[2 * i], qf[2 * i + 1]);
                            }
                            if (t == s) { sc0 = cA[0] + cA[3]; sc1 = cB[0] + cB[3]; }
                            if (t + 4 == s) { sc2 = cA[0] + cA[3]; sc3 = cB[0] + cB[3]; }
                        }
                    }
                }
            }
            mw = warp_max(fmaxf(fmaxf(sc0, sc1), fmaxf(sc2, sc3)));
            pk0 = pack2(ex2((sc0 - mw) * SC), ex2((sc1 - mw) * SC));
            pk1 = pack2(ex2((sc2 - mw) * SC), ex2((sc3 - mw) * SC));
            sc2 = (bf_lo(pk0) + bf_hi(pk0)) + (bf_lo(pk1) + bf_hi(pk1));
            sc2 = (float)__reduce_add_sync(0xffffffffu, __float2uint_rn(sc2 * 16777216.f)) * (1.0f / 16777216.f);
            if ((opq(tid) & 31) == 0) st_pkt2(&g_scr.mx[h * 32 + c * 8 + wu], __float_as_uint(mw), (__float_as_uint(sc2) & ~3u) | tag);
            auto head_factor = [&]() {
                const int lane = opq(tid) & 31;
                int it = 0;
                while (!__all_sync(0xffffffffu, (__float_as_uint(sc1) & 3u) == tag) && ++it < SPIN_CAP) {
                    const uint2 mv = ld_pkt2(&g_scr.mx[h * 32 + lane]); sc0 = f_(mv.x); sc1 = f_(mv.y);
                }
                const float e = ex2((sc0 - warp_max(sc0)) * SC);
                const uint32_t d = __reduce_add_sync(0xffffffffu, __float2uint_rn(sc1 * e * 524288.f));
                sc3 = __shfl_sync(0xffffffffu, e, c * 8 + wu) * 524288.f * rcp((float)d);
            };
#pragma unroll
            for (int s = 0; s < 3; s++) { acc[s][0] = acc[s][1] = acc[s][2] = acc[s][3] = 0.f; }
#define P_CONSTS \
                const uint32_t sel0 = g == 0 ? 0x4410u : (g == 1 ? 0x1044u : 0x4444u); \
                const uint32_t sel1 = g == 2 ? 0x4410u : (g == 3 ? 0x1044u : 0x4444u); \
                const int src00 = 4 * (t < 2 ? 4 * t : 4 * (t - 2) + 1);
#define P_FRAGS(tau) \
                const uint32_t pk = ((tau) & 4) ? pk1 : pk0; \
                const uint32_t w0 = __shfl_sync(0xffffffffu, pk, src00 + ((tau) & 3)); \
                const uint32_t w1 = __shfl_sync(0xffffffffu, pk, src00 + ((tau) & 3) + 8); \
                uint32_t pb[4][2]; \
                _Pragma("unroll") for (int j = 0; j < 4; j++) { \
                    const uint32_t src = ((j & 1) ? w1 : w0) >> ((j >> 1) * 16); \
                    pb[j][0] = __byte_perm(src, 0, sel0); pb[j][1] = __byte_perm(src, 0, sel1); \
                }
            if (layer == 0) {
#pragma unroll 1
                for (int s = 8; s < 16; s++) {
                    LANE_IDS
                    P_CONSTS
                    if (s == 13) { const uint2 mv = ld_pkt2(&g_scr.mx[h * 32 + lane]); sc0 = f_(mv.x); sc1 = f_(mv.y); }
                    P_FRAGS(V_SEQ(s))
                    mbar_wait(BAR1(s), PAR1(s));
                    const uint32_t tile = SLOT1(s);
#pragma unroll
                    for (int j = 0; j < 4; j++) {
#pragma unroll
                        for (int u = 0; u < 3; u++) {
                            uint32_t a0, a1, a2, a3;
                            lds128(tile + (j >> 1) * 3072 + V_OFF(3 * (j & 1) + u), a0, a1, a2, a3);
                            mma16816(acc[u], a0, a1, a2, a3, pb[j][0], pb[j][1]);

                        }
                    }
                    __syncwarp();
                    if (s < V0_AT || (s > V0_AT + 1 && s < 14)) refill1(s, lds32(tile), true);
                    if (s == V0_AT || s == V0_AT + 1) {
                        {
                            const uint32_t ar = sb + SM_R + wu * 784 + 32 * g + 16 * t;
                            if (t < 2) {
#pragma unroll
                                for (int u = 0; u < 3; u++) sts128(ar + 256 * u, __float_as_uint(acc[u][0]), __float_as_uint(acc[u][1]), __float_as_uint(acc[u][2]), __float_as_uint(acc[u][3]));
                            }
                        }
                        const uint32_t scl = s == V0_AT ? pack_scale(tile, lane, xl + 12) : lds32(xl + 12);
                        pack_tile<true>(tile, s + 8 - V0_AT, V0_AT + 3 - s, scl, xl, lane, [&](int m, uint32_t (&d)[3]) {
                            if (s != V0_AT && m == 0) {
#pragma unroll
                                for (int k = 0; k < 3; k++) d[k] = ring + 3072 + V_OFF(2 * k + 1);
                            }
                        });
                        if (s != V0_AT) {
                            lds128(tile + V_OFF(2), kq[45][0], kq[45][1], kq[45][2], kq[45][3]);
                            lds128(tile + V_OFF(3), kq[46][0], kq[46][1], kq[46][2], kq[46][3]);
                            lds128(tile + V_OFF(2) + 3072, kq[47][0], kq[47][1], kq[47][2], kq[47][3]);
                            __syncwarp();
                            issue1(V0_AT + 3, lds32(tile));
                        }
                        const int ln = opq(tid) & 31;
                        const uint32_t ar = sb + SM_R + wu * 784 + 8 * (ln & 28) + 16 * (ln & 1);
#pragma unroll
                        for (int u = 0; u < 3; u++) {
                            uint32_t a0, a1, a2, a3;
                            lds128(ar + 256 * u, a0, a1, a2, a3);
                            acc[u][0] = f_(a0); acc[u][1] = f_(a1); acc[u][2] = f_(a2); acc[u][3] = f_(a3);
                        }
                    }
                    if (s == 13) head_factor();
                    if (s >= 14 && elect_one()) {
                        if (atomicAdd(reinterpret_cast<unsigned*>(misc + 3), 1u) == 14u && (int)(now_ns() - lds32(xl + 4)) >= 0) {
                            PROF_X(47);
                            load_wo(maps, sb + SM_B, h, c, wbar, 6);
                            atomicAdd(reinterpret_cast<unsigned*>(misc + 3), 256u);
                        }
                    }
                }
            } else {
                LANE_IDS
                P_CONSTS
#pragma unroll
                for (int k = 0; k < 4; k++) lds128(V1_REST(t + 4 * (k >> 1)) + 16 * g + 128 * (k & 1), kq[36 + k][0], kq[36 + k][1], kq[36 + k][2], kq[36 + k][3]);
#pragma unroll 1
                for (int i = 3; i < 8; i++) {
                    const uint32_t tile = i > 3 ? ring + (i & 1) * TILE : xtile, tb = i > 3 ? rb + (i & 1) * 8 : xb;
                    if (i == 6) { const uint2 mv = ld_pkt2(&g_scr.mx[h * 32 + lane]); sc0 = f_(mv.x); sc1 = f_(mv.y); }
                    if (i == 7) head_factor();
                    if (i == PK_AT) {
                uint32_t nx, nk, ik, iv;
                lds128(xl, nx, nk, ik, iv);
                if (nx <= XCAP) {
                    const uint32_t pks = bmul2(pk0, iv);
#pragma unroll
                    for (int s = 0; s < 2; s++) {
                        const uint32_t pk1 = 0, pk0 = pks;
                        P_FRAGS(s)
#pragma unroll
                        for (int j = 0; j < 4; j++) {
#pragma unroll
                            for (int u = 0; u < 3; u++) {
                                const int i = 3 * (j & 1) + u, m = i >> 1, r = i & 1, hf = j >> 1;
                                if (s == 1 && m == 2) continue;
                                const int ql = s == 0 ? 4 * m + 2 * hf : m == 0 ? 3 + 4 * hf : 45 + hf, qc = s == 0 ? 4 * m + 1 : m == 0 ? 11 : 47;
                                uint32_t w[4];
                                unpack8(kq[ql][2 * r], kq[ql][2 * r + 1], kq[qc][2 * hf + r], w);
                                mma16816(acc[u], w[0], w[1], w[2], w[3], pb[j][0], pb[j][1]);
                            }
                        }
                    }
#pragma unroll 1
                    for (uint32_t n = 0; n < nx; n++) {
                        const uint32_t id = lds32(xl + 16 + 4 * n);
                        const int i = ((id >> 4) & 6) + ((id >> 3) & 1), key = ((id >> 6) & 6) + (i >= 3);
                        const uint32_t pw = __shfl_sync(0xffffffffu, pk0, 8 * (key & 3) + (key & 4) + ((id >> 12) & 3));
                        const float cr = bf_hi(id) * ((id & 16) ? bf_hi(pw) : bf_lo(pw));
                        const int d = (int)(64 * ((id >> 9) & 7) + 4 * (id & 4) + 4 * (i >= 3 ? i - 3 : i) + (id & 3) + ((~id >> 5) & 1024)) - 16 * lane;
#pragma unroll
                        for (int k = 0; k < 12; k++) if (d == k) acc[k >> 2][k & 3] += cr;
                    }
                } else {
                    const uint4* vg = reinterpret_cast<const uint4*>(static_cast<const char*>(maps.vp) + (size_t)row0 * 128) + 48 * t + g;
#pragma unroll 1
                    for (int s = 0; s < 2; s++) {
                        P_FRAGS(s)
#pragma unroll
                        for (int j = 0; j < 4; j++) {
#pragma unroll
                            for (int u = 0; u < 3; u++) {
                                if (s == 1 && (j & 1) && u) continue;
                                const uint4 w = ldg128(vg + 384 * s + 192 * (j >> 1) + 24 * (j & 1) + 8 * u);
                                mma16816v(acc[u], w.x, w.y, w.z, w.w, pb[j][0], pb[j][1]);
                            }
                        }
                    }
                }
#pragma unroll
                for (int s = 2; s > 0; s--) {
                    P_FRAGS(s)
#pragma unroll
                    for (int j = 0; j < 4; j++) {
#pragma unroll
                        for (int u = 0; u < 3; u++) {
                            if (s == 1 && !((j & 1) && u)) continue;
                            const int k = s == 2 ? 12 + 2 * (3 * (j & 1) + u) + (j >> 1) : 35 + (j >> 1) * 2 + u;
                            mma16816(acc[u], kq[k][0], kq[k][1], kq[k][2], kq[k][3], pb[j][0], pb[j][1]);
                        }
                    }
                }
                    }
                    P_FRAGS(i)
                    mbar_wait(tb, PAR2(i));
                    PROF_T(34 + i);
#pragma unroll
                    for (int k = 0; k < 6; k++) {
                        const uint32_t a = tile + V_OFF(k);
                        lds128(a, kq[24 + k][0], kq[24 + k][1], kq[24 + k][2], kq[24 + k][3]);
                        lds128(a + 3072, kq[30 + k][0], kq[30 + k][1], kq[30 + k][2], kq[30 + k][3]);
                    }
#pragma unroll
                    for (int j = 0; j < 4; j++) {
#pragma unroll
                        for (int u = 0; u < 3; u++) {
                            const int k = 24 + 6 * (j >> 1) + 3 * (j & 1) + u;
                            mma16816(acc[u], kq[k][0], kq[k][1], kq[k][2], kq[k][3], pb[j][0], pb[j][1]);
                        }
                    }
                    __syncwarp();
                    if (wu < L1R && i == 5 - (wu & 1)) tile_load_l1(tile, maps.vp, row0 + (i + 2) * 48, tb, lane);
                    else if (i == 4 || i == 5) tile_load(tile, &maps.v, row0 + (i + 2) * 48, tb, lds32(tile), maps.zero);
                    if (i == WO_AT1 && HAS_FFN && elect_one()) {
                        if (atomicAdd(reinterpret_cast<unsigned*>(misc + 2), 1u) == 7u) {
                            PROF_X(63);
                            load_wo(maps, sb + SM_Q, h, c, wbar, KEEP4 && __float_as_uint(misc[1]) >= DN0 ? 5 : 6);
                        }
                    }
                }
            }
#undef P_FRAGS
#undef P_CONSTS
#undef LANE_IDS
        }
        PROF_T(3 + layer * 16);
        PC(layer * 32 + 1);

        {
            const int lane = opq(tid) & 31;
            const uint32_t a = sb + SM_R + wu * 784 + 8 * (lane & 28) + 16 * (lane & 1);
#pragma unroll
            for (int u = 0; u < 3; u++) sts128p(a + 256 * u, acc[u][0] * sc3, acc[u][1] * sc3, acc[u][2] * sc3, acc[u][3] * sc3, lane & 2);
        }
        const uint32_t role1 = layer ? lds32(sb + SM_MISC + 4) : DN0 + NDN;
        const uint32_t pc = opq(sb + SM_R + 16 * opq(tid));
        uint4* const px0 = opq(&g_scr.hx[b * 48 + opq(tid)]);
        __syncthreads();
        PROF_T(4 + layer * 16);
        PC(layer * 32 + 2);
        float4 o = make_float4(0.f, 0.f, 0.f, 0.f);
        if (wu < 2) {
            float4 v[8];
#pragma unroll
            for (int w = 0; w < 8; w++) v[w] = lds4f(pc + w * 784);
            o.x = ((v[0].x + v[1].x) + (v[2].x + v[3].x)) + ((v[4].x + v[5].x) + (v[6].x + v[7].x));
            o.y = ((v[0].y + v[1].y) + (v[2].y + v[3].y)) + ((v[4].y + v[5].y) + (v[6].y + v[7].y));
            o.z = ((v[0].z + v[1].z) + (v[2].z + v[3].z)) + ((v[4].z + v[5].z) + (v[6].z + v[7].z));
            o.w = ((v[0].w + v[1].w) + (v[2].w + v[3].w)) + ((v[4].w + v[5].w) + (v[6].w + v[7].w));
            o.w = f_(__float_as_uint(o.w) & ~1u);
            st_pktp(px0, __float_as_uint(o.x), __float_as_uint(o.y), __float_as_uint(o.z), __float_as_uint(o.w), threadIdx.x < 48);
        }
        uint32_t ticket = 0;
        if (layer == 0 && tid == 224)
            asm volatile("atom.relaxed.gpu.global.inc.u32 %0, [%1], 0x7fffffff;" : "=r"(ticket) : "l"(g_scr.ticket + 8 + (b >> 3)) : "memory");
        if (layer == 0 && tid == 224 && lds32(sb + SM_MISC + 12) < 256u) {
            int it = 0;
            while ((int)(now_ns() - lds32(sb + SM_XL + 4)) < 0 && ++it < SPIN_CAP) {}
            PROF_X(47);
            load_wo(maps, sb + SM_B, h, c, wbar, 6);
        }
        uint32_t pr;
        uint4* pacc;
        {
            const int tid = opq(threadIdx.x), warp = tid >> 5, lane = tid & 31, g = lane >> 2, t = lane & 3, mat = lane >> 3, r8 = lane & 7;
            const int kg = warp >> 1, mg = warp & 1;
            const bool wo2 = role1 < DN0 + NDN;
            const uint32_t aw2 = 40960 + (wo2 && KEEP4 && role1 >= DN0 && kg >= 2 ? SM_B - SM_Q : 0);
            uint32_t aw[5];
#pragma unroll
            for (int i = 0; i < 5; i++) {
                const uint32_t lin = ((mat >> 1) * 8 + r8) * 320 + 64 * i + 32 * mg + 16 * (mat & 1);
                aw[i] = sb + (wo2 ? SM_Q : SM_B) + 5120 * kg + (lin ^ ((lin >> 3) & 48));
            }
#define CXE 0
            const uint32_t ao = pin(sb + SM_OS + 96 * kg + 16 * t), dw = pin(sb + SM_R + 16 * (16 * mg + g) + 4 * kg);
            pr = pin(sb + SM_R + 48 * tid); pacc = pin(&g_scr.acc[layer][(54 * c + tid) * ACC_STR]);
            const int w = 2 * min(tid, 47);
            const uint32_t d0 = pin(sb + SM_OS + 4 * (24 * ((w >> 3) & 3) + ((w >> 2) & 1) + (w < 64 ? 4 * (w & 3) + 2 * (w >> 5) : 16 + 2 * (w & 3))));
            const uint32_t d1 = pin(d0 + (w < 64 ? 16 : 8));
            const uint4* pp[3];
#pragma unroll
            for (int k = 0; k < 3; k++) pp[k] = pin(&g_scr.hx[(h * 4 + ((c + 1 + k) & 3)) * 48 + min(tid, 47)]);
            uint4 v3[3];
#pragma unroll
            for (int k = 0; k < 3; k++) v3[k] = make_uint4(0u, 0u, 0u, 1u);
            if ((PRE1 & 8) && layer) {
#pragma unroll
                for (int ks = 0; ks < 3; ks++) {
                    mbar_wait(wbar + 8 * ks, wo2);
#pragma unroll
                    for (int i = 0; i < 5; i++) ldsm4t(aw[i] + (ks == 2 ? aw2 : 20480 * ks), kq[3 * i + ks]);
                    if (ks == CXE && wu < 2) {
#pragma unroll
                        for (int k = 0; k < 3; k++) v3[k] = ld_pkt(pp[k]);
                    }
                }
                PROF_T(50);
            }
            if (wu < 2) {
                for (int it = 0; any_odd(v3[0].w, v3[1].w, v3[2].w) && it < SPIN_CAP; it++) {
#pragma unroll
                    for (int k = 0; k < 3; k++) v3[k] = ld_pkt(pp[k]);
                }
                o.x = (o.x + f_(v3[0].x)) + (f_(v3[1].x) + f_(v3[2].x)); o.y = (o.y + f_(v3[0].y)) + (f_(v3[1].y) + f_(v3[2].y));
                o.z = (o.z + f_(v3[0].z)) + (f_(v3[1].z) + f_(v3[2].z)); o.w = (o.w + f_(v3[0].w)) + (f_(v3[1].w) + f_(v3[2].w));
                sts32p(d0, f_(pack2(o.x, o.y)), tid >= 48);
                sts32p(d1, f_(pack2(o.z, o.w)), tid >= 48);
            }
            PC(layer * 32 + 3);
            __syncthreads();
            PROF_T(5 + layer * 16);
            PC(layer * 32 + 5);
            if (tid == 224 && layer == 0) {
                if (ticket >= 6 + ((b >> 3) & 1)) ticket = DN0 + NDN;
                else asm volatile("atom.relaxed.gpu.global.inc.u32 %0, [%1], 0x7fffffff;" : "=r"(ticket) : "l"(g_scr.ticket) : "memory");
            }
            uint32_t ob[6];
            lds128(ao, ob[0], ob[1], ob[2], ob[3]);
            lds64(ao + 64 - 8 * t, ob[4], ob[5]);
            float cc[5][4];
#pragma unroll
            for (int i = 0; i < 5; i++) cc[i][0] = cc[i][1] = cc[i][2] = cc[i][3] = 0.f;
            if ((PRE1 & 8) && layer) {
#pragma unroll
                for (int ks = 0; ks < 3; ks++) {
#pragma unroll
                    for (int i = 0; i < 5; i++) mma16816(cc[i], kq[3 * i + ks][0], kq[3 * i + ks][1], kq[3 * i + ks][2], kq[3 * i + ks][3], ob[2 * ks], ob[2 * ks + 1]);
                }
            } else {
#pragma unroll
                for (int ks = 0; ks < 3; ks++) {
                    mbar_wait(wbar + 8 * ks, wo2);
                    if (ks == 2) { PC(layer * 32 + 4); PROF_T(48 + layer * 2); }
                    uint32_t a[5][4];
#pragma unroll
                    for (int i = 0; i < 5; i++) ldsm4t(aw[i] + (ks == 2 ? aw2 : 20480 * ks), a[i]);
#pragma unroll
                    for (int i = 0; i < 5; i++) mma16816(cc[i], a[i][0], a[i][1], a[i][2], a[i][3], ob[2 * ks], ob[2 * ks + 1]);
                }
            }
            if (t == 0) {
#pragma unroll
                for (int i = 0; i < 5; i++) { sts32(dw + 512 * i, cc[i][0]); sts32(dw + 512 * i + 128, cc[i][2]); }
            }
        }
        PC(layer * 32 + 6);
        __syncthreads();
        PROF_T(6 + layer * 16);
        PC(layer * 32 + 7);
        if (tid < 54) {
            const float4 v0 = lds4f(pr), v1 = lds4f(pr + 16), v2 = lds4f(pr + 32);
            const float y0 = (v0.x + v0.y) + (v0.z + v0.w), y1 = (v1.x + v1.y) + (v1.z + v1.w), y2 = (v2.x + v2.y) + (v2.z + v2.w);
            red_pkt(pacc, y0, tid == 53 ? 0.f : y1, tid == 53 ? 0.f : y2);
        }
        if (tid == 224 && layer == 0) {
            misc[1] = __uint_as_float(ticket);
            if (ticket < DN0 + NDN && (ticket < NG || !DNTH)) load_ffn(maps, ticket, sb + SM_B, fbar);
        }
        PROF_T(7 + layer * 16);
        PC(layer * 32 + 8);
        __syncthreads();
        const int role = (int)__float_as_uint(misc[1]);
        PC(layer * 32 + 9);
        const uint32_t fbase = sb + SM_B;
        const uint32_t DONE32 = 0x42000000u;
        if (role < NG) {
            const int tid = opq(threadIdx.x), warp = tid >> 5, lane = tid & 31, g = lane >> 2, t = lane & 3, mat = lane >> 3, r8 = lane & 7;
            const uint32_t ag = fbase + (80 * warp + (mat >> 1) * 8 + r8) * 96 + (((mat & 1) ^ (r8 >> 2)) << 4);
            constexpr int GI = 32, GK = 16 * 96;
            const bool on = (g & 1) == (t >> 1), isx = on && g < 2;
            const uint32_t pm = opq(isx ? sb + SM_XS + 160 * warp + 16 * t : sb + (on ? SM_ONE : SM_ZERO)), pm2 = opq(pm + 128 - (isx ? 8 * t : 0));
            const uint32_t dg = opq(sb + SM_R + 4 * (2 * (warp * 48 + g) + t)), ds = opq(sb + SM_ST + 8 * warp + (lane < 16 ? 4 : 0));
            const bool ws = (lane & 15) == 0, lo = lane < 16;
            uint32_t pre[6][4];
            float s1 = 0.f, s2 = 0.f;
            {
                bool hx = false;
                int it = 0;
                const int cq = wu >> 1, odd = wu & 1, r = min(26 * odd + lane, 26 + 27 * odd), c0 = 3 * r - 80 * odd, k0 = 160 * cq + 3 * r;
                const uint4* px = &g_scr.acc[layer][(54 * cq + r) * ACC_STR];
                const bool act = lane <= 26 + odd;
                const bool on0 = act && c0 >= 0, on1 = act && c0 + 1 >= 0 && c0 + 1 < 80, on2 = act && c0 + 2 < 80;
                const uint32_t w0 = sb + SM_XS + 4 * xpos(k0 >> 1), w1 = sb + SM_XS + 4 * xpos(min((k0 >> 1) + 1, DM / 2 - 1));
                const uint32_t e0 = w0 + 2 * (k0 & 1), e1 = (k0 & 1) ? w1 : w0 + 2, e2 = w1 + 2 * (k0 & 1);
                auto sts16 = [](uint32_t a, uint32_t x, bool on) {
                    asm volatile("{\n.reg .pred p;\nsetp.ne.u32 p, %2, 0;\n@p st.shared.u16 [%0], %1;\n}" ::"r"(a), "h"((unsigned short)x), "r"((uint32_t)on) : "memory");
                };
                const float x0 = on0 ? f_(lds16(e0) << 16) : 0.f, x1 = on1 ? f_(lds16(e1) << 16) : 0.f, x2 = on2 ? f_(lds16(e2) << 16) : 0.f;
                auto take_x = [&](const uint4 v) {
                    if (__all_sync(0xffffffffu, v.w == DONE32)) {
                        hx = true;
                        const uint32_t a = pack2(f_(v.x), f_(v.y)), p = pack2(x0 + bf_lo(a), x1 + bf_hi(a)), q = pack2(x2 + bfr(f_(v.z)), 0.f);
                        sts16(e0, p, on0); sts16(e1, p >> 16, on1); sts16(e2, q, on2);
                        const float y0 = on0 ? bf_lo(p) : 0.f, y1 = on1 ? bf_hi(p) : 0.f, y2 = on2 ? bf_lo(q) : 0.f;
                        s1 = y0 + (y1 + y2); s2 = y0 * y0 + (y1 * y1 + y2 * y2);
                    }
                };
                auto try_x = [&]() { take_x(ld_pkt(px)); };
                while (!mbar_test(fbar, 0) && ++it < SPIN_CAP) { if (!hx) try_x(); }
                uint4 v0 = make_uint4(0u, 0u, 0u, 0u);
                if ((PRE1 & 4) && !hx) v0 = ld_pkt(px);
#pragma unroll
                for (int n = 0; n < 6; n++) ldsm4t(ag + (n % 3) * GI + (n / 3) * GK, pre[n]);
                if ((PRE1 & 1) && layer) {
#pragma unroll
                    for (int n = 6; n < 15; n++) ldsm4t(ag + (n % 3) * GI + (n / 3) * GK, kq[n - 6]);
                }
                if ((PRE1 & 4) && !hx) take_x(v0);
                PC(layer * 32 + 10);
                for (; !hx && it < SPIN_CAP; it++) try_x();
                PC(layer * 32 + 11);
            __syncwarp();
            PC(layer * 32 + 12);
            PROF_T(9 + layer * 16);
            float sv = lo ? s1 : s2, cc[3][4];
            if ((PRE1 & 1) && layer) gemv15r(cc, pre, kq, pm, pm2, sv, lo ? s2 : s1);
            else gemv15<GK>(cc, pre, [&](int i) { return ag + i * GI; }, pm, pm2, sv, lo ? s2 : s1);
#pragma unroll
            for (int i = 0; i < 3; i++) { sts32p(dg + 128 * i, cc[i][0] + cc[i][3], t & 2); sts32p(dg + 128 * i + 64, cc[i][1] + cc[i][2], t & 2); }
            if (ws) sts32(ds, sv);
            const uint32_t pg = opq(sb + SM_R + 8 * (24 * warp + (lane < 24 ? lane : 0))), st = opq(sb + SM_ST);
            uint4* const ph = opq(lane < 24 && lane % 6 == 0 ? &g_scr.ah[role * 8 + 4 * warp + lane / 6] : nullptr);
            PC(layer * 32 + 13);
            __syncthreads();
            PC(layer * 32 + 14);
            PROF_T(43 + layer * 16);
            if (wu < 2) {
                float mean, inv;
                ln_stats(st, mean, inv);
                float2 v[8];
#pragma unroll
                for (int w = 0; w < 8; w++) v[w] = lds2f(pg + w * 384);
                const float gx = ((v[0].x + v[1].x) + (v[2].x + v[3].x)) + ((v[4].x + v[5].x) + (v[6].x + v[7].x));
                const float gs = ((v[0].y + v[1].y) + (v[2].y + v[3].y)) + ((v[4].y + v[5].y) + (v[6].y + v[7].y));
                float ga = inv * (gx - mean * gs);
                if (role < NG / 2) { ga = bfr(ga); ga *= rcp(1.0f + ex2(-1.4426950408889634f * ga)); }
                const uint32_t wd = pack2(ga, __shfl_down_sync(0xffffffffu, ga, 1));
                const uint32_t wa = __shfl_down_sync(0xffffffffu, wd, 2), wb = __shfl_down_sync(0xffffffffu, wd, 4);
                if (ph) st_pkt(ph, wd, wa, wb, tag);
            }
            if (HOLD & 2) __syncthreads();
            }
            PROF_T(10 + layer * 16);
            PC(layer * 32 + 15);
        } else if (role < DN0 + NDN) {
            const int j = role - DN0;
            const int tid = opq(threadIdx.x), warp = tid >> 5, lane = tid & 31, g = lane >> 2, t = lane & 3, mat = lane >> 3, r8 = lane & 7;
            float xres = 0.f;
            uint32_t xr0 = 0, xr1 = 0;
            if (wu == 0) {
                const int col = 16 * j + (lane & 15), cc = col / 160, r = col - 160 * cc, e = r % 3;
                const uint4* px = &g_scr.acc[layer][(54 * cc + r / 3) * ACC_STR];
                const float x0 = __bfloat162float(reinterpret_cast<const __nv_bfloat16*>(xs32)[2 * xpos(col >> 1) + (col & 1)]);
                uint4 v;
                int it = 0;
                bool ld = DNTH && layer == 0;
                do {
                    v = ld_pkt(px);
                    if (ld && f_(__shfl_sync(0xffffffffu, v.w, 0)) >= (float)DNTH) { ld = false; if (lane == 0) load_ffn(maps, role, sb + SM_B, fbar); }
                } while (!__all_sync(0xffffffffu, v.w == DONE32) && ++it < SPIN_CAP);
                if (ld && lane == 0) load_ffn(maps, role, sb + SM_B, fbar);
                xres = x0 + bfr(f_(e == 0 ? v.x : (e == 1 ? v.y : v.z)));
                const int p4 = 4 * (lane & 3);
                xr0 = pack2(__shfl_sync(0xffffffffu, xres, p4), __shfl_sync(0xffffffffu, xres, p4 + 1));
                xr1 = pack2(__shfl_sync(0xffffffffu, xres, p4 + 2), __shfl_sync(0xffffffffu, xres, p4 + 3));
            }
            PC(layer * 32 + 17);
            PROF_T(9 + layer * 16);
            const uint32_t ad = fbase + (192 * warp + (mat >> 1) * 8 + r8) * 32 + (((mat & 1) ^ (r8 >> 2)) << 4);
            uint32_t* hs = reinterpret_cast<uint32_t*>(rr) + warp * 96;
            uint32_t pre[NPRE][4];
            {
                uint32_t pos[3];
#pragma unroll
                for (int i = 0; i < 3; i++) { const int w = 3 * lane + i; pos[i] = pin(sb + SM_R + 384 * warp + 4 * ((w & ~15) + 4 * (w & 3) + ((w >> 2) & 1) + ((w >> 2) & 2))); }
                uint4 v = make_uint4(0u, 0u, 0u, 0u), u = v;
                if (layer == 0) { v = ld_pkt(&g_scr.ah[tid]); u = ld_pkt(&g_scr.ah[256 + tid]); }
                mbar_wait(fbar, 0);
#pragma unroll
                for (int n = 0; n < NPRE; n++) ldsm4t(ad + n * 512, pre[n]);
                if ((PRE1 & 2) && layer) {
#pragma unroll
                    for (int n = NPRE; n < 12; n++) ldsm4t(ad + n * 512, kq[12 + n]);
                }
                PC(layer * 32 + 18);
                int it = 0;
                for (; any_ne(v.w, u.w, tag) && it < SPIN_CAP; it++) { v = ld_pkt(&g_scr.ah[tid]); u = ld_pkt(&g_scr.ah[256 + tid]); }
                PC(layer * 32 + 19);
                sts32(pos[0], f_(bmul2(v.x, u.x))); sts32(pos[1], f_(bmul2(v.y, u.y))); sts32(pos[2], f_(bmul2(v.z, u.z)));
            __syncwarp();
            PROF_T(11 + layer * 16);
            PC(layer * 32 + 20);
            float ca[4] = {0.f, 0.f, 0.f, 0.f}, cb[4] = {0.f, 0.f, 0.f, 0.f};
            if ((PRE1 & 2) && layer) {
                float cc[4] = {0.f, 0.f, 0.f, 0.f}, cd[4] = {0.f, 0.f, 0.f, 0.f};
#pragma unroll
                for (int jj = 0; jj < 6; jj++) {
                    const uint4 hv = *reinterpret_cast<const uint4*>(hs + 16 * jj + 4 * t);
                    const uint32_t (&f0)[4] = 2 * jj < NPRE ? pre[2 * jj < NPRE ? 2 * jj : 0] : kq[12 + 2 * jj];
                    const uint32_t (&f1)[4] = 2 * jj + 1 < NPRE ? pre[2 * jj + 1 < NPRE ? 2 * jj + 1 : 0] : kq[13 + 2 * jj];
                    if (jj & 1) { mma16816(cc, f0[0], f0[1], f0[2], f0[3], hv.x, hv.y); mma16816(cd, f1[0], f1[1], f1[2], f1[3], hv.z, hv.w); }
                    else { mma16816(ca, f0[0], f0[1], f0[2], f0[3], hv.x, hv.y); mma16816(cb, f1[0], f1[1], f1[2], f1[3], hv.z, hv.w); }
                }
#pragma unroll
                for (int e = 0; e < 4; e++) { ca[e] += cc[e]; cb[e] += cd[e]; }
            } else {
#pragma unroll
                for (int jj = 0; jj < 6; jj++) {
                    const uint4 hv = *reinterpret_cast<const uint4*>(hs + 16 * jj + 4 * t);
                    uint32_t a[4];
                    if (2 * jj < NPRE) { a[0] = pre[2 * jj][0]; a[1] = pre[2 * jj][1]; a[2] = pre[2 * jj][2]; a[3] = pre[2 * jj][3]; }
                    else ldsm4t(ad + 2 * jj * 512, a);
                    mma16816(ca, a[0], a[1], a[2], a[3], hv.x, hv.y);
                    if (2 * jj + 1 < NPRE) { a[0] = pre[2 * jj + 1][0]; a[1] = pre[2 * jj + 1][1]; a[2] = pre[2 * jj + 1][2]; a[3] = pre[2 * jj + 1][3]; }
                    else ldsm4t(ad + (2 * jj + 1) * 512, a);
                    mma16816(cb, a[0], a[1], a[2], a[3], hv.z, hv.w);
                }
            }
            if (t == 0) { rr[768 + warp * 16 + g] = ca[0] + cb[0]; rr[768 + warp * 16 + 8 + g] = ca[2] + cb[2]; }
            const uint32_t pd = opq(sb + SM_R + 3072 + 16 * (lane & 3));
            uint4* const py = opq(&g_scr.ay[j * 4 + lane]);
            uint2* const po = opq(reinterpret_cast<uint2*>(out + 16 * j) + lane);
            PC(layer * 32 + 21);
            __syncthreads();
            PC(layer * 32 + 22);
            if (wu == 0) {
                float4 p[8];
#pragma unroll
                for (int w = 0; w < 8; w++) p[w] = lds4f(pd + 64 * w);
                const uint32_t y0 = pack2(((p[0].x + p[1].x) + (p[2].x + p[3].x)) + ((p[4].x + p[5].x) + (p[6].x + p[7].x)),
                                          ((p[0].y + p[1].y) + (p[2].y + p[3].y)) + ((p[4].y + p[5].y) + (p[6].y + p[7].y)));
                const uint32_t y1 = pack2(((p[0].z + p[1].z) + (p[2].z + p[3].z)) + ((p[4].z + p[5].z) + (p[6].z + p[7].z)),
                                          ((p[0].w + p[1].w) + (p[2].w + p[3].w)) + ((p[4].w + p[5].w) + (p[6].w + p[7].w)));
                uint32_t wd, wn;
                asm("add.rn.bf16x2 %0, %1, %2;" : "=r"(wd) : "r"(xr0), "r"(y0));
                asm("add.rn.bf16x2 %0, %1, %2;" : "=r"(wn) : "r"(xr1), "r"(y1));
                asm volatile("{\n.reg .pred p;\nsetp.ne.u32 p, %3, 0;\n@p st.global.v2.u32 [%0], {%1,%2};\n}" ::"l"(po), "r"(wd), "r"(wn), "r"((uint32_t)(layer && tid < 4)) : "memory");
                st_pktp(py, wd, wn, 0, tag, tid < 4);
            }
            if (HOLD & 1) __syncthreads();
            }
            PROF_T(12 + layer * 16);
            PC(layer * 32 + 23);
        }
    }
}

typedef CUresult (*EncodeFn)(CUtensorMap*, CUtensorMapDataType, cuuint32_t, void*, const cuuint64_t*, const cuuint64_t*, const cuuint32_t*,
                             const cuuint32_t*, CUtensorMapInterleave, CUtensorMapSwizzle, CUtensorMapL2promotion, CUtensorMapFloatOOBfill);

void make_map(EncodeFn enc, CUtensorMap* m, const void* base, int rank, uint64_t d0, uint64_t d1, uint64_t d2, uint64_t s1, uint64_t s2,
              uint32_t b0, uint32_t b1, uint32_t b2, CUtensorMapSwizzle sw, CUtensorMapL2promotion pr = CU_TENSOR_MAP_L2_PROMOTION_NONE) {
    cuuint64_t dims[3] = {d0, d1, d2};
    cuuint64_t strides[2] = {s1, s2};
    cuuint32_t box[3] = {b0, b1, b2};
    cuuint32_t es[3] = {1, 1, 1};
    enc(m, CU_TENSOR_MAP_DATA_TYPE_BFLOAT16, rank, const_cast<void*>(base), dims, strides, box, es, CU_TENSOR_MAP_INTERLEAVE_NONE, sw,
        pr, CU_TENSOR_MAP_FLOAT_OOB_FILL_NONE);
}

}

extern "C" void kernel_launch(void* const* d_in, const int* in_sizes, int n_in, void* d_out, int out_size) {
    (void)in_sizes; (void)n_in; (void)out_size;
    static EncodeFn enc = nullptr;
    if (!enc) {
        void* fn = nullptr;
        cudaDriverEntryPointQueryResult qr;
        cudaGetDriverEntryPoint("cuTensorMapEncodeTiled", &fn, cudaEnableDefault, &qr);
        enc = reinterpret_cast<EncodeFn>(fn);
        cudaFuncSetAttribute(decode_kernel, cudaFuncAttributeMaxDynamicSharedMemorySize, SM_TOTAL);
    }
    Maps maps;
    make_map(enc, &maps.k, d_in[1], 2, 64, (uint64_t)NH * SK * 3, 1, 128, 0, 64, 48, 1, CU_TENSOR_MAP_SWIZZLE_128B);
    make_map(enc, &maps.v, d_in[2], 2, 64, (uint64_t)NH * SK * 3, 1, 128, 0, 64, 48, 1, CU_TENSOR_MAP_SWIZZLE_128B);
    make_map(enc, &maps.wq, d_in[3], 3, 64, DM, NH * DH / 64, NH * DH * 2, 128, 64, 160, 3, CU_TENSOR_MAP_SWIZZLE_128B);
    make_map(enc, &maps.wo, d_in[4], 3, 32, DM / 32, NH * DH, 64, DM * 2, 32, 5, 32, CU_TENSOR_MAP_SWIZZLE_64B);
    make_map(enc, &maps.vr, (const char*)d_in[2] + 512, 2, 128, (uint64_t)NH * SK / 2, 1, 768, 0, 128, 2, 1, CU_TENSOR_MAP_SWIZZLE_NONE);
    constexpr int GW = 48;
    make_map(enc, &maps.w1, d_in[6], 3, FF, 160, 4, FF * 2, 160 * FF * 2, GW, 160, 4, CU_TENSOR_MAP_SWIZZLE_NONE, FFN_PROMO);
    make_map(enc, &maps.w3, d_in[7], 3, FF, 160, 4, FF * 2, 160 * FF * 2, GW, 160, 4, CU_TENSOR_MAP_SWIZZLE_NONE, FFN_PROMO);
    make_map(enc, &maps.w2, d_in[8], 3, DM, 256, 6, DM * 2, 256 * DM * 2, 16, 256, 6, CU_TENSOR_MAP_SWIZZLE_32B, FFN_PROMO);
    maps.vp = d_in[2];
    maps.kp = d_in[1];
    maps.zero = 0;
    decode_kernel<<<NCTA, NT, SM_TOTAL, cudaStreamPerThread>>>(maps, (const __nv_bfloat16*)d_in[0], (__nv_bfloat16*)d_out);
}
```

```cpp
#include <cuda_runtime.h>
#include <cuda_bf16.h>
#include <cuda.h>
#include <stdint.h>
#include <math.h>

namespace {

constexpr int DM = 640;
constexpr int NH = 32;
constexpr int DH = 192;
constexpr int SK = 32768;
constexpr int WIN = 4096;
constexpr int FF = 1536;
constexpr int NCTA = 128;
constexpr int NT = 256;
constexpr int TILE = 6144;
constexpr int NG = 64;
constexpr int DN0 = 64;
constexpr int NDN = 40;

constexpr int SM_RING = 0;
constexpr int SM_B = 8 * 2 * TILE;
constexpr int SM_Q = SM_B + 61440;
__host__ __device__ constexpr int c_slot(int w) { return w < 2 ? 4096 + 10240 * w : 12288 + 6144 * w; }
__host__ __device__ constexpr int v1_pos(int n) { return 10240 * (n >> 3) + 512 * (n & 7); }
constexpr int SM_XS = SM_Q + 61440;
constexpr int SM_R = SM_XS + 1280;
constexpr int SM_ST = SM_R + 4096;
constexpr int SM_QS = SM_R + 6272;
constexpr int SM_OS = SM_QS + 384;
constexpr int SM_BAR = SM_OS + 384;
constexpr int SM_XBAR = SM_BAR + 24 * 8;
constexpr int SM_MISC = SM_XBAR + 8 * 8;
constexpr int SM_ONE = SM_MISC + 16;
constexpr int SM_ZERO = SM_ONE + 160;
constexpr int XCAP = 48;
constexpr int XSTR = 16 + 4 * XCAP;
constexpr int SM_XL = SM_ZERO + 160;
constexpr int SM_TOTAL = SM_XL + 8 * XSTR;
static_assert(SM_TOTAL <= 232448, "shared memory");

constexpr unsigned long long POL_EF = 0x12F0000000000000ull;
constexpr unsigned long long POL_EN = 0x16F0000000000000ull;

#define RT_MASK 0xF2E0u
#define RT_MASK2 0xEAE0u
#define WO_AT1 5
#define FFN_PROMO CU_TENSOR_MAP_L2_PROMOTION_NONE
#define FFN_POL POL_EF
#define HAS_FFN (__float_as_uint(misc[1]) < DN0 + NDN)
#define NPRE 6

#define STAG 200
#define L1R 3
#define PRE1 13
#define HOLD 2
#define DNTH 23
constexpr int V0_AT = 8;
constexpr unsigned long long SEQ1 = 0x2765431076543210ull;
constexpr uint32_t IN_S1 = 0xAA49, IN_S0 = 0x124, PARITY1 = 0x6638, PARITY2 = 0xCE;
#define KEEP4 1
constexpr int NQ = 48;
constexpr int SPIN_CAP = 1 << 19;
constexpr uint32_t ONES = 0x3F803F80u;

struct alignas(4096) Scratch {
    uint4 hx[NCTA * 48];
    uint4 acc[2][256];
    uint4 ay[256];
    uint4 ah[NG * 8];
    uint2 mx[NH * 32];
    uint32_t ticket[32];
    uint32_t pad1[32];
};
__device__ Scratch g_scr;
#define PROF_T(i)
#define PROF_X(i)
#define PC(i)

__device__ __forceinline__ uint32_t smem_u32(const void* p) { return (uint32_t)__cvta_generic_to_shared(p); }
__device__ __forceinline__ void mbar_init(uint32_t bar, uint32_t cnt) {
    asm volatile("mbarrier.init.shared::cta.b64 [%0], %1;" ::"r"(bar), "r"(cnt) : "memory");
}
__device__ __forceinline__ void mbar_expect_tx(uint32_t bar, uint32_t bytes) {
    asm volatile("mbarrier.arrive.expect_tx.shared::cta.b64 _, [%0], %1;" ::"r"(bar), "r"(bytes) : "memory");
}
__device__ __forceinline__ bool mbar_test(uint32_t bar, uint32_t parity) {
    uint32_t done;
    asm volatile("{\n.reg .pred p;\nmbarrier.try_wait.parity.shared::cta.b64 p, [%1], %2;\nselp.u32 %0, 1, 0, p;\n}"
                 : "=r"(done) : "r"(bar), "r"(parity) : "memory");
    return done;
}
__device__ __forceinline__ void mbar_wait(uint32_t bar, uint32_t parity) {
    for (int it = 0; it < SPIN_CAP; it++) if (mbar_test(bar, parity)) break;
}
__device__ __forceinline__ void tma2d(uint32_t dst, const CUtensorMap* map, int c0, int c1, uint32_t bar, unsigned long long pol) {
    asm volatile("cp.async.bulk.tensor.2d.shared::cluster.global.mbarrier::complete_tx::bytes.L2::cache_hint [%0], [%1, {%3, %4}], [%2], %5;"
                 ::"r"(dst), "l"(map), "r"(bar), "r"(c0), "r"(c1), "l"(pol) : "memory");
}
__device__ __forceinline__ void tma3d(uint32_t dst, const CUtensorMap* map, int c0, int c1, int c2, uint32_t bar, unsigned long long pol) {
    asm volatile("cp.async.bulk.tensor.3d.shared::cluster.global.mbarrier::complete_tx::bytes.L2::cache_hint [%0], [%1, {%3, %4, %5}], [%2], %6;"
                 ::"r"(dst), "l"(map), "r"(bar), "r"(c0), "r"(c1), "r"(c2), "l"(pol) : "memory");
}
__device__ __forceinline__ void tile_load(uint32_t dst, const CUtensorMap* map, int row, uint32_t bar, uint32_t dep, uint32_t zero) {
    asm volatile("{\n.reg .pred p;\n.reg .b32 n;\nmad.lo.u32 n, %5, %6, 6144;\nelect.sync _|p, 0xffffffff;\n"
                 "@p mbarrier.arrive.expect_tx.shared::cta.b64 _, [%2], n;\n"
                 "@p cp.async.bulk.tensor.2d.shared::cluster.global.mbarrier::complete_tx::bytes.L2::cache_hint [%0], [%1, {0, %3}], [%2], %4;\n}"
                 ::"r"(dst), "l"(map), "r"(bar), "r"(row), "l"(POL_EF), "r"(dep), "r"(zero) : "memory");
}
__device__ __forceinline__ void tile_keep(const CUtensorMap* map, int row) {
    asm volatile("{\n.reg .pred p;\nelect.sync _|p, 0xffffffff;\n"
                 "@p cp.async.bulk.prefetch.tensor.2d.L2.global.L2::cache_hint [%0, {0, %1}], %2;\n}"
                 ::"l"(map), "r"(row), "l"(POL_EN) : "memory");
}
__device__ __forceinline__ void tile_load_l1(uint32_t dst, const void* base, int row, uint32_t bar, int lane) {
    const char* g = static_cast<const char*>(base) + (size_t)row * 128 + lane * 16;
    const uint32_t s0 = dst + (lane >> 3) * 128 + (((lane & 7) ^ (lane >> 3)) << 4), s1 = s0 ^ 64;
#pragma unroll
    for (int k = 0; k < 12; k++)
        asm volatile("cp.async.ca.shared.global.L2::cache_hint [%0], [%1], 16, %2;" ::"r"(((k & 1) ? s1 : s0) + k * 512), "l"(g + k * 512), "l"(POL_EF) : "memory");
    asm volatile("cp.async.mbarrier.arrive.shared::cta.b64 [%0];" ::"r"(bar) : "memory");
    __syncwarp();
    if (lane == 0) asm volatile("mbarrier.arrive.shared::cta.b64 _, [%0];" ::"r"(bar) : "memory");
}
__device__ __forceinline__ bool elect_one() {
    uint32_t p;
    asm volatile("{\n.reg .pred p;\nelect.sync _|p, 0xffffffff;\nselp.u32 %0, 1, 0, p;\n}" : "=r"(p));
    return p;
}
__device__ __forceinline__ void lds128(uint32_t addr, uint32_t& a, uint32_t& b, uint32_t& c, uint32_t& d) {
    asm volatile("ld.shared.v4.u32 {%0,%1,%2,%3}, [%4];" : "=r"(a), "=r"(b), "=r"(c), "=r"(d) : "r"(addr) : "memory");
}
__device__ __forceinline__ void lds128p(uint32_t addr, uint32_t on, uint32_t& a, uint32_t& b, uint32_t& c, uint32_t& d) {
    asm volatile("{\n.reg .pred p;\nsetp.ne.u32 p, %5, 0;\n@p ld.shared.v4.u32 {%0,%1,%2,%3}, [%4];\n}" : "+r"(a), "+r"(b), "+r"(c), "+r"(d) : "r"(addr), "r"(on) : "memory");
}
__device__ __forceinline__ void lds64(uint32_t addr, uint32_t& a, uint32_t& b) {
    asm volatile("ld.shared.v2.u32 {%0,%1}, [%2];" : "=r"(a), "=r"(b) : "r"(addr) : "memory");
}
__device__ __forceinline__ void ldsm4t(uint32_t addr, uint32_t (&a)[4]) {
    asm volatile("ldmatrix.sync.aligned.m8n8.x4.trans.shared.b16 {%0,%1,%2,%3}, [%4];" : "=r"(a[0]), "=r"(a[1]), "=r"(a[2]), "=r"(a[3]) : "r"(addr) : "memory");
}
__device__ __forceinline__ void mma16816(float (&c)[4], uint32_t a0, uint32_t a1, uint32_t a2, uint32_t a3, uint32_t b0, uint32_t b1) {
    asm("mma.sync.aligned.m16n8k16.row.col.f32.bf16.bf16.f32 {%0,%1,%2,%3}, {%4,%5,%6,%7}, {%8,%9}, {%0,%1,%2,%3};"
        : "+f"(c[0]), "+f"(c[1]), "+f"(c[2]), "+f"(c[3]) : "r"(a0), "r"(a1), "r"(a2), "r"(a3), "r"(b0), "r"(b1));
}
__device__ __forceinline__ void mma16816v(float (&c)[4], uint32_t a0, uint32_t a1, uint32_t a2, uint32_t a3, uint32_t b0, uint32_t b1) {
    asm volatile("mma.sync.aligned.m16n8k16.row.col.f32.bf16.bf16.f32 {%0,%1,%2,%3}, {%4,%5,%6,%7}, {%8,%9}, {%0,%1,%2,%3};"
        : "+f"(c[0]), "+f"(c[1]), "+f"(c[2]), "+f"(c[3]) : "r"(a0), "r"(a1), "r"(a2), "r"(a3), "r"(b0), "r"(b1));
}
__device__ __forceinline__ int xpos(int w) {
    const int seg = w / 40, r = w - 40 * seg;
    return 40 * seg + (r < 32 ? (r & 16) + 4 * (r & 3) + ((r >> 2) & 3) : 32 + 2 * (r & 3) + ((r >> 2) & 1));
}
#define NA_LD ""
#define NA_ST ""
__device__ __forceinline__ void st_pkt(uint4* p, uint32_t a, uint32_t b, uint32_t c, uint32_t d) {
    asm volatile("{\n.reg .b128 t;\n.reg .b64 lo, hi;\nmov.b64 lo, {%1,%2};\nmov.b64 hi, {%3,%4};\nmov.b128 t, {lo,hi};\nst.relaxed.gpu.global" NA_ST ".b128 [%0], t;\n}"
                 ::"l"(p), "r"(a), "r"(b), "r"(c), "r"(d) : "memory");
}
__device__ __forceinline__ void red_pkt(uint4* p, float a, float b, float c) {
    asm volatile("red.relaxed.gpu.global.add.v4.f32 [%0], {%1,%2,%3,%4};" ::"l"(p), "f"(a), "f"(b), "f"(c), "f"(1.0f) : "memory");
}
__device__ __forceinline__ void st_pktp(uint4* p, uint32_t a, uint32_t b, uint32_t c, uint32_t d, bool on) {
    asm volatile("{\n.reg .pred p;\n.reg .b128 t;\n.reg .b64 lo, hi;\nsetp.ne.u32 p, %5, 0;\nmov.b64 lo, {%1,%2};\nmov.b64 hi, {%3,%4};\nmov.b128 t, {lo,hi};\n"
                 "@p st.relaxed.gpu.global.b128 [%0], t;\n}" ::"l"(p), "r"(a), "r"(b), "r"(c), "r"(d), "r"((uint32_t)on) : "memory");
}
__device__ __forceinline__ void st_pktfp(uint4* p, float a, float b, float c, float d, uint32_t bit, bool on) {
    st_pktp(p, __float_as_uint(a), __float_as_uint(b), __float_as_uint(c), (__float_as_uint(d) & ~1u) | bit, on);
}
__device__ __forceinline__ uint4 ld_pkt(const uint4* p) {
    uint4 v;
    asm volatile("{\n.reg .b128 t;\n.reg .b64 lo, hi;\nld.relaxed.gpu.global" NA_LD ".b128 t, [%4];\nmov.b128 {lo,hi}, t;\nmov.b64 {%0,%1}, lo;\nmov.b64 {%2,%3}, hi;\n}"
                 : "=r"(v.x), "=r"(v.y), "=r"(v.z), "=r"(v.w) : "l"(p) : "memory");
    return v;
}
__device__ __forceinline__ bool all_odd(uint32_t a, uint32_t b, uint32_t c, uint32_t d) {
    uint32_t r;
    asm volatile("{\n.reg .pred p, q, t;\n.reg .b32 x;\nsetp.eq.b32 t, 0, 0;\nlop3.b32 x, %1, %2, %3, 0x80;\nlop3.and.b32 _|p, x, %4, 1, 0x80, t;\n"
                 "vote.sync.all.pred q, p, 0xffffffff;\nselp.u32 %0, 1, 0, q;\n}" : "=r"(r) : "r"(a), "r"(b), "r"(c), "r"(d));
    return r;
}
__device__ __forceinline__ bool any_odd(uint32_t a, uint32_t b, uint32_t c) {
    uint32_t r;
    asm volatile("{\n.reg .pred p, q, t;\n.reg .b32 x;\nsetp.eq.b32 t, 0, 0;\nlop3.b32 x, %1, %2, %3, 0xFE;\nlop3.and.b32 _|p, x, 1, 0, 0xC0, t;\n"
                 "vote.sync.any.pred q, p, 0xffffffff;\nselp.u32 %0, 1, 0, q;\n}" : "=r"(r) : "r"(a), "r"(b), "r"(c));
    return r;
}
__device__ __forceinline__ bool any_ne(uint32_t a, uint32_t b, uint32_t c) {
    uint32_t r;
    asm volatile("{\n.reg .pred p, q, t;\nsetp.eq.b32 t, 0, 0;\nlop3.and.b32 _|p, %1, %2, %3, 0x7E, t;\n"
                 "vote.sync.any.pred q, p, 0xffffffff;\nselp.u32 %0, 1, 0, q;\n}" : "=r"(r) : "r"(a), "r"(b), "r"(c));
    return r;
}
__device__ __forceinline__ uint2 ld_pkt2(const uint2* p) {
    unsigned long long v;
    asm volatile("ld.relaxed.gpu.global" NA_LD ".b64 %0, [%1];" : "=l"(v) : "l"(p) : "memory");
    return make_uint2((uint32_t)v, (uint32_t)(v >> 32));
}
__device__ __forceinline__ void st_pkt2(uint2* p, uint32_t a, uint32_t b) {
    asm volatile("st.relaxed.gpu.global" NA_ST ".b64 [%0], %1;" ::"l"(p), "l"((unsigned long long)a | ((unsigned long long)b << 32)) : "memory");
}
__device__ __forceinline__ float ex2(float x) { float y; asm("ex2.approx.ftz.f32 %0, %1;" : "=f"(y) : "f"(x)); return y; }
__device__ __forceinline__ float rcp(float x) { float y; asm("rcp.approx.ftz.f32 %0, %1;" : "=f"(y) : "f"(x)); return y; }
__device__ __forceinline__ uint32_t pack2(float lo, float hi) {
    uint32_t r; asm("cvt.rn.bf16x2.f32 %0, %1, %2;" : "=r"(r) : "f"(hi), "f"(lo)); return r;
}
__device__ __forceinline__ float bf_lo(uint32_t w) { return __uint_as_float(w << 16); }
__device__ __forceinline__ float bf_hi(uint32_t w) { return __uint_as_float(w & 0xffff0000u); }
__device__ __forceinline__ float bfr(float x) { return bf_lo(pack2(x, 0.f)); }
__device__ __forceinline__ float f_(uint32_t u) { return __uint_as_float(u); }

template <int SK, typename AddrF>
__device__ __forceinline__ void gemv15(float (&cc)[3][4], uint32_t (&pre)[6][4], AddrF ad, uint32_t px, uint32_t px2, float& sv, float so) {
    uint32_t x0[4], x1[4], a[3][4];
    asm volatile("ld.shared.v4.u32 {%0,%1,%2,%3}, [%20];\nld.shared.v4.u32 {%4,%5,%6,%7}, [%20+64];\n"
                 "ldmatrix.sync.aligned.m8n8.x4.trans.shared.b16 {%8,%9,%10,%11}, [%21];\n"
                 "ldmatrix.sync.aligned.m8n8.x4.trans.shared.b16 {%12,%13,%14,%15}, [%22];\n"
                 "ldmatrix.sync.aligned.m8n8.x4.trans.shared.b16 {%16,%17,%18,%19}, [%23];\nbar.warp.sync 0xffffffff;"
                 : "=r"(x0[0]), "=r"(x0[1]), "=r"(x0[2]), "=r"(x0[3]), "=r"(x1[0]), "=r"(x1[1]), "=r"(x1[2]), "=r"(x1[3]),
                   "=r"(a[0][0]), "=r"(a[0][1]), "=r"(a[0][2]), "=r"(a[0][3]), "=r"(a[1][0]), "=r"(a[1][1]), "=r"(a[1][2]), "=r"(a[1][3]),
                   "=r"(a[2][0]), "=r"(a[2][1]), "=r"(a[2][2]), "=r"(a[2][3])
                 : "r"(px), "r"(ad(0) + 2 * SK), "r"(ad(1) + 2 * SK), "r"(ad(2) + 2 * SK) : "memory");
    __syncwarp();
    sv += __shfl_xor_sync(0xffffffffu, so, 16);
#pragma unroll
    for (int i = 0; i < 3; i++) {
        cc[i][0] = cc[i][1] = cc[i][2] = cc[i][3] = 0.f;
        mma16816v(cc[i], pre[i][0], pre[i][1], pre[i][2], pre[i][3], x0[0], x0[1]);
    }
    sv += __shfl_xor_sync(0xffffffffu, sv, 8);
#pragma unroll
    for (int i = 0; i < 3; i++) {
        mma16816v(cc[i], pre[3 + i][0], pre[3 + i][1], pre[3 + i][2], pre[3 + i][3], x0[2], x0[3]);
        ldsm4t(ad(i) + 3 * SK, pre[i]);
    }
    lds64(px2, x0[0], x0[1]);
    __syncwarp();
    sv += __shfl_xor_sync(0xffffffffu, sv, 4);
#pragma unroll
    for (int i = 0; i < 3; i++) {
        mma16816v(cc[i], a[i][0], a[i][1], a[i][2], a[i][3], x1[0], x1[1]);
        ldsm4t(ad(i) + 4 * SK, pre[3 + i]);
    }
    __syncwarp();
    sv += __shfl_xor_sync(0xffffffffu, sv, 2);
#pragma unroll
    for (int i = 0; i < 3; i++) mma16816v(cc[i], pre[i][0], pre[i][1], pre[i][2], pre[i][3], x1[2], x1[3]);
    sv += __shfl_xor_sync(0xffffffffu, sv, 1);
#pragma unroll
    for (int i = 0; i < 3; i++) mma16816v(cc[i], pre[3 + i][0], pre[3 + i][1], pre[3 + i][2], pre[3 + i][3], x0[0], x0[1]);
}
__device__ __forceinline__ void gemv15r(float (&cc)[3][4], const uint32_t (&pre)[6][4], const uint32_t (&ext)[NQ][4], uint32_t px, uint32_t px2, float& sv, float so) {
    uint32_t x0[4], x1[4], x2[2];
    float cd[3][4];
    lds128(px, x0[0], x0[1], x0[2], x0[3]);
    lds128(px + 64, x1[0], x1[1], x1[2], x1[3]);
    lds64(px2, x2[0], x2[1]);
    sv += __shfl_xor_sync(0xffffffffu, so, 16);
#pragma unroll
    for (int i = 0; i < 3; i++) {
        cc[i][0] = cc[i][1] = cc[i][2] = cc[i][3] = cd[i][0] = cd[i][1] = cd[i][2] = cd[i][3] = 0.f;
        mma16816v(cc[i], pre[i][0], pre[i][1], pre[i][2], pre[i][3], x0[0], x0[1]);
        mma16816v(cd[i], pre[3 + i][0], pre[3 + i][1], pre[3 + i][2], pre[3 + i][3], x0[2], x0[3]);
    }
    sv += __shfl_xor_sync(0xffffffffu, sv, 8);
#pragma unroll
    for (int i = 0; i < 3; i++) {
        mma16816v(cc[i], ext[i][0], ext[i][1], ext[i][2], ext[i][3], x1[0], x1[1]);
        mma16816v(cd[i], ext[3 + i][0], ext[3 + i][1], ext[3 + i][2], ext[3 + i][3], x1[2], x1[3]);
    }
    sv += __shfl_xor_sync(0xffffffffu, sv, 4);
#pragma unroll
    for (int i = 0; i < 3; i++) mma16816v(cc[i], ext[6 + i][0], ext[6 + i][1], ext[6 + i][2], ext[6 + i][3], x2[0], x2[1]);
    sv += __shfl_xor_sync(0xffffffffu, sv, 2);
    sv += __shfl_xor_sync(0xffffffffu, sv, 1);
#pragma unroll
    for (int i = 0; i < 3; i++) { cc[i][0] += cd[i][0]; cc[i][1] += cd[i][1]; cc[i][2] += cd[i][2]; cc[i][3] += cd[i][3]; }
}

__device__ __forceinline__ float warp_max(float x) {
    int i = __float_as_int(x);
    i = __reduce_max_sync(0xffffffffu, i ^ ((i >> 31) & 0x7fffffff));
    return __int_as_float(i ^ ((i >> 31) & 0x7fffffff));
}
__device__ __forceinline__ void idle(uint32_t clk) {
    uint32_t t0, t;
    asm volatile("mov.u32 %0, %%clock;" : "=r"(t0) :: "memory");
    do asm volatile("mov.u32 %0, %%clock;" : "=r"(t) :: "memory"); while (t - t0 < clk);
}
__device__ __forceinline__ uint32_t now_ns() { uint32_t t; asm volatile("mov.u32 %0, %%globaltimer_lo;" : "=r"(t)); return t; }
__device__ __forceinline__ int opq(int x) { asm volatile("" : "+r"(x)); return x; }
__device__ __forceinline__ uint32_t opq(uint32_t x) { asm volatile("" : "+r"(x)); return x; }
__device__ __forceinline__ uint32_t pin(uint32_t x) { return __shfl_sync(0xffffffffu, x, threadIdx.x & 31); }
template <typename T> __device__ __forceinline__ T* pin(T* p) {
    const unsigned long long v = (unsigned long long)p;
    return (T*)((unsigned long long)pin((uint32_t)v) | (unsigned long long)pin((uint32_t)(v >> 32)) << 32);
}
template <typename T> __device__ __forceinline__ T* opq(T* p) { asm volatile("" : "+l"(p)); return p; }
__device__ __forceinline__ float4 lds4f(uint32_t a) { float4 v; asm volatile("ld.shared.v4.f32 {%0,%1,%2,%3}, [%4];" : "=f"(v.x), "=f"(v.y), "=f"(v.z), "=f"(v.w) : "r"(a) : "memory"); return v; }
__device__ __forceinline__ float2 lds2f(uint32_t a) { float2 v; asm volatile("ld.shared.v2.f32 {%0,%1}, [%2];" : "=f"(v.x), "=f"(v.y) : "r"(a) : "memory"); return v; }
__device__ __forceinline__ void ln_stats(uint32_t st, float& mean, float& inv) {
    const float4 a = lds4f(st), b = lds4f(st + 16), c = lds4f(st + 32), d = lds4f(st + 48);
    const float s2 = ((a.x + a.z) + (b.x + b.z)) + ((c.x + c.z) + (d.x + d.z));
    const float md = (((a.y + a.w) + (b.y + b.w)) + ((c.y + c.w) + (d.y + d.w))) * (1.0f / DM);
    const float var = fmaxf(s2 * (1.0f / DM) - md * md, 0.f);
    mean = bfr(md);
    asm("rsqrt.approx.ftz.f32 %0, %1;" : "=f"(inv) : "f"(var + 1e-5f));
}
__device__ __forceinline__ void sts32(uint32_t a, float v) { asm volatile("st.shared.f32 [%0], %1;" ::"r"(a), "f"(v) : "memory"); }
__device__ __forceinline__ void sts32p(uint32_t a, float v, uint32_t off) {
    asm volatile("{\n.reg .pred p;\nsetp.eq.u32 p, %2, 0;\n@p st.shared.f32 [%0], %1;\n}" ::"r"(a), "f"(v), "r"(off) : "memory");
}
__device__ __forceinline__ void sts128p(uint32_t a, float x, float y, float z, float w, uint32_t off) {
    asm volatile("{\n.reg .pred p;\nsetp.eq.u32 p, %5, 0;\n@p st.shared.v4.f32 [%0], {%1,%2,%3,%4};\n}" ::"r"(a), "f"(x), "f"(y), "f"(z), "f"(w), "r"(off) : "memory");
}
__device__ __forceinline__ void sts64(uint32_t a, float v, float w) { asm volatile("st.shared.v2.f32 [%0], {%1,%2};" ::"r"(a), "f"(v), "f"(w) : "memory"); }

__device__ __forceinline__ uint32_t prmt(uint32_t a, uint32_t b, uint32_t s) { uint32_t r; asm("prmt.b32 %0, %1, %2, %3;" : "=r"(r) : "r"(a), "r"(b), "r"(s)); return r; }
__device__ __forceinline__ uint32_t bmul2(uint32_t a, uint32_t b) { uint32_t r; asm("mul.rn.bf16x2 %0, %1, %2;" : "=r"(r) : "r"(a), "r"(b)); return r; }
__device__ __forceinline__ void sts128(uint32_t addr, uint32_t a, uint32_t b, uint32_t c, uint32_t d) {
    asm volatile("st.shared.v4.u32 [%0], {%1,%2,%3,%4};" ::"r"(addr), "r"(a), "r"(b), "r"(c), "r"(d) : "memory");
}
__device__ __forceinline__ uint4 ldg128(const uint4* p) {
    uint4 v;
    asm volatile("ld.volatile.global.v4.u32 {%0,%1,%2,%3}, [%4];" : "=r"(v.x), "=r"(v.y), "=r"(v.z), "=r"(v.w) : "l"(p) : "memory");
    return v;
}
__device__ __forceinline__ uint32_t lds32(uint32_t a) { uint32_t v; asm volatile("ld.shared.u32 %0, [%1];" : "=r"(v) : "r"(a) : "memory"); return v; }
__device__ __forceinline__ uint32_t lds16(uint32_t a) { unsigned short v; asm volatile("ld.shared.u16 %0, [%1];" : "=h"(v) : "r"(a) : "memory"); return v; }
__device__ __forceinline__ void unpack8(uint32_t la, uint32_t lb, uint32_t c, uint32_t (&w)[4]) {
    const uint32_t ha = c & 0x87878787u, hb = __funnelshift_l(c, c, 4) & 0x87878787u;
    w[0] = prmt(la, ha, 0x5140); w[1] = prmt(la, ha, 0x7362); w[2] = prmt(lb, hb, 0x5140); w[3] = prmt(lb, hb, 0x7362);
}
__device__ __forceinline__ uint32_t bdiff2(uint32_t y, uint32_t inv, uint32_t x) {
    uint32_t r;
    asm("{\n.reg .b32 n;\nneg.bf16x2 n, %3;\nfma.rn.bf16x2 %0, %1, %2, n;\n}" : "=r"(r) : "r"(y), "r"(inv), "r"(x));
    return r;
}
__device__ __forceinline__ uint32_t pack_scale(uint32_t tile, int lane, uint32_t inv_addr) {
    uint32_t m = 0;
#pragma unroll 1
    for (int k = 0; k < 12; k++) {
        uint32_t a, b, c, d;
        lds128(tile + k * 512 + lane * 16, a, b, c, d);
        asm("max.xorsign.abs.bf16x2 %0, %0, %1;" : "+r"(a) : "r"(b));
        asm("max.xorsign.abs.bf16x2 %0, %0, %1;" : "+r"(c) : "r"(d));
        asm("max.xorsign.abs.bf16x2 %0, %0, %1;" : "+r"(a) : "r"(c));
        asm("max.xorsign.abs.bf16x2 %0, %0, %1;" : "+r"(m) : "r"(a));
    }
    m = __reduce_max_sync(0xffffffffu, max(m & 0x7fffu, (m >> 16) & 0x7fffu));
    const uint32_t inv = (112u + min((m + 0x28u) >> 7, 141u)) * 0x00800080u;
    if (lane == 0) asm volatile("st.shared.u32 [%0], %1;" ::"r"(inv_addr), "r"(inv) : "memory");
    return inv;
}

#define K_OFF(i) ((uint32_t)((3 * ((g >> 1) + 4 * (g & 1)) + ((i) >> 1)) * 128 + ((t ^ ((3 * ((g >> 1) + 4 * (g & 1)) + ((i) >> 1)) & 7) ^ (((i) & 1) << 2)) << 4)))
#define V_OFF(i) ((uint32_t)((6 * t + (i)) * 128 + ((g ^ ((6 * t + (i)) & 7)) << 4)))
template <bool ISV, typename DST>
__device__ __forceinline__ void pack_tile(uint32_t tile, int tau, int nm, uint32_t inv, uint32_t xl, int lane, DST dst) {
    const int g = lane >> 2, t = lane & 3;
    const uint32_t scl = 254u * 0x00800080u - inv;
#pragma unroll 1
    for (int m = 0; m < nm; m++) {
        const int row = ISV ? 6 * t + 2 * m : 3 * ((g >> 1) + 4 * (g & 1)) + m;
        const uint32_t a0 = tile + row * 128 + (((ISV ? g : t) ^ (row & 7)) << 4), a1 = ISV ? (a0 ^ 16) + 128 : a0 ^ 64;
        uint32_t l[8], cw[4], ck = 0, cd = 0;
#pragma unroll
        for (int r = 0; r < 4; r++) {
            uint32_t w0, w1, w2, w3;
            lds128(((r & 1) ? a1 : a0) + (r >> 1) * 3072, w0, w1, w2, w3);
            const uint32_t y0 = bmul2(w0, scl), y1 = bmul2(w1, scl), y2 = bmul2(w2, scl), y3 = bmul2(w3, scl);
            cd |= bdiff2(y0, inv, w0) | bdiff2(y1, inv, w1);
            cd |= bdiff2(y2, inv, w2) | bdiff2(y3, inv, w3);
            const uint32_t ha = prmt(y0, y1, 0x7531), hb = prmt(y2, y3, 0x7531);
            l[2 * r] = prmt(y0, y1, 0x6420); l[2 * r + 1] = prmt(y2, y3, 0x6420);
            asm("lop3.b32 %0, %1, 0x87878787, %2, 0xe2;" : "=r"(cw[r]) : "r"(ha), "r"(__funnelshift_r(hb, hb, 4)));
            ck |= ha | hb;
        }
        const uint32_t bad = __ballot_sync(0xffffffffu, (ck & 0x78787878u) | cd);
        if (bad) {
            const int src = __ffs(bad) - 1;
            const uint32_t b0 = __shfl_sync(0xffffffffu, a0, src), b1 = __shfl_sync(0xffffffffu, a1, src), n0 = lds32(xl);
            const uint32_t ax = ((lane & 8) ? b1 : b0) + (lane >> 4) * 3072 + 2 * (lane & 7), x = lds16(ax), y = bmul2(x, scl);
            const bool out = (y & 0x7800u) | bdiff2(y, inv, x);
            const uint32_t n = n0 + __popc(__ballot_sync(0xffffffffu, out) << (31 - lane)) - 1;
            if (out) {
                asm volatile("st.shared.u16 [%0], %1;" ::"r"(ax), "h"((unsigned short)0) : "memory");
                if (n < XCAP) sts32(xl + 16 + 4 * n, f_(x << 16 | tau << 12 | src << 7 | m << 5 | lane));
            }
            if (lane == 31) sts32(xl, f_(n + 1));
            __syncwarp();
            if (n0 <= XCAP) { m--; continue; }
        }
        uint32_t d[3] = {a0, a1, a0 + 3072};
        dst(m, d);
        sts128(d[0], l[0], l[1], l[2], l[3]);
        sts128(d[1], l[4], l[5], l[6], l[7]);
        sts128(d[2], cw[0], cw[1], cw[2], cw[3]);
    }
}

struct Maps { CUtensorMap k, v, wq, wo, w1, w3, w2, vr; const void* vp; const void* kp; uint32_t zero; };
#define RT_SEL ((wu & 1) ? RT_MASK2 : RT_MASK)
#define PFK 5
#define Q_AT 3
#define WO_T0 33200
#define K5D 250
#define PK_AT 6

__device__ __forceinline__ void load_ffn(const Maps& maps, int b, uint32_t dst, uint32_t bar) {
    const bool gu = b < NG;
    mbar_expect_tx(bar, gu ? 61440 : 49152);
    tma3d(dst, gu ? (b < NG / 2 ? &maps.w1 : &maps.w3) : &maps.w2, gu ? 48 * (b & (NG / 2 - 1)) : 16 * (b - DN0), 0, 0, bar, FFN_POL);
}

__device__ __forceinline__ void load_wo(const Maps& maps, uint32_t dst, int h, int c, uint32_t bar, int nbox) {
#pragma unroll 1
    for (int i = 0; i < nbox; i++) {
        if (!(i & 1)) mbar_expect_tx(bar + 4 * i, i + 1 < nbox ? 20480 : 10240);
        tma3d(dst + i * 10240, &maps.wo, 0, 5 * c, h * DH + 32 * i, bar + 4 * (i & 6), POL_EF);
    }
}

__global__ void __launch_bounds__(NT, 1)
decode_kernel(const __grid_constant__ Maps maps, const __nv_bfloat16* __restrict__ x_in, __nv_bfloat16* __restrict__ out) {
    extern __shared__ __align__(1024) unsigned char smem[];
    const int tid = threadIdx.x, warp = tid >> 5, lane = tid & 31;
    const int wu = __shfl_sync(0xffffffffu, tid >> 5, 0);
    const int b = blockIdx.x, h = b >> 2, c = b & 3;
    const uint32_t sb = smem_u32(smem);
    const uint32_t qbar = sb + SM_BAR + 16 * 8, fbar = qbar + 8, wbar = qbar + 16;
    uint32_t* xs32 = reinterpret_cast<uint32_t*>(smem + SM_XS);
    float* rr = reinterpret_cast<float*>(smem + SM_R);
    float* misc = reinterpret_cast<float*>(smem + SM_MISC);

    PROF_T(0);
    {
        uint2 xv = make_uint2(0u, 0u);
        const uint32_t t_start = now_ns();
        if (elect_one()) {
            const uint32_t rb = sb + SM_BAR + wu * 16, xb = sb + SM_XBAR + wu * 8;
            mbar_init(rb, 1); mbar_init(rb + 8, 1); mbar_init(xb, 1);
            if (wu == 0) mbar_init(qbar, 1);
            asm volatile("fence.mbarrier_init.release.cluster;" ::: "memory");
            const int row = (h * SK + (SK - WIN) + c * 1024 + wu * 128) * 3;
            const uint32_t ring = sb + SM_RING + wu * 2 * TILE;
#pragma unroll
            for (int n = 0; n < 3; n++) {
                const uint32_t bar = ((IN_S1 >> n) & 1) ? rb + 8 : ((IN_S0 >> n) & 1) ? rb : xb;
                mbar_expect_tx(bar, TILE);
                tma2d(((IN_S1 >> n) & 1) ? ring + TILE : ((IN_S0 >> n) & 1) ? ring : sb + SM_B + wu * TILE, &maps.k, 0, row + 48 * n, bar, POL_EF);
                if (n == 0 && wu == 0) {
                    mbar_expect_tx(qbar, 61440);
                    tma3d(sb + SM_Q, &maps.wq, 0, 160 * c, 3 * h, qbar, POL_EF);
                }
            }
            if (wu == 1) {
                mbar_init(fbar, 1);
#pragma unroll
                for (int i = 0; i < 3; i++) mbar_init(wbar + 8 * i, 1);
                asm volatile("fence.mbarrier_init.release.cluster;" ::: "memory");
            }
            if (wu >= 2) {
                const CUtensorMap* mp = wu == 2 ? &maps.v : wu == 3 ? &maps.wo : wu == 4 ? &maps.w1 : wu == 5 ? &maps.w3 : wu == 6 ? &maps.w2 : &maps.vr;
                asm volatile("prefetch.tensormap [%0];" ::"l"(mp) : "memory");
            }
        }
        if (tid < 160) asm volatile("ld.global.nc.v2.u32 {%0,%1}, [%2];" : "=r"(xv.x), "=r"(xv.y) : "l"(x_in + 4 * tid) : "memory");
        if (tid == 96) { misc[2] = 0.f; misc[3] = 0.f; }
        if (lane == 1) *reinterpret_cast<uint2*>(smem + SM_XL + warp * XSTR) = make_uint2(0u, t_start + WO_T0);
        if (tid >= 128 && tid < 148) {
            const uint32_t v = tid < 138 ? ONES : 0u;
            reinterpret_cast<uint4*>(smem + SM_ONE)[tid - 128] = make_uint4(v, v, v, v);
        }
        if (tid < 160) { xs32[xpos(2 * tid)] = xv.x; xs32[xpos(2 * tid + 1)] = xv.y; }
        __syncthreads();
        PROF_T(14);
        if (b == 0 && tid >= 232) asm volatile("st.relaxed.gpu.global.u32 [%0], %1;" ::"l"(g_scr.ticket + tid - 232), "r"(0) : "memory");
        if (tid == 64 || (tid == 65 && b < 216 - NCTA)) st_pkt(&g_scr.acc[1][(b + NCTA * (tid - 64))], 0, 0, 0, 0);
    }

    uint32_t kq[NQ][4];
    const float SC = 0.07216878364870322f * 1.4426950408889634f;

#pragma unroll 1
    for (int ph = 0; ph < 3; ph++) {
        const int layer = ph >> 1;
        const uint32_t tag = layer + 1;
        PROF_T(1 + layer * 16);
        if (ph) {
        {
            const int tl = opq(tid), warp = tl >> 5, lane = tl & 31, g = lane >> 2, t = lane & 3, mat = lane >> 3, r8 = lane & 7;
            const int kh = warp >> 2, mg = warp & 3;
            uint32_t aq[3];
#pragma unroll
            for (int i = 0; i < 3; i++) {
                const int ch = 6 * mg + 2 * i + (mat & 1);
                aq[i] = sb + SM_Q + (80 * kh + (mat >> 1) * 8 + r8) * 128 + (ch >> 3) * 20480 + (((ch & 7) ^ r8) << 4);
            }
#define PF_K5 if (layer == 1 && PFK) tile_keep(&maps.k, (h * SK + (SK - WIN) + c * 1024 + wu * 128 + PFK * 16) * 3);
            uint2 xv = make_uint2(0u, 0u);
            mbar_wait(qbar, 0);
            uint32_t pre[6][4];
#pragma unroll
            for (int n = 0; n < 6; n++) ldsm4t(aq[n % 3] + (n / 3) * 2048, pre[n]);
            if (layer == 1) {
                __syncthreads();
                if (elect_one()) {
                    const uint32_t bar = sb + SM_BAR + wu * 16;
                    asm volatile("mbarrier.expect_tx.relaxed.cta.shared::cta.b64 [%0], 1536;" ::"r"(bar) : "memory");
#pragma unroll
                    for (int k = 0; k < 3; k++)
                        tma2d(sb + SM_Q + v1_pos(3 * wu + k), &maps.vr, 0, (h * SK + (SK - WIN) + c * 1024 + wu * 128) / 2 + 8 + 2 * k, bar, POL_EF);
                }
            }
            const uint32_t pm = opq(g == 1 ? sb + SM_ONE : sb + SM_XS + 160 * (2 * c + kh) + 16 * t), pm2 = opq(pm + 128 - (g == 1 ? 0 : 8 * t));
            const uint32_t dq = opq(sb + SM_R + 8 * (kh * 192 + 48 * mg + g)), ds = opq(sb + SM_ST + 8 * warp + (lane < 16 ? 4 : 0));
            const bool wr = t == 0, ws = (lane & 15) == 0, lo = lane < 16;
            if (wu < 5) {
                const int p0 = xpos(2 * tl), p1 = xpos(2 * tl + 1);
                if (layer == 1) {
                    uint4 v;
                    for (int it = 0; it < SPIN_CAP; it++) { v = ld_pkt(&g_scr.ay[tl]); if (__all_sync(0xffffffffu, v.w == 1)) break; }
                    xv = make_uint2(v.x, v.y);
                    xs32[p0] = xv.x; xs32[p1] = xv.y;
                } else xv = make_uint2(xs32[p0], xs32[p1]);
            }
            if (layer) PC(24);
            __syncthreads();
            PF_K5
            if (layer) PC(25);
            PROF_T(13 + layer * 16);
            const float e0 = bf_lo(xv.x), e1 = bf_hi(xv.x), e2 = bf_lo(xv.y), e3 = bf_hi(xv.y);
            const float s1 = (e0 + e1) + (e2 + e3), s2 = (e0 * e0 + e1 * e1) + (e2 * e2 + e3 * e3);
            float sv = lo ? s1 : s2, cc[3][4];
            gemv15<2048>(cc, pre, [&](int i) { return aq[i]; }, pm, pm2, sv, lo ? s2 : s1);
            if (wr) {
#pragma unroll
                for (int i = 0; i < 3; i++) { sts64(dq + 128 * i, cc[i][0], cc[i][1]); sts64(dq + 128 * i + 64, cc[i][2], cc[i][3]); }
            }
            if (ws) sts32(ds, sv);
        }
        const uint32_t pa = opq(sb + SM_R + 32 * opq(tid)), st = opq(sb + SM_ST);
        uint4* const pq = opq(&g_scr.hx[b * 48 + opq(tid)]);
        if (layer) PC(26);
        __syncthreads();
        if (layer) PC(27);
        PROF_T(33 + layer * 16);
        if (wu < 2) {
            float mean, inv;
            ln_stats(st, mean, inv);
            const float4 a0 = lds4f(pa), a1 = lds4f(pa + 16), b0 = lds4f(pa + 1536), b1 = lds4f(pa + 1552);
            const float q0 = (a0.x + b0.x) - mean * (a0.y + b0.y), q1 = (a0.z + b0.z) - mean * (a0.w + b0.w);
            const float q2 = (a1.x + b1.x) - mean * (a1.y + b1.y), q3 = (a1.z + b1.z) - mean * (a1.w + b1.w);
            st_pktfp(pq, q0, q1, q2, q3, 1, tid < 48);
        }
        if (layer == 1 && tid >= 192 && tid < 194 && b < 108) st_pkt(&g_scr.acc[0][(2 * b + opq(tid) - 192)], 0, 0, 0, 0);
        }
        if (layer) PC(28);
        if (layer == 1 && (wu & 2)) {
            idle(K5D);
            tile_load(sb + SM_Q + c_slot(wu), &maps.k, (h * SK + (SK - WIN) + c * 1024 + wu * 128 + 5 * 16) * 3, sb + SM_XBAR + wu * 8, 0, 0);
        }

        float sc0 = -INFINITY, sc1 = -INFINITY, sc2 = 0.f, sc3 = 0.f, mw;
        uint32_t pk0, pk1;
        float acc[3][4];
        {
            const uint32_t ring = sb + SM_RING + wu * 2 * TILE, rb = sb + SM_BAR + wu * 16;
            const uint32_t xtile = sb + SM_Q + c_slot(wu), xb = sb + SM_XBAR + wu * 8;
#define V_SEQ(n) ((int)(SEQ1 >> (4 * (n))) & 7)
#define SLOT1(n) (((IN_S1 >> (n)) & 1) ? ring + TILE : ((IN_S0 >> (n)) & 1) ? ring : sb + SM_B + wu * TILE)
#define BAR1(n) (((IN_S1 >> (n)) & 1) ? rb + 8 : ((IN_S0 >> (n)) & 1) ? rb : xb)
#define PAR1(n) ((PARITY1 >> (n)) & 1)
#define PAR2(n) ((PARITY2 >> (n)) & 1)
            const int row0 = (h * SK + (SK - WIN) + c * 1024 + wu * 128) * 3;
            auto issue1 = [&](int n, uint32_t dep, bool vph = false) {
                const CUtensorMap* mp = n < 8 ? &maps.k : &maps.v;
                const int tl = V_SEQ(n), row = row0 + tl * 48;
                const uint32_t dst = SLOT1(n), bar = BAR1(n);
                if (vph && wu < L1R && tl == 7 - (wu & 1)) {
                    tile_load_l1(dst, maps.vp, row, bar, opq(tid) & 31);
                    return;
                }
                tile_load(dst, mp, row, bar, dep, maps.zero);
                if ((RT_SEL >> (tl + (n & 8))) & 1) {
                    if (n != V0_AT + 1) tile_keep(mp, row);
                    else if ((opq(tid) & 31) < 8)
                        asm volatile("cp.async.bulk.prefetch.L2.global.L2::cache_hint [%0], 256, %1;"
                                     ::"l"(static_cast<const char*>(maps.vp) + (size_t)(row + 4 + 6 * (opq(tid) & 31)) * 128), "l"(POL_EN) : "memory");
                }
            };
            auto refill1 = [&](int s, uint32_t dep, bool vph = false) { issue1(s + (!vph || s < V0_AT ? 3 : 2), dep, vph); };
#define LANE_IDS const int tl = opq(tid), lane = tl & 31, g = lane >> 2, t = lane & 3; (void)tl; (void)lane; (void)g; (void)t;
            const uint32_t xl = sb + SM_XL + wu * XSTR;
            if (layer == 0) {
#pragma unroll 1
                for (int s = ph ? Q_AT : 0; s < (ph ? 5 : Q_AT); s++) {
                    LANE_IDS
                    const uint32_t tile = SLOT1(s);
                    mbar_wait(BAR1(s), PAR1(s));
                    const uint32_t scl = s == 0 ? pack_scale(tile, lane, xl + 8) : lds32(xl + 8);
                    pack_tile<false>(tile, s, 3, scl, xl, lane, [](int, uint32_t (&)[3]) {});
#pragma unroll
                    for (int n = 0; n < 5; n++) {
                        if (s == n) {
#pragma unroll
                            for (int m = 0; m < 3; m++) {
                                const uint32_t a = tile + K_OFF(2 * m);
                                lds128(a, kq[9 * n + 3 * m][0], kq[9 * n + 3 * m][1], kq[9 * n + 3 * m][2], kq[9 * n + 3 * m][3]);
                                lds128(a ^ 64, kq[9 * n + 3 * m + 1][0], kq[9 * n + 3 * m + 1][1], kq[9 * n + 3 * m + 1][2], kq[9 * n + 3 * m + 1][3]);
                                lds128(a + 3072, kq[9 * n + 3 * m + 2][0], kq[9 * n + 3 * m + 2][1], kq[9 * n + 3 * m + 2][2], kq[9 * n + 3 * m + 2][3]);
                            }
                        }
                    }
                    __syncwarp();
                    refill1(s, lds32(tile));
                }
                if (!ph) continue;
            }
            {
                if (wu < 2) {
                    const int tl = min(opq(tid), 47);
                    const int w = 2 * tl;
                    const uint32_t pos = opq(sb + SM_QS + 4 * (((w >> 2) & 3) * 24 + 2 * (w >> 4) + ((w >> 1) & 1)));
                    uint4 v[4];
                    float mean, inv;
                    ln_stats(opq(sb + SM_ST), mean, inv);
                    for (int it = 0; it < SPIN_CAP; it++) {
#pragma unroll
                        for (int k = 0; k < 4; k++) v[k] = ld_pkt(&g_scr.hx[(h * 4 + k) * 48 + tl]);
                        if (all_odd(v[0].w, v[1].w, v[2].w, v[3].w)) break;
                    }
                    sts32(pos, f_(pack2(inv * ((f_(v[0].x) + f_(v[1].x)) + (f_(v[2].x) + f_(v[3].x))), inv * ((f_(v[0].y) + f_(v[1].y)) + (f_(v[2].y) + f_(v[3].y))))));
                    sts32(pos + 48, f_(pack2(inv * ((f_(v[0].z) + f_(v[1].z)) + (f_(v[2].z) + f_(v[3].z))), inv * ((f_(v[0].w) + f_(v[1].w)) + (f_(v[2].w) + f_(v[3].w))))));
                }
            }
            if (layer) PC(29);
            __syncthreads();
            if (layer) PC(30);
            PROF_T(2 + layer * 16);
#define V1_REST(p) ((p) < 6 ? sb + SM_Q + v1_pos(3 * wu + ((p) >> 1)) + 256 * ((p) & 1) : ((sb + SM_R + wu * 784 + 127) & ~127u) - 1536 + 256 * (p))
#define V1_LOAD(bar) if (elect_one()) tma2d(V1_REST(6), &maps.vr, 0, row0 / 6 + 14, bar, POL_EF);
#define V1_EXPECT(bar) { if ((opq(tid) & 31) == 0) asm volatile("mbarrier.expect_tx.relaxed.cta.shared::cta.b64 [%0], 512;" ::"r"(bar) : "memory"); }
            if (layer == 1 && !(wu & 2)) tile_load(xtile, &maps.k, row0 + 5 * 48, xb, 0, 0);
            if (layer == 1 && wu >= 4) idle(STAG);
            {
                uint32_t qf[12];
                int t;
                {
                    const int lane = opq(tid) & 31;
                    t = lane & 3;
                    const uint32_t qa = sb + SM_QS + (2 * t + ((lane >> 2) & 1)) * 48;
#pragma unroll
                    for (int i = 0; i < 3; i++) lds128(qa + 16 * i, qf[4 * i], qf[4 * i + 1], qf[4 * i + 2], qf[4 * i + 3]);
                }
                const uint32_t sq = lds32(xl + 8) - 64u * 0x00800080u;
#pragma unroll
                for (int i = 0; i < 12; i++) qf[i] = bmul2(qf[i], sq);
#define KR_STEP(tau, m) \
                    _Pragma("unroll") for (int i = 2 * (m); i < 2 * (m) + 2; i++) { \
                        const int q0 = 9 * tau + 3 * (i >> 1), r = i & 1; \
                        uint32_t w[4]; \
                        unpack8(kq[q0][2 * r], kq[q0][2 * r + 1], kq[q0 + 2][r], w); \
                        mma16816(cA, w[0], w[1], w[2], w[3], qf[2 * i], qf[2 * i + 1]); \
                        unpack8(kq[q0 + 1][2 * r], kq[q0 + 1][2 * r + 1], kq[q0 + 2][2 + r], w); \
                        mma16816(cB, w[0], w[1], w[2], w[3], qf[2 * i], qf[2 * i + 1]); \
                    }
#define KR_BEGIN float cA[4] = {0.f, 0.f, 0.f, 0.f}, cB[4] = {0.f, 0.f, 0.f, 0.f};
#define KR_END(tau) \
                    const float sA = (cA[0] + cA[3]) * 18446744073709551616.f, sB = (cB[0] + cB[3]) * 18446744073709551616.f; \
                    if (t == (tau & 3)) { if (tau < 4) { sc0 = sA; sc1 = sB; } else { sc2 = sA; sc3 = sB; } }
#define KR_SCORES(tau) { KR_BEGIN KR_STEP(tau, 0) KR_STEP(tau, 1) KR_STEP(tau, 2) KR_END(tau) }
                uint32_t va[3];
                {
                    const int lane = opq(tid) & 31, g = lane >> 2, t = lane & 3;
#pragma unroll
                    for (int i = 0; i < 3; i++) va[i] = ring + V_OFF(2 * i);
                }
#define V_STG(n) _Pragma("unroll") for (int j = 3 * (n); j < 3 * (n) + 3; j++) { \
                    const int i = (j % 12) >> 1; \
                    lds128p(((i & 1) ? (va[i >> 1] ^ 16) + 128 : va[i >> 1]) + (j / 12) * TILE + (j & 1) * 3072, layer, kq[j][0], kq[j][1], kq[j][2], kq[j][3]); }
                uint32_t dep = 0;
                {
                    KR_BEGIN
                    KR_STEP(0, 0) V_STG(0) KR_STEP(0, 1) V_STG(1) KR_STEP(0, 2) V_STG(2)
                    KR_END(0)
                }
                {
                    KR_BEGIN
                    KR_STEP(1, 0) V_STG(3)
                    __syncwarp();
                    dep = lds32(ring);
                    if (layer == 1) tile_load(ring, &maps.k, row0 + 6 * 48, rb, dep, maps.zero);
                    KR_STEP(1, 1) V_STG(4) KR_STEP(1, 2) V_STG(5)
                    KR_END(1)
                }
                {
                    KR_BEGIN
                    KR_STEP(2, 0) V_STG(6) KR_STEP(2, 1) V_STG(7)
                    __syncwarp();
                    dep = lds32(ring + TILE);
                    KR_STEP(2, 2)
                    if (layer == 1) {
                        V1_EXPECT(rb + 8)
                        tile_load(ring + TILE, &maps.k, row0 + 7 * 48, rb + 8, dep, maps.zero);
                        V1_LOAD(rb + 8)
                    }
                    KR_END(2)
                }
#pragma unroll 1
                for (int s = 5; s < 8; s++) {
                    {
                        LANE_IDS
                        const uint32_t tile = !layer ? SLOT1(s) : s == 5 ? xtile : ring + (s - 6) * TILE, tb = !layer ? BAR1(s) : s == 5 ? xb : rb + (s - 6) * 8;
                        const float ur = f_((318u << 23) - (lds32(xl + 8) << 16));
                        mbar_wait(tb, layer ? PAR2(s - 5) : PAR1(s));
                        if (layer) PROF_T(29 + s);
                        float cA[4] = {0.f, 0.f, 0.f, 0.f}, cB[4] = {0.f, 0.f, 0.f, 0.f};
#pragma unroll
                        for (int i = 0; i < 6; i++) {
                            uint32_t a0, a1, a2, a3;
                            lds128(tile + K_OFF(i), a0, a1, a2, a3);
                            mma16816(cA, a0, a1, a2, a3, qf[2 * i], qf[2 * i + 1]);
                            lds128(tile + K_OFF(i) + 3072, a0, a1, a2, a3);
                            mma16816(cB, a0, a1, a2, a3, qf[2 * i], qf[2 * i + 1]);
                        }
                        __syncwarp();
                        const uint32_t last = lds32(tile);
                        if (layer) tile_load(tile, &maps.v, row0 + (s - 2) * 48, tb, last, maps.zero);
                        else refill1(s, last);
                        if (t == (s & 3)) { sc2 = (cA[0] + cA[3]) * ur; sc3 = (cB[0] + cB[3]) * ur; }
                    }
                    if (s == 5) KR_SCORES(3)
                    if (s == 6) {
                        KR_SCORES(4)
                        const int lane = opq(tid) & 31;
                        const uint32_t nx = min(lds32(xl), (uint32_t)XCAP);
#pragma unroll 1
                        for (uint32_t n = 0; n < nx; n++) {
                            const uint32_t id = lds32(xl + 16 + 4 * n);
                            const uint32_t qo = 96 * ((id >> 7) & 3) + 48 * ((id >> 1) & 1) + 16 * ((id >> 5) & 3) + (id & 12) + 2 * (id & 1);
                            const float cr = bf_hi(id) * f_(lds16(sb + SM_QS + qo) << 16);
                            const int d = (int)(16 * ((id >> 9) & 7) + 4 * ((id >> 12) & 3) + ((id >> 13) & 2) + ((id >> 4) & 1) + ((id >> 8) & 128)) - 4 * lane;
                            if (d == 0) sc0 += cr;
                            if (d == 1) sc1 += cr;
                            if (d == 2) sc2 += cr;
                            if (d == 3) sc3 += cr;
                        }
                    }
                }
#undef KR_SCORES
#undef KR_STEP
#undef KR_BEGIN
#undef KR_END
#undef V_STG
                {
                    LANE_IDS
                    if (lds32(xl) > XCAP || !__all_sync(0xffffffffu, (fabsf(sc0) + fabsf(sc1)) + (fabsf(sc2) + fabsf(sc3)) < INFINITY)) {
                        const uint32_t qa = sb + SM_QS + (2 * t + (g & 1)) * 48;
#pragma unroll
                        for (int i = 0; i < 3; i++) lds128(qa + 16 * i, qf[4 * i], qf[4 * i + 1], qf[4 * i + 2], qf[4 * i + 3]);
                        const uint4* kg = reinterpret_cast<const uint4*>(static_cast<const char*>(maps.kp) + (size_t)row0 * 128) + ((g >> 1) + 4 * (g & 1)) * 24 + t;
#pragma unroll 1
                        for (int s = 0; s < 8; s++) {
                            float cA[4] = {0.f, 0.f, 0.f, 0.f}, cB[4] = {0.f, 0.f, 0.f, 0.f};
#pragma unroll
                            for (int i = 0; i < 6; i++) {
                                uint4 u = ldg128(kg + s * 384 + 4 * i);
                                mma16816v(cA, u.x, u.y, u.z, u.w, qf[2 * i], qf[2 * i + 1]);
                                u = ldg128(kg + s * 384 + 4 * i + 192);
                                mma16816v(cB, u.x, u.y, u.z, u.w, qf[2 * i], qf[2 * i + 1]);
                            }
                            if (t == s) { sc0 = cA[0] + cA[3]; sc1 = cB[0] + cB[3]; }
                            if (t + 4 == s) { sc2 = cA[0] + cA[3]; sc3 = cB[0] + cB[3]; }
                        }
                    }
                }
            }
            mw = warp_max(fmaxf(fmaxf(sc0, sc1), fmaxf(sc2, sc3)));
            pk0 = pack2(ex2((sc0 - mw) * SC), ex2((sc1 - mw) * SC));
            pk1 = pack2(ex2((sc2 - mw) * SC), ex2((sc3 - mw) * SC));
            sc2 = (bf_lo(pk0) + bf_hi(pk0)) + (bf_lo(pk1) + bf_hi(pk1));
            sc2 = (float)__reduce_add_sync(0xffffffffu, __float2uint_rn(sc2 * 16777216.f)) * (1.0f / 16777216.f);
            if ((opq(tid) & 31) == 0) st_pkt2(&g_scr.mx[h * 32 + c * 8 + wu], __float_as_uint(mw), (__float_as_uint(sc2) & ~3u) | tag);
            auto head_factor = [&]() {
                const int lane = opq(tid) & 31;
                int it = 0;
                while (!__all_sync(0xffffffffu, (__float_as_uint(sc1) & 3u) == tag) && ++it < SPIN_CAP) {
                    const uint2 mv = ld_pkt2(&g_scr.mx[h * 32 + lane]); sc0 = f_(mv.x); sc1 = f_(mv.y);
                }
                const float e = ex2((sc0 - warp_max(sc0)) * SC);
                const uint32_t d = __reduce_add_sync(0xffffffffu, __float2uint_rn(sc1 * e * 524288.f));
                sc3 = __shfl_sync(0xffffffffu, e, c * 8 + wu) * 524288.f * rcp((float)d);
            };
#pragma unroll
            for (int s = 0; s < 3; s++) { acc[s][0] = acc[s][1] = acc[s][2] = acc[s][3] = 0.f; }
#define P_CONSTS \
                const uint32_t sel0 = g == 0 ? 0x4410u : (g == 1 ? 0x1044u : 0x4444u); \
                const uint32_t sel1 = g == 2 ? 0x4410u : (g == 3 ? 0x1044u : 0x4444u); \
                const int src00 = 4 * (t < 2 ? 4 * t : 4 * (t - 2) + 1);
#define P_FRAGS(tau) \
                const uint32_t pk = ((tau) & 4) ? pk1 : pk0; \
                const uint32_t w0 = __shfl_sync(0xffffffffu, pk, src00 + ((tau) & 3)); \
                const uint32_t w1 = __shfl_sync(0xffffffffu, pk, src00 + ((tau) & 3) + 8); \
                uint32_t pb[4][2]; \
                _Pragma("unroll") for (int j = 0; j < 4; j++) { \
                    const uint32_t src = ((j & 1) ? w1 : w0) >> ((j >> 1) * 16); \
                    pb[j][0] = __byte_perm(src, 0, sel0); pb[j][1] = __byte_perm(src, 0, sel1); \
                }
            if (layer == 0) {
#pragma unroll 1
                for (int s = 8; s < 16; s++) {
                    LANE_IDS
                    P_CONSTS
                    if (s == 13) { const uint2 mv = ld_pkt2(&g_scr.mx[h * 32 + lane]); sc0 = f_(mv.x); sc1 = f_(mv.y); }
                    P_FRAGS(V_SEQ(s))
                    mbar_wait(BAR1(s), PAR1(s));
                    const uint32_t tile = SLOT1(s);
#pragma unroll
                    for (int j = 0; j < 4; j++) {
#pragma unroll
                        for (int u = 0; u < 3; u++) {
                            uint32_t a0, a1, a2, a3;
                            lds128(tile + (j >> 1) * 3072 + V_OFF(3 * (j & 1) + u), a0, a1, a2, a3);
                            mma16816(acc[u], a0, a1, a2, a3, pb[j][0], pb[j][1]);

                        }
                    }
                    __syncwarp();
                    if (s < V0_AT || (s > V0_AT + 1 && s < 14)) refill1(s, lds32(tile), true);
                    if (s == V0_AT || s == V0_AT + 1) {
                        {
                            const uint32_t ar = sb + SM_R + wu * 784 + 32 * g + 16 * t;
                            if (t < 2) {
#pragma unroll
                                for (int u = 0; u < 3; u++) sts128(ar + 256 * u, __float_as_uint(acc[u][0]), __float_as_uint(acc[u][1]), __float_as_uint(acc[u][2]), __float_as_uint(acc[u][3]));
                            }
                        }
                        const uint32_t scl = s == V0_AT ? pack_scale(tile, lane, xl + 12) : lds32(xl + 12);
                        pack_tile<true>(tile, s + 8 - V0_AT, V0_AT + 3 - s, scl, xl, lane, [&](int m, uint32_t (&d)[3]) {
                            if (s != V0_AT && m == 0) {
#pragma unroll
                                for (int k = 0; k < 3; k++) d[k] = ring + 3072 + V_OFF(2 * k + 1);
                            }
                        });
                        if (s != V0_AT) {
                            lds128(tile + V_OFF(2), kq[45][0], kq[45][1], kq[45][2], kq[45][3]);
                            lds128(tile + V_OFF(3), kq[46][0], kq[46][1], kq[46][2], kq[46][3]);
                            lds128(tile + V_OFF(2) + 3072, kq[47][0], kq[47][1], kq[47][2], kq[47][3]);
                            __syncwarp();
                            issue1(V0_AT + 3, lds32(tile));
                        }
                        const int ln = opq(tid) & 31;
                        const uint32_t ar = sb + SM_R + wu * 784 + 8 * (ln & 28) + 16 * (ln & 1);
#pragma unroll
                        for (int u = 0; u < 3; u++) {
                            uint32_t a0, a1, a2, a3;
                            lds128(ar + 256 * u, a0, a1, a2, a3);
                            acc[u][0] = f_(a0); acc[u][1] = f_(a1); acc[u][2] = f_(a2); acc[u][3] = f_(a3);
                        }
                    }
                    if (s == 13) head_factor();
                    if (s >= 14 && elect_one()) {
                        if (atomicAdd(reinterpret_cast<unsigned*>(misc + 3), 1u) == 14u && (int)(now_ns() - lds32(xl + 4)) >= 0) {
                            PROF_X(47);
                            load_wo(maps, sb + SM_B, h, c, wbar, 6);
                            atomicAdd(reinterpret_cast<unsigned*>(misc + 3), 256u);
                        }
                    }
                }
            } else {
                LANE_IDS
                P_CONSTS
#pragma unroll
                for (int k = 0; k < 4; k++) lds128(V1_REST(t + 4 * (k >> 1)) + 16 * g + 128 * (k & 1), kq[36 + k][0], kq[36 + k][1], kq[36 + k][2], kq[36 + k][3]);
#pragma unroll 1
                for (int i = 3; i < 8; i++) {
                    const uint32_t tile = i > 3 ? ring + (i & 1) * TILE : xtile, tb = i > 3 ? rb + (i & 1) * 8 : xb;
                    if (i == 6) { const uint2 mv = ld_pkt2(&g_scr.mx[h * 32 + lane]); sc0 = f_(mv.x); sc1 = f_(mv.y); }
                    if (i == 7) head_factor();
                    if (i == PK_AT) {
                uint32_t nx, nk, ik, iv;
                lds128(xl, nx, nk, ik, iv);
                if (nx <= XCAP) {
                    const uint32_t pks = bmul2(pk0, iv);
#pragma unroll
                    for (int s = 0; s < 2; s++) {
                        const uint32_t pk1 = 0, pk0 = pks;
                        P_FRAGS(s)
#pragma unroll
                        for (int j = 0; j < 4; j++) {
#pragma unroll
                            for (int u = 0; u < 3; u++) {
                                const int i = 3 * (j & 1) + u, m = i >> 1, r = i & 1, hf = j >> 1;
                                if (s == 1 && m == 2) continue;
                                const int ql = s == 0 ? 4 * m + 2 * hf : m == 0 ? 3 + 4 * hf : 45 + hf, qc = s == 0 ? 4 * m + 1 : m == 0 ? 11 : 47;
                                uint32_t w[4];
                                unpack8(kq[ql][2 * r], kq[ql][2 * r + 1], kq[qc][2 * hf + r], w);
                                mma16816(acc[u], w[0], w[1], w[2], w[3], pb[j][0], pb[j][1]);
                            }
                        }
                    }
#pragma unroll 1
                    for (uint32_t n = 0; n < nx; n++) {
                        const uint32_t id = lds32(xl + 16 + 4 * n);
                        const int i = ((id >> 4) & 6) + ((id >> 3) & 1), key = ((id >> 6) & 6) + (i >= 3);
                        const uint32_t pw = __shfl_sync(0xffffffffu, pk0, 8 * (key & 3) + (key & 4) + ((id >> 12) & 3));
                        const float cr = bf_hi(id) * ((id & 16) ? bf_hi(pw) : bf_lo(pw));
                        const int d = (int)(64 * ((id >> 9) & 7) + 4 * (id & 4) + 4 * (i >= 3 ? i - 3 : i) + (id & 3) + ((~id >> 5) & 1024)) - 16 * lane;
#pragma unroll
                        for (int k = 0; k < 12; k++) if (d == k) acc[k >> 2][k & 3] += cr;
                    }
                } else {
                    const uint4* vg = reinterpret_cast<const uint4*>(static_cast<const char*>(maps.vp) + (size_t)row0 * 128) + 48 * t + g;
#pragma unroll 1
                    for (int s = 0; s < 2; s++) {
                        P_FRAGS(s)
#pragma unroll
                        for (int j = 0; j < 4; j++) {
#pragma unroll
                            for (int u = 0; u < 3; u++) {
                                if (s == 1 && (j & 1) && u) continue;
                                const uint4 w = ldg128(vg + 384 * s + 192 * (j >> 1) + 24 * (j & 1) + 8 * u);
                                mma16816v(acc[u], w.x, w.y, w.z, w.w, pb[j][0], pb[j][1]);
                            }
                        }
                    }
                }
#pragma unroll
                for (int s = 2; s > 0; s--) {
                    P_FRAGS(s)
#pragma unroll
                    for (int j = 0; j < 4; j++) {
#pragma unroll
                        for (int u = 0; u < 3; u++) {
                            if (s == 1 && !((j & 1) && u)) continue;
                            const int k = s == 2 ? 12 + 2 * (3 * (j & 1) + u) + (j >> 1) : 35 + (j >> 1) * 2 + u;
                            mma16816(acc[u], kq[k][0], kq[k][1], kq[k][2], kq[k][3], pb[j][0], pb[j][1]);
                        }
                    }
                }
                    }
                    P_FRAGS(i)
                    mbar_wait(tb, PAR2(i));
                    PROF_T(34 + i);
#pragma unroll
                    for (int k = 0; k < 6; k++) {
                        const uint32_t a = tile + V_OFF(k);
                        lds128(a, kq[24 + k][0], kq[24 + k][1], kq[24 + k][2], kq[24 + k][3]);
                        lds128(a + 3072, kq[30 + k][0], kq[30 + k][1], kq[30 + k][2], kq[30 + k][3]);
                    }
#pragma unroll
                    for (int j = 0; j < 4; j++) {
#pragma unroll
                        for (int u = 0; u < 3; u++) {
                            const int k = 24 + 6 * (j >> 1) + 3 * (j & 1) + u;
                            mma16816(acc[u], kq[k][0], kq[k][1], kq[k][2], kq[k][3], pb[j][0], pb[j][1]);
                        }
                    }
                    __syncwarp();
                    if (wu < L1R && i == 5 - (wu & 1)) tile_load_l1(tile, maps.vp, row0 + (i + 2) * 48, tb, lane);
                    else if (i == 4 || i == 5) tile_load(tile, &maps.v, row0 + (i + 2) * 48, tb, lds32(tile), maps.zero);
                    if (i == WO_AT1 && HAS_FFN && elect_one()) {
                        if (atomicAdd(reinterpret_cast<unsigned*>(misc + 2), 1u) == 7u) {
                            PROF_X(63);
                            load_wo(maps, sb + SM_Q, h, c, wbar, KEEP4 && __float_as_uint(misc[1]) >= DN0 ? 5 : 6);
                        }
                    }
                }
            }
#undef P_FRAGS
#undef P_CONSTS
#undef LANE_IDS
        }
        PROF_T(3 + layer * 16);
        PC(layer * 32 + 1);

        {
            const int lane = opq(tid) & 31;
            const uint32_t a = sb + SM_R + wu * 784 + 8 * (lane & 28) + 16 * (lane & 1);
#pragma unroll
            for (int u = 0; u < 3; u++) sts128p(a + 256 * u, acc[u][0] * sc3, acc[u][1] * sc3, acc[u][2] * sc3, acc[u][3] * sc3, lane & 2);
        }
        const uint32_t role1 = layer ? lds32(sb + SM_MISC + 4) : DN0 + NDN;
        const uint32_t pc = opq(sb + SM_R + 16 * opq(tid));
        uint4* const px0 = opq(&g_scr.hx[b * 48 + opq(tid)]);
        __syncthreads();
        PROF_T(4 + layer * 16);
        PC(layer * 32 + 2);
        float4 o = make_float4(0.f, 0.f, 0.f, 0.f);
        if (wu < 2) {
            float4 v[8];
#pragma unroll
            for (int w = 0; w < 8; w++) v[w] = lds4f(pc + w * 784);
            o.x = ((v[0].x + v[1].x) + (v[2].x + v[3].x)) + ((v[4].x + v[5].x) + (v[6].x + v[7].x));
            o.y = ((v[0].y + v[1].y) + (v[2].y + v[3].y)) + ((v[4].y + v[5].y) + (v[6].y + v[7].y));
            o.z = ((v[0].z + v[1].z) + (v[2].z + v[3].z)) + ((v[4].z + v[5].z) + (v[6].z + v[7].z));
            o.w = ((v[0].w + v[1].w) + (v[2].w + v[3].w)) + ((v[4].w + v[5].w) + (v[6].w + v[7].w));
            o.w = f_(__float_as_uint(o.w) & ~1u);
            st_pktp(px0, __float_as_uint(o.x), __float_as_uint(o.y), __float_as_uint(o.z), __float_as_uint(o.w), threadIdx.x < 48);
        }
        uint32_t ticket = 0;
        if (layer == 0 && tid == 224)
            asm volatile("atom.relaxed.gpu.global.inc.u32 %0, [%1], 0x7fffffff;" : "=r"(ticket) : "l"(g_scr.ticket + 8 + (b >> 3)) : "memory");
        if (layer == 0 && tid == 224 && lds32(sb + SM_MISC + 12) < 256u) {
            int it = 0;
            while ((int)(now_ns() - lds32(sb + SM_XL + 4)) < 0 && ++it < SPIN_CAP) {}
            PROF_X(47);
            load_wo(maps, sb + SM_B, h, c, wbar, 6);
        }
        uint32_t pr;
        uint4* pacc;
        {
            const int tid = opq(threadIdx.x), warp = tid >> 5, lane = tid & 31, g = lane >> 2, t = lane & 3, mat = lane >> 3, r8 = lane & 7;
            const int kg = warp >> 1, mg = warp & 1;
            const bool wo2 = role1 < DN0 + NDN;
            const uint32_t aw2 = 40960 + (wo2 && KEEP4 && role1 >= DN0 && kg >= 2 ? SM_B - SM_Q : 0);
            uint32_t aw[5];
#pragma unroll
            for (int i = 0; i < 5; i++) {
                const uint32_t lin = ((mat >> 1) * 8 + r8) * 320 + 64 * i + 32 * mg + 16 * (mat & 1);
                aw[i] = sb + (wo2 ? SM_Q : SM_B) + 5120 * kg + (lin ^ ((lin >> 3) & 48));
            }
#define CXE 0
            const uint32_t ao = pin(sb + SM_OS + 96 * kg + 16 * t), dw = pin(sb + SM_R + 16 * (16 * mg + g) + 4 * kg);
            pr = pin(sb + SM_R + 48 * tid); pacc = pin(&g_scr.acc[layer][(54 * c + tid)]);
            const int w = 2 * min(tid, 47);
            const uint32_t d0 = pin(sb + SM_OS + 4 * (24 * ((w >> 3) & 3) + ((w >> 2) & 1) + (w < 64 ? 4 * (w & 3) + 2 * (w >> 5) : 16 + 2 * (w & 3))));
            const uint32_t d1 = pin(d0 + (w < 64 ? 16 : 8));
            const uint4* pp[3];
#pragma unroll
            for (int k = 0; k < 3; k++) pp[k] = pin(&g_scr.hx[(h * 4 + ((c + 1 + k) & 3)) * 48 + min(tid, 47)]);
            uint4 v3[3];
#pragma unroll
            for (int k = 0; k < 3; k++) v3[k] = make_uint4(0u, 0u, 0u, 1u);
            if ((PRE1 & 8) && layer) {
#pragma unroll
                for (int ks = 0; ks < 3; ks++) {
                    mbar_wait(wbar + 8 * ks, wo2);
#pragma unroll
                    for (int i = 0; i < 5; i++) ldsm4t(aw[i] + (ks == 2 ? aw2 : 20480 * ks), kq[3 * i + ks]);
                    if (ks == CXE && wu < 2) {
#pragma unroll
                        for (int k = 0; k < 3; k++) v3[k] = ld_pkt(pp[k]);
                    }
                }
                PROF_T(50);
            }
            if (wu < 2) {
                for (int it = 0; any_odd(v3[0].w, v3[1].w, v3[2].w) && it < SPIN_CAP; it++) {
#pragma unroll
                    for (int k = 0; k < 3; k++) v3[k] = ld_pkt(pp[k]);
                }
                o.x = (o.x + f_(v3[0].x)) + (f_(v3[1].x) + f_(v3[2].x)); o.y = (o.y + f_(v3[0].y)) + (f_(v3[1].y) + f_(v3[2].y));
                o.z = (o.z + f_(v3[0].z)) + (f_(v3[1].z) + f_(v3[2].z)); o.w = (o.w + f_(v3[0].w)) + (f_(v3[1].w) + f_(v3[2].w));
                sts32p(d0, f_(pack2(o.x, o.y)), tid >= 48);
                sts32p(d1, f_(pack2(o.z, o.w)), tid >= 48);
            }
            PC(layer * 32 + 3);
            __syncthreads();
            PROF_T(5 + layer * 16);
            PC(layer * 32 + 5);
            if (tid == 224 && layer == 0) {
                if (ticket >= 6 + ((b >> 3) & 1)) ticket = DN0 + NDN;
                else asm volatile("atom.relaxed.gpu.global.inc.u32 %0, [%1], 0x7fffffff;" : "=r"(ticket) : "l"(g_scr.ticket) : "memory");
            }
            uint32_t ob[6];
            lds128(ao, ob[0], ob[1], ob[2], ob[3]);
            lds64(ao + 64 - 8 * t, ob[4], ob[5]);
            float cc[5][4];
#pragma unroll
            for (int i = 0; i < 5; i++) cc[i][0] = cc[i][1] = cc[i][2] = cc[i][3] = 0.f;
            if ((PRE1 & 8) && layer) {
#pragma unroll
                for (int ks = 0; ks < 3; ks++) {
#pragma unroll
                    for (int i = 0; i < 5; i++) mma16816(cc[i], kq[3 * i + ks][0], kq[3 * i + ks][1], kq[3 * i + ks][2], kq[3 * i + ks][3], ob[2 * ks], ob[2 * ks + 1]);
                }
            } else {
#pragma unroll
                for (int ks = 0; ks < 3; ks++) {
                    mbar_wait(wbar + 8 * ks, wo2);
                    if (ks == 2) { PC(layer * 32 + 4); PROF_T(48 + layer * 2); }
                    uint32_t a[5][4];
#pragma unroll
                    for (int i = 0; i < 5; i++) ldsm4t(aw[i] + (ks == 2 ? aw2 : 20480 * ks), a[i]);
#pragma unroll
                    for (int i = 0; i < 5; i++) mma16816(cc[i], a[i][0], a[i][1], a[i][2], a[i][3], ob[2 * ks], ob[2 * ks + 1]);
                }
            }
            if (t == 0) {
#pragma unroll
                for (int i = 0; i < 5; i++) { sts32(dw + 512 * i, cc[i][0]); sts32(dw + 512 * i + 128, cc[i][2]); }
            }
        }
        PC(layer * 32 + 6);
        __syncthreads();
        PROF_T(6 + layer * 16);
        PC(layer * 32 + 7);
        if (tid < 54) {
            const float4 v0 = lds4f(pr), v1 = lds4f(pr + 16), v2 = lds4f(pr + 32);
            const float y0 = (v0.x + v0.y) + (v0.z + v0.w), y1 = (v1.x + v1.y) + (v1.z + v1.w), y2 = (v2.x + v2.y) + (v2.z + v2.w);
            red_pkt(pacc, y0, tid == 53 ? 0.f : y1, tid == 53 ? 0.f : y2);
        }
        if (tid == 224 && layer == 0) {
            misc[1] = __uint_as_float(ticket);
            if (ticket < DN0 + NDN && (ticket < NG || !DNTH)) load_ffn(maps, ticket, sb + SM_B, fbar);
        }
        PROF_T(7 + layer * 16);
        PC(layer * 32 + 8);
        __syncthreads();
        const int role = (int)__float_as_uint(misc[1]);
        PC(layer * 32 + 9);
        const uint32_t fbase = sb + SM_B;
        const uint32_t DONE32 = 0x42000000u;
        if (role < NG) {
            const int tid = opq(threadIdx.x), warp = tid >> 5, lane = tid & 31, g = lane >> 2, t = lane & 3, mat = lane >> 3, r8 = lane & 7;
            const uint32_t ag = fbase + (80 * warp + (mat >> 1) * 8 + r8) * 96 + (((mat & 1) ^ (r8 >> 2)) << 4);
            constexpr int GI = 32, GK = 16 * 96;
            const bool on = (g & 1) == (t >> 1), isx = on && g < 2;
            const uint32_t pm = opq(isx ? sb + SM_XS + 160 * warp + 16 * t : sb + (on ? SM_ONE : SM_ZERO)), pm2 = opq(pm + 128 - (isx ? 8 * t : 0));
            const uint32_t dg = opq(sb + SM_R + 4 * (2 * (warp * 48 + g) + t)), ds = opq(sb + SM_ST + 8 * warp + (lane < 16 ? 4 : 0));
            const bool ws = (lane & 15) == 0, lo = lane < 16;
            uint32_t pre[6][4];
            float s1 = 0.f, s2 = 0.f;
            {
                bool hx = false;
                int it = 0;
                const int cq = wu >> 1, odd = wu & 1, r = min(26 * odd + lane, 26 + 27 * odd), c0 = 3 * r - 80 * odd, k0 = 160 * cq + 3 * r;
                const uint4* px = &g_scr.acc[layer][(54 * cq + r)];
                const bool act = lane <= 26 + odd;
                const bool on0 = act && c0 >= 0, on1 = act && c0 + 1 >= 0 && c0 + 1 < 80, on2 = act && c0 + 2 < 80;
                const uint32_t w0 = sb + SM_XS + 4 * xpos(k0 >> 1), w1 = sb + SM_XS + 4 * xpos(min((k0 >> 1) + 1, DM / 2 - 1));
                const uint32_t e0 = w0 + 2 * (k0 & 1), e1 = (k0 & 1) ? w1 : w0 + 2, e2 = w1 + 2 * (k0 & 1);
                auto sts16 = [](uint32_t a, uint32_t x, bool on) {
                    asm volatile("{\n.reg .pred p;\nsetp.ne.u32 p, %2, 0;\n@p st.shared.u16 [%0], %1;\n}" ::"r"(a), "h"((unsigned short)x), "r"((uint32_t)on) : "memory");
                };
                const float x0 = on0 ? f_(lds16(e0) << 16) : 0.f, x1 = on1 ? f_(lds16(e1) << 16) : 0.f, x2 = on2 ? f_(lds16(e2) << 16) : 0.f;
                auto take_x = [&](const uint4 v) {
                    if (__all_sync(0xffffffffu, v.w == DONE32)) {
                        hx = true;
                        const uint32_t a = pack2(f_(v.x), f_(v.y)), p = pack2(x0 + bf_lo(a), x1 + bf_hi(a)), q = pack2(x2 + bfr(f_(v.z)), 0.f);
                        sts16(e0, p, on0); sts16(e1, p >> 16, on1); sts16(e2, q, on2);
                        const float y0 = on0 ? bf_lo(p) : 0.f, y1 = on1 ? bf_hi(p) : 0.f, y2 = on2 ? bf_lo(q) : 0.f;
                        s1 = y0 + (y1 + y2); s2 = y0 * y0 + (y1 * y1 + y2 * y2);
                    }
                };
                auto try_x = [&]() { take_x(ld_pkt(px)); };
                while (!mbar_test(fbar, 0) && ++it < SPIN_CAP) { if (!hx) try_x(); }
                uint4 v0 = make_uint4(0u, 0u, 0u, 0u);
                if ((PRE1 & 4) && !hx) v0 = ld_pkt(px);
#pragma unroll
                for (int n = 0; n < 6; n++) ldsm4t(ag + (n % 3) * GI + (n / 3) * GK, pre[n]);
                if ((PRE1 & 1) && layer) {
#pragma unroll
                    for (int n = 6; n < 15; n++) ldsm4t(ag + (n % 3) * GI + (n / 3) * GK, kq[n - 6]);
                }
                if ((PRE1 & 4) && !hx) take_x(v0);
                PC(layer * 32 + 10);
                for (; !hx && it < SPIN_CAP; it++) try_x();
                PC(layer * 32 + 11);
            __syncwarp();
            PC(layer * 32 + 12);
            PROF_T(9 + layer * 16);
            float sv = lo ? s1 : s2, cc[3][4];
            if ((PRE1 & 1) && layer) gemv15r(cc, pre, kq, pm, pm2, sv, lo ? s2 : s1);
            else gemv15<GK>(cc, pre, [&](int i) { return ag + i * GI; }, pm, pm2, sv, lo ? s2 : s1);
#pragma unroll
            for (int i = 0; i < 3; i++) { sts32p(dg + 128 * i, cc[i][0] + cc[i][3], t & 2); sts32p(dg + 128 * i + 64, cc[i][1] + cc[i][2], t & 2); }
            if (ws) sts32(ds, sv);
            const uint32_t pg = opq(sb + SM_R + 8 * (24 * warp + (lane < 24 ? lane : 0))), st = opq(sb + SM_ST);
            uint4* const ph = opq(lane < 24 && lane % 6 == 0 ? &g_scr.ah[role * 8 + 4 * warp + lane / 6] : nullptr);
            PC(layer * 32 + 13);
            __syncthreads();
            PC(layer * 32 + 14);
            PROF_T(43 + layer * 16);
            if (wu < 2) {
                float mean, inv;
                ln_stats(st, mean, inv);
                float2 v[8];
#pragma unroll
                for (int w = 0; w < 8; w++) v[w] = lds2f(pg + w * 384);
                const float gx = ((v[0].x + v[1].x) + (v[2].x + v[3].x)) + ((v[4].x + v[5].x) + (v[6].x + v[7].x));
                const float gs = ((v[0].y + v[1].y) + (v[2].y + v[3].y)) + ((v[4].y + v[5].y) + (v[6].y + v[7].y));
                float ga = inv * (gx - mean * gs);
                if (role < NG / 2) { ga = bfr(ga); ga *= rcp(1.0f + ex2(-1.4426950408889634f * ga)); }
                const uint32_t wd = pack2(ga, __shfl_down_sync(0xffffffffu, ga, 1));
                const uint32_t wa = __shfl_down_sync(0xffffffffu, wd, 2), wb = __shfl_down_sync(0xffffffffu, wd, 4);
                if (ph) st_pkt(ph, wd, wa, wb, tag);
            }
            if (HOLD & 2) __syncthreads();
            }
            PROF_T(10 + layer * 16);
            PC(layer * 32 + 15);
        } else if (role < DN0 + NDN) {
            const int j = role - DN0;
            const int tid = opq(threadIdx.x), warp = tid >> 5, lane = tid & 31, g = lane >> 2, t = lane & 3, mat = lane >> 3, r8 = lane & 7;
            float xres = 0.f;
            uint32_t xr0 = 0, xr1 = 0;
            if (wu == 0) {
                const int col = 16 * j + (lane & 15), cc = col / 160, r = col - 160 * cc, e = r % 3;
                const uint4* px = &g_scr.acc[layer][(54 * cc + r / 3)];
                const float x0 = __bfloat162float(reinterpret_cast<const __nv_bfloat16*>(xs32)[2 * xpos(col >> 1) + (col & 1)]);
                uint4 v;
                int it = 0;
                bool ld = DNTH && layer == 0;
                do {
                    v = ld_pkt(px);
                    if (ld && f_(__shfl_sync(0xffffffffu, v.w, 0)) >= (float)DNTH) { ld = false; if (lane == 0) load_ffn(maps, role, sb + SM_B, fbar); }
                } while (!__all_sync(0xffffffffu, v.w == DONE32) && ++it < SPIN_CAP);
                if (ld && lane == 0) load_ffn(maps, role, sb + SM_B, fbar);
                xres = x0 + bfr(f_(e == 0 ? v.x : (e == 1 ? v.y : v.z)));
                const int p4 = 4 * (lane & 3);
                xr0 = pack2(__shfl_sync(0xffffffffu, xres, p4), __shfl_sync(0xffffffffu, xres, p4 + 1));
                xr1 = pack2(__shfl_sync(0xffffffffu, xres, p4 + 2), __shfl_sync(0xffffffffu, xres, p4 + 3));
            }
            PC(layer * 32 + 17);
            PROF_T(9 + layer * 16);
            const uint32_t ad = fbase + (192 * warp + (mat >> 1) * 8 + r8) * 32 + (((mat & 1) ^ (r8 >> 2)) << 4);
            uint32_t* hs = reinterpret_cast<uint32_t*>(rr) + warp * 96;
            uint32_t pre[NPRE][4];
            {
                uint32_t pos[3];
#pragma unroll
                for (int i = 0; i < 3; i++) { const int w = 3 * lane + i; pos[i] = pin(sb + SM_R + 384 * warp + 4 * ((w & ~15) + 4 * (w & 3) + ((w >> 2) & 1) + ((w >> 2) & 2))); }
                uint4 v = make_uint4(0u, 0u, 0u, 0u), u = v;
                if (layer == 0) { v = ld_pkt(&g_scr.ah[tid]); u = ld_pkt(&g_scr.ah[256 + tid]); }
                mbar_wait(fbar, 0);
#pragma unroll
                for (int n = 0; n < NPRE; n++) ldsm4t(ad + n * 512, pre[n]);
                if ((PRE1 & 2) && layer) {
#pragma unroll
                    for (int n = NPRE; n < 12; n++) ldsm4t(ad + n * 512, kq[12 + n]);
                }
                PC(layer * 32 + 18);
                int it = 0;
                for (; any_ne(v.w, u.w, tag) && it < SPIN_CAP; it++) { v = ld_pkt(&g_scr.ah[tid]); u = ld_pkt(&g_scr.ah[256 + tid]); }
                PC(layer * 32 + 19);
                sts32(pos[0], f_(bmul2(v.x, u.x))); sts32(pos[1], f_(bmul2(v.y, u.y))); sts32(pos[2], f_(bmul2(v.z, u.z)));
            __syncwarp();
            PROF_T(11 + layer * 16);
            PC(layer * 32 + 20);
            float ca[4] = {0.f, 0.f, 0.f, 0.f}, cb[4] = {0.f, 0.f, 0.f, 0.f};
            if ((PRE1 & 2) && layer) {
                float cc[4] = {0.f, 0.f, 0.f, 0.f}, cd[4] = {0.f, 0.f, 0.f, 0.f};
#pragma unroll
                for (int jj = 0; jj < 6; jj++) {
                    const uint4 hv = *reinterpret_cast<const uint4*>(hs + 16 * jj + 4 * t);
                    const uint32_t (&f0)[4] = 2 * jj < NPRE ? pre[2 * jj < NPRE ? 2 * jj : 0] : kq[12 + 2 * jj];
                    const uint32_t (&f1)[4] = 2 * jj + 1 < NPRE ? pre[2 * jj + 1 < NPRE ? 2 * jj + 1 : 0] : kq[13 + 2 * jj];
                    if (jj & 1) { mma16816(cc, f0[0], f0[1], f0[2], f0[3], hv.x, hv.y); mma16816(cd, f1[0], f1[1], f1[2], f1[3], hv.z, hv.w); }
                    else { mma16816(ca, f0[0], f0[1], f0[2], f0[3], hv.x, hv.y); mma16816(cb, f1[0], f1[1], f1[2], f1[3], hv.z, hv.w); }
                }
#pragma unroll
                for (int e = 0; e < 4; e++) { ca[e] += cc[e]; cb[e] += cd[e]; }
            } else {
#pragma unroll
                for (int jj = 0; jj < 6; jj++) {
                    const uint4 hv = *reinterpret_cast<const uint4*>(hs + 16 * jj + 4 * t);
                    uint32_t a[4];
                    if (2 * jj < NPRE) { a[0] = pre[2 * jj][0]; a[1] = pre[2 * jj][1]; a[2] = pre[2 * jj][2]; a[3] = pre[2 * jj][3]; }
                    else ldsm4t(ad + 2 * jj * 512, a);
                    mma16816(ca, a[0], a[1], a[2], a[3], hv.x, hv.y);
                    if (2 * jj + 1 < NPRE) { a[0] = pre[2 * jj + 1][0]; a[1] = pre[2 * jj + 1][1]; a[2] = pre[2 * jj + 1][2]; a[3] = pre[2 * jj + 1][3]; }
                    else ldsm4t(ad + (2 * jj + 1) * 512, a);
                    mma16816(cb, a[0], a[1], a[2], a[3], hv.z, hv.w);
                }
            }
            if (t == 0) { rr[768 + warp * 16 + g] = ca[0] + cb[0]; rr[768 + warp * 16 + 8 + g] = ca[2] + cb[2]; }
            const uint32_t pd = opq(sb + SM_R + 3072 + 16 * (lane & 3));
            uint4* const py = opq(&g_scr.ay[j * 4 + lane]);
            uint2* const po = opq(reinterpret_cast<uint2*>(out + 16 * j) + lane);
            PC(layer * 32 + 21);
            __syncthreads();
            PC(layer * 32 + 22);
            if (wu == 0) {
                float4 p[8];
#pragma unroll
                for (int w = 0; w < 8; w++) p[w] = lds4f(pd + 64 * w);
                const uint32_t y0 = pack2(((p[0].x + p[1].x) + (p[2].x + p[3].x)) + ((p[4].x + p[5].x) + (p[6].x + p[7].x)),
                                          ((p[0].y + p[1].y) + (p[2].y + p[3].y)) + ((p[4].y + p[5].y) + (p[6].y + p[7].y)));
                const uint32_t y1 = pack2(((p[0].z + p[1].z) + (p[2].z + p[3].z)) + ((p[4].z + p[5].z) + (p[6].z + p[7].z)),
                                          ((p[0].w + p[1].w) + (p[2].w + p[3].w)) + ((p[4].w + p[5].w) + (p[6].w + p[7].w)));
                uint32_t wd, wn;
                asm("add.rn.bf16x2 %0, %1, %2;" : "=r"(wd) : "r"(xr0), "r"(y0));
                asm("add.rn.bf16x2 %0, %1, %2;" : "=r"(wn) : "r"(xr1), "r"(y1));
                asm volatile("{\n.reg .pred p;\nsetp.ne.u32 p, %3, 0;\n@p st.global.v2.u32 [%0], {%1,%2};\n}" ::"l"(po), "r"(wd), "r"(wn), "r"((uint32_t)(layer && tid < 4)) : "memory");
                st_pktp(py, wd, wn, 0, tag, tid < 4);
            }
            if (HOLD & 1) __syncthreads();
            }
            PROF_T(12 + layer * 16);
            PC(layer * 32 + 23);
        }
    }
}

typedef CUresult (*EncodeFn)(CUtensorMap*, CUtensorMapDataType, cuuint32_t, void*, const cuuint64_t*, const cuuint64_t*, const cuuint32_t*,
                             const cuuint32_t*, CUtensorMapInterleave, CUtensorMapSwizzle, CUtensorMapL2promotion, CUtensorMapFloatOOBfill);

void make_map(EncodeFn enc, CUtensorMap* m, const void* base, int rank, uint64_t d0, uint64_t d1, uint64_t d2, uint64_t s1, uint64_t s2,
              uint32_t b0, uint32_t b1, uint32_t b2, CUtensorMapSwizzle sw, CUtensorMapL2promotion pr = CU_TENSOR_MAP_L2_PROMOTION_NONE) {
    cuuint64_t dims[3] = {d0, d1, d2};
    cuuint64_t strides[2] = {s1, s2};
    cuuint32_t box[3] = {b0, b1, b2};
    cuuint32_t es[3] = {1, 1, 1};
    enc(m, CU_TENSOR_MAP_DATA_TYPE_BFLOAT16, rank, const_cast<void*>(base), dims, strides, box, es, CU_TENSOR_MAP_INTERLEAVE_NONE, sw,
        pr, CU_TENSOR_MAP_FLOAT_OOB_FILL_NONE);
}

}

extern "C" void kernel_launch(void* const* d_in, const int* in_sizes, int n_in, void* d_out, int out_size) {
    (void)in_sizes; (void)n_in; (void)out_size;
    static EncodeFn enc = nullptr;
    if (!enc) {
        void* fn = nullptr;
        cudaDriverEntryPointQueryResult qr;
        cudaGetDriverEntryPoint("cuTensorMapEncodeTiled", &fn, cudaEnableDefault, &qr);
        enc = reinterpret_cast<EncodeFn>(fn);
        cudaFuncSetAttribute(decode_kernel, cudaFuncAttributeMaxDynamicSharedMemorySize, SM_TOTAL);
    }
    Maps maps;
    make_map(enc, &maps.k, d_in[1], 2, 64, (uint64_t)NH * SK * 3, 1, 128, 0, 64, 48, 1, CU_TENSOR_MAP_SWIZZLE_128B);
    make_map(enc, &maps.v, d_in[2], 2, 64, (uint64_t)NH * SK * 3, 1, 128, 0, 64, 48, 1, CU_TENSOR_MAP_SWIZZLE_128B);
    make_map(enc, &maps.wq, d_in[3], 3, 64, DM, NH * DH / 64, NH * DH * 2, 128, 64, 160, 3, CU_TENSOR_MAP_SWIZZLE_128B);
    make_map(enc, &maps.wo, d_in[4], 3, 32, DM / 32, NH * DH, 64, DM * 2, 32, 5, 32, CU_TENSOR_MAP_SWIZZLE_64B);
    make_map(enc, &maps.vr, (const char*)d_in[2] + 512, 2, 128, (uint64_t)NH * SK / 2, 1, 768, 0, 128, 2, 1, CU_TENSOR_MAP_SWIZZLE_NONE);
    constexpr int GW = 48;
    make_map(enc, &maps.w1, d_in[6], 3, FF, 160, 4, FF * 2, 160 * FF * 2, GW, 160, 4, CU_TENSOR_MAP_SWIZZLE_NONE, FFN_PROMO);
    make_map(enc, &maps.w3, d_in[7], 3, FF, 160, 4, FF * 2, 160 * FF * 2, GW, 160, 4, CU_TENSOR_MAP_SWIZZLE_NONE, FFN_PROMO);
    make_map(enc, &maps.w2, d_in[8], 3, DM, 256, 6, DM * 2, 256 * DM * 2, 16, 256, 6, CU_TENSOR_MAP_SWIZZLE_32B, FFN_PROMO);
    maps.vp = d_in[2];
    maps.kp = d_in[1];
    maps.zero = 0;
    decode_kernel<<<NCTA, NT, SM_TOTAL, cudaStreamPerThread>>>(maps, (const __nv_bfloat16*)d_in[0], (__nv_bfloat16*)d_out);
}
```

```cpp
#include <cuda_runtime.h>
#include <cuda_bf16.h>
#include <cuda.h>
#include <stdint.h>
#include <math.h>

namespace {

constexpr int DM = 640;
constexpr int NH = 32;
constexpr int DH = 192;
constexpr int SK = 32768;
constexpr int WIN = 4096;
constexpr int FF = 1536;
constexpr int NCTA = 128;
constexpr int NT = 256;
constexpr int TILE = 6144;
constexpr int NG = 64;
constexpr int DN0 = 64;
constexpr int NDN = 40;

constexpr int SM_RING = 0;
constexpr int SM_B = 8 * 2 * TILE;
constexpr int SM_Q = SM_B + 61440;
__host__ __device__ constexpr int c_slot(int w) { return w < 2 ? 4096 + 10240 * w : 12288 + 6144 * w; }
__host__ __device__ constexpr int v1_pos(int n) { return 10240 * (n >> 3) + 512 * (n & 7); }
constexpr int SM_XS = SM_Q + 61440;
constexpr int SM_R = SM_XS + 1280;
constexpr int SM_ST = SM_R + 4096;
constexpr int SM_QS = SM_R + 6272;
constexpr int SM_OS = SM_QS + 384;
constexpr int SM_BAR = SM_OS + 384;
constexpr int SM_XBAR = SM_BAR + 24 * 8;
constexpr int SM_MISC = SM_XBAR + 8 * 8;
constexpr int SM_ONE = SM_MISC + 16;
constexpr int SM_ZERO = SM_ONE + 160;
constexpr int XCAP = 48;
constexpr int XSTR = 16 + 4 * XCAP;
constexpr int SM_XL = SM_ZERO + 160;
constexpr int SM_TOTAL = SM_XL + 8 * XSTR;
static_assert(SM_TOTAL <= 232448, "shared memory");

constexpr unsigned long long POL_EF = 0x12F0000000000000ull;
constexpr unsigned long long POL_EN = 0x16F0000000000000ull;

#define RT_MASK 0xF2E0u
#define RT_MASK2 0xEAE0u
#define WO_AT1 5
#define FFN_PROMO CU_TENSOR_MAP_L2_PROMOTION_NONE
#define FFN_POL POL_EF
#define HAS_FFN (__float_as_uint(misc[1]) < DN0 + NDN)
#define NPRE 6

#define STAG 200
#define L1R 3
#define PRE1 13
#define HOLD 2
#define DNTH 23
constexpr int V0_AT = 8;
constexpr unsigned long long SEQ1 = 0x2765431076543210ull;
constexpr uint32_t IN_S1 = 0xAA49, IN_S0 = 0x124, PARITY1 = 0x6638, PARITY2 = 0xCE;
#define KEEP4 1
constexpr int NQ = 48;
constexpr int SPIN_CAP = 1 << 19;
constexpr uint32_t ONES = 0x3F803F80u;

__host__ __device__ constexpr int acc_pos(int p) { return (p >> 2) * 8 + (p & 3); }
struct alignas(4096) Scratch {
    uint4 hx[NCTA * 48];
    uint4 acc[2][512];
    uint4 ay[256];
    uint4 ah[NG * 8];
    uint2 mx[NH * 32];
    uint32_t ticket[32];
    uint32_t pad1[32];
};
__device__ Scratch g_scr;
#define PROF_T(i)
#define PROF_X(i)
#define PC(i)

__device__ __forceinline__ uint32_t smem_u32(const void* p) { return (uint32_t)__cvta_generic_to_shared(p); }
__device__ __forceinline__ void mbar_init(uint32_t bar, uint32_t cnt) {
    asm volatile("mbarrier.init.shared::cta.b64 [%0], %1;" ::"r"(bar), "r"(cnt) : "memory");
}
__device__ __forceinline__ void mbar_expect_tx(uint32_t bar, uint32_t bytes) {
    asm volatile("mbarrier.arrive.expect_tx.shared::cta.b64 _, [%0], %1;" ::"r"(bar), "r"(bytes) : "memory");
}
__device__ __forceinline__ bool mbar_test(uint32_t bar, uint32_t parity) {
    uint32_t done;
    asm volatile("{\n.reg .pred p;\nmbarrier.try_wait.parity.shared::cta.b64 p, [%1], %2;\nselp.u32 %0, 1, 0, p;\n}"
                 : "=r"(done) : "r"(bar), "r"(parity) : "memory");
    return done;
}
__device__ __forceinline__ void mbar_wait(uint32_t bar, uint32_t parity) {
    for (int it = 0; it < SPIN_CAP; it++) if (mbar_test(bar, parity)) break;
}
__device__ __forceinline__ void tma2d(uint32_t dst, const CUtensorMap* map, int c0, int c1, uint32_t bar, unsigned long long pol) {
    asm volatile("cp.async.bulk.tensor.2d.shared::cluster.global.mbarrier::complete_tx::bytes.L2::cache_hint [%0], [%1, {%3, %4}], [%2], %5;"
                 ::"r"(dst), "l"(map), "r"(bar), "r"(c0), "r"(c1), "l"(pol) : "memory");
}
__device__ __forceinline__ void tma3d(uint32_t dst, const CUtensorMap* map, int c0, int c1, int c2, uint32_t bar, unsigned long long pol) {
    asm volatile("cp.async.bulk.tensor.3d.shared::cluster.global.mbarrier::complete_tx::bytes.L2::cache_hint [%0], [%1, {%3, %4, %5}], [%2], %6;"
                 ::"r"(dst), "l"(map), "r"(bar), "r"(c0), "r"(c1), "r"(c2), "l"(pol) : "memory");
}
__device__ __forceinline__ void tile_load(uint32_t dst, const CUtensorMap* map, int row, uint32_t bar, uint32_t dep, uint32_t zero) {
    asm volatile("{\n.reg .pred p;\n.reg .b32 n;\nmad.lo.u32 n, %5, %6, 6144;\nelect.sync _|p, 0xffffffff;\n"
                 "@p mbarrier.arrive.expect_tx.shared::cta.b64 _, [%2], n;\n"
                 "@p cp.async.bulk.tensor.2d.shared::cluster.global.mbarrier::complete_tx::bytes.L2::cache_hint [%0], [%1, {0, %3}], [%2], %4;\n}"
                 ::"r"(dst), "l"(map), "r"(bar), "r"(row), "l"(POL_EF), "r"(dep), "r"(zero) : "memory");
}
__device__ __forceinline__ void tile_keep(const CUtensorMap* map, int row) {
    asm volatile("{\n.reg .pred p;\nelect.sync _|p, 0xffffffff;\n"
                 "@p cp.async.bulk.prefetch.tensor.2d.L2.global.L2::cache_hint [%0, {0, %1}], %2;\n}"
                 ::"l"(map), "r"(row), "l"(POL_EN) : "memory");
}
__device__ __forceinline__ void tile_load_l1(uint32_t dst, const void* base, int row, uint32_t bar, int lane) {
    const char* g = static_cast<const char*>(base) + (size_t)row * 128 + lane * 16;
    const uint32_t s0 = dst + (lane >> 3) * 128 + (((lane & 7) ^ (lane >> 3)) << 4), s1 = s0 ^ 64;
#pragma unroll
    for (int k = 0; k < 12; k++)
        asm volatile("cp.async.ca.shared.global.L2::cache_hint [%0], [%1], 16, %2;" ::"r"(((k & 1) ? s1 : s0) + k * 512), "l"(g + k * 512), "l"(POL_EF) : "memory");
    asm volatile("cp.async.mbarrier.arrive.shared::cta.b64 [%0];" ::"r"(bar) : "memory");
    __syncwarp();
    if (lane == 0) asm volatile("mbarrier.arrive.shared::cta.b64 _, [%0];" ::"r"(bar) : "memory");
}
__device__ __forceinline__ bool elect_one() {
    uint32_t p;
    asm volatile("{\n.reg .pred p;\nelect.sync _|p, 0xffffffff;\nselp.u32 %0, 1, 0, p;\n}" : "=r"(p));
    return p;
}
__device__ __forceinline__ void lds128(uint32_t addr, uint32_t& a, uint32_t& b, uint32_t& c, uint32_t& d) {
    asm volatile("ld.shared.v4.u32 {%0,%1,%2,%3}, [%4];" : "=r"(a), "=r"(b), "=r"(c), "=r"(d) : "r"(addr) : "memory");
}
__device__ __forceinline__ void lds128p(uint32_t addr, uint32_t on, uint32_t& a, uint32_t& b, uint32_t& c, uint32_t& d) {
    asm volatile("{\n.reg .pred p;\nsetp.ne.u32 p, %5, 0;\n@p ld.shared.v4.u32 {%0,%1,%2,%3}, [%4];\n}" : "+r"(a), "+r"(b), "+r"(c), "+r"(d) : "r"(addr), "r"(on) : "memory");
}
__device__ __forceinline__ void lds64(uint32_t addr, uint32_t& a, uint32_t& b) {
    asm volatile("ld.shared.v2.u32 {%0,%1}, [%2];" : "=r"(a), "=r"(b) : "r"(addr) : "memory");
}
__device__ __forceinline__ void ldsm4t(uint32_t addr, uint32_t (&a)[4]) {
    asm volatile("ldmatrix.sync.aligned.m8n8.x4.trans.shared.b16 {%0,%1,%2,%3}, [%4];" : "=r"(a[0]), "=r"(a[1]), "=r"(a[2]), "=r"(a[3]) : "r"(addr) : "memory");
}
__device__ __forceinline__ void mma16816(float (&c)[4], uint32_t a0, uint32_t a1, uint32_t a2, uint32_t a3, uint32_t b0, uint32_t b1) {
    asm("mma.sync.aligned.m16n8k16.row.col.f32.bf16.bf16.f32 {%0,%1,%2,%3}, {%4,%5,%6,%7}, {%8,%9}, {%0,%1,%2,%3};"
        : "+f"(c[0]), "+f"(c[1]), "+f"(c[2]), "+f"(c[3]) : "r"(a0), "r"(a1), "r"(a2), "r"(a3), "r"(b0), "r"(b1));
}
__device__ __forceinline__ void mma16816v(float (&c)[4], uint32_t a0, uint32_t a1, uint32_t a2, uint32_t a3, uint32_t b0, uint32_t b1) {
    asm volatile("mma.sync.aligned.m16n8k16.row.col.f32.bf16.bf16.f32 {%0,%1,%2,%3}, {%4,%5,%6,%7}, {%8,%9}, {%0,%1,%2,%3};"
        : "+f"(c[0]), "+f"(c[1]), "+f"(c[2]), "+f"(c[3]) : "r"(a0), "r"(a1), "r"(a2), "r"(a3), "r"(b0), "r"(b1));
}
__device__ __forceinline__ int xpos(int w) {
    const int seg = w / 40, r = w - 40 * seg;
    return 40 * seg + (r < 32 ? (r & 16) + 4 * (r & 3) + ((r >> 2) & 3) : 32 + 2 * (r & 3) + ((r >> 2) & 1));
}
#define NA_LD ""
#define NA_ST ""
__device__ __forceinline__ void st_pkt(uint4* p, uint32_t a, uint32_t b, uint32_t c, uint32_t d) {
    asm volatile("{\n.reg .b128 t;\n.reg .b64 lo, hi;\nmov.b64 lo, {%1,%2};\nmov.b64 hi, {%3,%4};\nmov.b128 t, {lo,hi};\nst.relaxed.gpu.global" NA_ST ".b128 [%0], t;\n}"
                 ::"l"(p), "r"(a), "r"(b), "r"(c), "r"(d) : "memory");
}
__device__ __forceinline__ void red_pkt(uint4* p, float a, float b, float c) {
    asm volatile("red.relaxed.gpu.global.add.v4.f32 [%0], {%1,%2,%3,%4};" ::"l"(p), "f"(a), "f"(b), "f"(c), "f"(1.0f) : "memory");
}
__device__ __forceinline__ void st_pktp(uint4* p, uint32_t a, uint32_t b, uint32_t c, uint32_t d, bool on) {
    asm volatile("{\n.reg .pred p;\n.reg .b128 t;\n.reg .b64 lo, hi;\nsetp.ne.u32 p, %5, 0;\nmov.b64 lo, {%1,%2};\nmov.b64 hi, {%3,%4};\nmov.b128 t, {lo,hi};\n"
                 "@p st.relaxed.gpu.global.b128 [%0], t;\n}" ::"l"(p), "r"(a), "r"(b), "r"(c), "r"(d), "r"((uint32_t)on) : "memory");
}
__device__ __forceinline__ void st_pktfp(uint4* p, float a, float b, float c, float d, uint32_t bit, bool on) {
    st_pktp(p, __float_as_uint(a), __float_as_uint(b), __float_as_uint(c), (__float_as_uint(d) & ~1u) | bit, on);
}
__device__ __forceinline__ uint4 ld_pkt(const uint4* p) {
    uint4 v;
    asm volatile("{\n.reg .b128 t;\n.reg .b64 lo, hi;\nld.relaxed.gpu.global" NA_LD ".b128 t, [%4];\nmov.b128 {lo,hi}, t;\nmov.b64 {%0,%1}, lo;\nmov.b64 {%2,%3}, hi;\n}"
                 : "=r"(v.x), "=r"(v.y), "=r"(v.z), "=r"(v.w) : "l"(p) : "memory");
    return v;
}
__device__ __forceinline__ bool all_odd(uint32_t a, uint32_t b, uint32_t c, uint32_t d) {
    uint32_t r;
    asm volatile("{\n.reg .pred p, q, t;\n.reg .b32 x;\nsetp.eq.b32 t, 0, 0;\nlop3.b32 x, %1, %2, %3, 0x80;\nlop3.and.b32 _|p, x, %4, 1, 0x80, t;\n"
                 "vote.sync.all.pred q, p, 0xffffffff;\nselp.u32 %0, 1, 0, q;\n}" : "=r"(r) : "r"(a), "r"(b), "r"(c), "r"(d));
    return r;
}
__device__ __forceinline__ bool any_odd(uint32_t a, uint32_t b, uint32_t c) {
    uint32_t r;
    asm volatile("{\n.reg .pred p, q, t;\n.reg .b32 x;\nsetp.eq.b32 t, 0, 0;\nlop3.b32 x, %1, %2, %3, 0xFE;\nlop3.and.b32 _|p, x, 1, 0, 0xC0, t;\n"
                 "vote.sync.any.pred q, p, 0xffffffff;\nselp.u32 %0, 1, 0, q;\n}" : "=r"(r) : "r"(a), "r"(b), "r"(c));
    return r;
}
__device__ __forceinline__ bool any_ne(uint32_t a, uint32_t b, uint32_t c) {
    uint32_t r;
    asm volatile("{\n.reg .pred p, q, t;\nsetp.eq.b32 t, 0, 0;\nlop3.and.b32 _|p, %1, %2, %3, 0x7E, t;\n"
                 "vote.sync.any.pred q, p, 0xffffffff;\nselp.u32 %0, 1, 0, q;\n}" : "=r"(r) : "r"(a), "r"(b), "r"(c));
    return r;
}
__device__ __forceinline__ uint2 ld_pkt2(const uint2* p) {
    unsigned long long v;
    asm volatile("ld.relaxed.gpu.global" NA_LD ".b64 %0, [%1];" : "=l"(v) : "l"(p) : "memory");
    return make_uint2((uint32_t)v, (uint32_t)(v >> 32));
}
__device__ __forceinline__ void st_pkt2(uint2* p, uint32_t a, uint32_t b) {
    asm volatile("st.relaxed.gpu.global" NA_ST ".b64 [%0], %1;" ::"l"(p), "l"((unsigned long long)a | ((unsigned long long)b << 32)) : "memory");
}
__device__ __forceinline__ float ex2(float x) { float y; asm("ex2.approx.ftz.f32 %0, %1;" : "=f"(y) : "f"(x)); return y; }
__device__ __forceinline__ float rcp(float x) { float y; asm("rcp.approx.ftz.f32 %0, %1;" : "=f"(y) : "f"(x)); return y; }
__device__ __forceinline__ uint32_t pack2(float lo, float hi) {
    uint32_t r; asm("cvt.rn.bf16x2.f32 %0, %1, %2;" : "=r"(r) : "f"(hi), "f"(lo)); return r;
}
__device__ __forceinline__ float bf_lo(uint32_t w) { return __uint_as_float(w << 16); }
__device__ __forceinline__ float bf_hi(uint32_t w) { return __uint_as_float(w & 0xffff0000u); }
__device__ __forceinline__ float bfr(float x) { return bf_lo(pack2(x, 0.f)); }
__device__ __forceinline__ float f_(uint32_t u) { return __uint_as_float(u); }

template <int SK, typename AddrF>
__device__ __forceinline__ void gemv15(float (&cc)[3][4], uint32_t (&pre)[6][4], AddrF ad, uint32_t px, uint32_t px2, float& sv, float so) {
    uint32_t x0[4], x1[4], a[3][4];
    asm volatile("ld.shared.v4.u32 {%0,%1,%2,%3}, [%20];\nld.shared.v4.u32 {%4,%5,%6,%7}, [%20+64];\n"
                 "ldmatrix.sync.aligned.m8n8.x4.trans.shared.b16 {%8,%9,%10,%11}, [%21];\n"
                 "ldmatrix.sync.aligned.m8n8.x4.trans.shared.b16 {%12,%13,%14,%15}, [%22];\n"
                 "ldmatrix.sync.aligned.m8n8.x4.trans.shared.b16 {%16,%17,%18,%19}, [%23];\nbar.warp.sync 0xffffffff;"
                 : "=r"(x0[0]), "=r"(x0[1]), "=r"(x0[2]), "=r"(x0[3]), "=r"(x1[0]), "=r"(x1[1]), "=r"(x1[2]), "=r"(x1[3]),
                   "=r"(a[0][0]), "=r"(a[0][1]), "=r"(a[0][2]), "=r"(a[0][3]), "=r"(a[1][0]), "=r"(a[1][1]), "=r"(a[1][2]), "=r"(a[1][3]),
                   "=r"(a[2][0]), "=r"(a[2][1]), "=r"(a[2][2]), "=r"(a[2][3])
                 : "r"(px), "r"(ad(0) + 2 * SK), "r"(ad(1) + 2 * SK), "r"(ad(2) + 2 * SK) : "memory");
    __syncwarp();
    sv += __shfl_xor_sync(0xffffffffu, so, 16);
#pragma unroll
    for (int i = 0; i < 3; i++) {
        cc[i][0] = cc[i][1] = cc[i][2] = cc[i][3] = 0.f;
        mma16816v(cc[i], pre[i][0], pre[i][1], pre[i][2], pre[i][3], x0[0], x0[1]);
    }
    sv += __shfl_xor_sync(0xffffffffu, sv, 8);
#pragma unroll
    for (int i = 0; i < 3; i++) {
        mma16816v(cc[i], pre[3 + i][0], pre[3 + i][1], pre[3 + i][2], pre[3 + i][3], x0[2], x0[3]);
        ldsm4t(ad(i) + 3 * SK, pre[i]);
    }
    lds64(px2, x0[0], x0[1]);
    __syncwarp();
    sv += __shfl_xor_sync(0xffffffffu, sv, 4);
#pragma unroll
    for (int i = 0; i < 3; i++) {
        mma16816v(cc[i], a[i][0], a[i][1], a[i][2], a[i][3], x1[0], x1[1]);
        ldsm4t(ad(i) + 4 * SK, pre[3 + i]);
    }
    __syncwarp();
    sv += __shfl_xor_sync(0xffffffffu, sv, 2);
#pragma unroll
    for (int i = 0; i < 3; i++) mma16816v(cc[i], pre[i][0], pre[i][1], pre[i][2], pre[i][3], x1[2], x1[3]);
    sv += __shfl_xor_sync(0xffffffffu, sv, 1);
#pragma unroll
    for (int i = 0; i < 3; i++) mma16816v(cc[i], pre[3 + i][0], pre[3 + i][1], pre[3 + i][2], pre[3 + i][3], x0[0], x0[1]);
}
__device__ __forceinline__ void gemv15r(float (&cc)[3][4], const uint32_t (&pre)[6][4], const uint32_t (&ext)[NQ][4], uint32_t px, uint32_t px2, float& sv, float so) {
    uint32_t x0[4], x1[4], x2[2];
    float cd[3][4];
    lds128(px, x0[0], x0[1], x0[2], x0[3]);
    lds128(px + 64, x1[0], x1[1], x1[2], x1[3]);
    lds64(px2, x2[0], x2[1]);
    sv += __shfl_xor_sync(0xffffffffu, so, 16);
#pragma unroll
    for (int i = 0; i < 3; i++) {
        cc[i][0] = cc[i][1] = cc[i][2] = cc[i][3] = cd[i][0] = cd[i][1] = cd[i][2] = cd[i][3] = 0.f;
        mma16816v(cc[i], pre[i][0], pre[i][1], pre[i][2], pre[i][3], x0[0], x0[1]);
        mma16816v(cd[i], pre[3 + i][0], pre[3 + i][1], pre[3 + i][2], pre[3 + i][3], x0[2], x0[3]);
    }
    sv += __shfl_xor_sync(0xffffffffu, sv, 8);
#pragma unroll
    for (int i = 0; i < 3; i++) {
        mma16816v(cc[i], ext[i][0], ext[i][1], ext[i][2], ext[i][3], x1[0], x1[1]);
        mma16816v(cd[i], ext[3 + i][0], ext[3 + i][1], ext[3 + i][2], ext[3 + i][3], x1[2], x1[3]);
    }
    sv += __shfl_xor_sync(0xffffffffu, sv, 4);
#pragma unroll
    for (int i = 0; i < 3; i++) mma16816v(cc[i], ext[6 + i][0], ext[6 + i][1], ext[6 + i][2], ext[6 + i][3], x2[0], x2[1]);
    sv += __shfl_xor_sync(0xffffffffu, sv, 2);
    sv += __shfl_xor_sync(0xffffffffu, sv, 1);
#pragma unroll
    for (int i = 0; i < 3; i++) { cc[i][0] += cd[i][0]; cc[i][1] += cd[i][1]; cc[i][2] += cd[i][2]; cc[i][3] += cd[i][3]; }
}

__device__ __forceinline__ float warp_max(float x) {
    int i = __float_as_int(x);
    i = __reduce_max_sync(0xffffffffu, i ^ ((i >> 31) & 0x7fffffff));
    return __int_as_float(i ^ ((i >> 31) & 0x7fffffff));
}
__device__ __forceinline__ void idle(uint32_t clk) {
    uint32_t t0, t;
    asm volatile("mov.u32 %0, %%clock;" : "=r"(t0) :: "memory");
    do asm volatile("mov.u32 %0, %%clock;" : "=r"(t) :: "memory"); while (t - t0 < clk);
}
__device__ __forceinline__ uint32_t now_ns() { uint32_t t; asm volatile("mov.u32 %0, %%globaltimer_lo;" : "=r"(t)); return t; }
__device__ __forceinline__ int opq(int x) { asm volatile("" : "+r"(x)); return x; }
__device__ __forceinline__ uint32_t opq(uint32_t x) { asm volatile("" : "+r"(x)); return x; }
__device__ __forceinline__ uint32_t pin(uint32_t x) { return __shfl_sync(0xffffffffu, x, threadIdx.x & 31); }
template <typename T> __device__ __forceinline__ T* pin(T* p) {
    const unsigned long long v = (unsigned long long)p;
    return (T*)((unsigned long long)pin((uint32_t)v) | (unsigned long long)pin((uint32_t)(v >> 32)) << 32);
}
template <typename T> __device__ __forceinline__ T* opq(T* p) { asm volatile("" : "+l"(p)); return p; }
__device__ __forceinline__ float4 lds4f(uint32_t a) { float4 v; asm volatile("ld.shared.v4.f32 {%0,%1,%2,%3}, [%4];" : "=f"(v.x), "=f"(v.y), "=f"(v.z), "=f"(v.w) : "r"(a) : "memory"); return v; }
__device__ __forceinline__ float2 lds2f(uint32_t a) { float2 v; asm volatile("ld.shared.v2.f32 {%0,%1}, [%2];" : "=f"(v.x), "=f"(v.y) : "r"(a) : "memory"); return v; }
__device__ __forceinline__ void ln_stats(uint32_t st, float& mean, float& inv) {
    const float4 a = lds4f(st), b = lds4f(st + 16), c = lds4f(st + 32), d = lds4f(st + 48);
    const float s2 = ((a.x + a.z) + (b.x + b.z)) + ((c.x + c.z) + (d.x + d.z));
    const float md = (((a.y + a.w) + (b.y + b.w)) + ((c.y + c.w) + (d.y + d.w))) * (1.0f / DM);
    const float var = fmaxf(s2 * (1.0f / DM) - md * md, 0.f);
    mean = bfr(md);
    asm("rsqrt.approx.ftz.f32 %0, %1;" : "=f"(inv) : "f"(var + 1e-5f));
}
__device__ __forceinline__ void sts32(uint32_t a, float v) { asm volatile("st.shared.f32 [%0], %1;" ::"r"(a), "f"(v) : "memory"); }
__device__ __forceinline__ void sts32p(uint32_t a, float v, uint32_t off) {
    asm volatile("{\n.reg .pred p;\nsetp.eq.u32 p, %2, 0;\n@p st.shared.f32 [%0], %1;\n}" ::"r"(a), "f"(v), "r"(off) : "memory");
}
__device__ __forceinline__ void sts128p(uint32_t a, float x, float y, float z, float w, uint32_t off) {
    asm volatile("{\n.reg .pred p;\nsetp.eq.u32 p, %5, 0;\n@p st.shared.v4.f32 [%0], {%1,%2,%3,%4};\n}" ::"r"(a), "f"(x), "f"(y), "f"(z), "f"(w), "r"(off) : "memory");
}
__device__ __forceinline__ void sts64(uint32_t a, float v, float w) { asm volatile("st.shared.v2.f32 [%0], {%1,%2};" ::"r"(a), "f"(v), "f"(w) : "memory"); }

__device__ __forceinline__ uint32_t prmt(uint32_t a, uint32_t b, uint32_t s) { uint32_t r; asm("prmt.b32 %0, %1, %2, %3;" : "=r"(r) : "r"(a), "r"(b), "r"(s)); return r; }
__device__ __forceinline__ uint32_t bmul2(uint32_t a, uint32_t b) { uint32_t r; asm("mul.rn.bf16x2 %0, %1, %2;" : "=r"(r) : "r"(a), "r"(b)); return r; }
__device__ __forceinline__ void sts128(uint32_t addr, uint32_t a, uint32_t b, uint32_t c, uint32_t d) {
    asm volatile("st.shared.v4.u32 [%0], {%1,%2,%3,%4};" ::"r"(addr), "r"(a), "r"(b), "r"(c), "r"(d) : "memory");
}
__device__ __forceinline__ uint4 ldg128(const uint4* p) {
    uint4 v;
    asm volatile("ld.volatile.global.v4.u32 {%0,%1,%2,%3}, [%4];" : "=r"(v.x), "=r"(v.y), "=r"(v.z), "=r"(v.w) : "l"(p) : "memory");
    return v;
}
__device__ __forceinline__ uint32_t lds32(uint32_t a) { uint32_t v; asm volatile("ld.shared.u32 %0, [%1];" : "=r"(v) : "r"(a) : "memory"); return v; }
__device__ __forceinline__ uint32_t lds16(uint32_t a) { unsigned short v; asm volatile("ld.shared.u16 %0, [%1];" : "=h"(v) : "r"(a) : "memory"); return v; }
__device__ __forceinline__ void unpack8(uint32_t la, uint32_t lb, uint32_t c, uint32_t (&w)[4]) {
    const uint32_t ha = c & 0x87878787u, hb = __funnelshift_l(c, c, 4) & 0x87878787u;
    w[0] = prmt(la, ha, 0x5140); w[1] = prmt(la, ha, 0x7362); w[2] = prmt(lb, hb, 0x5140); w[3] = prmt(lb, hb, 0x7362);
}
__device__ __forceinline__ uint32_t bdiff2(uint32_t y, uint32_t inv, uint32_t x) {
    uint32_t r;
    asm("{\n.reg .b32 n;\nneg.bf16x2 n, %3;\nfma.rn.bf16x2 %0, %1, %2, n;\n}" : "=r"(r) : "r"(y), "r"(inv), "r"(x));
    return r;
}
__device__ __forceinline__ uint32_t pack_scale(uint32_t tile, int lane, uint32_t inv_addr) {
    uint32_t m = 0;
#pragma unroll 1
    for (int k = 0; k < 12; k++) {
        uint32_t a, b, c, d;
        lds128(tile + k * 512 + lane * 16, a, b, c, d);
        asm("max.xorsign.abs.bf16x2 %0, %0, %1;" : "+r"(a) : "r"(b));
        asm("max.xorsign.abs.bf16x2 %0, %0, %1;" : "+r"(c) : "r"(d));
        asm("max.xorsign.abs.bf16x2 %0, %0, %1;" : "+r"(a) : "r"(c));
        asm("max.xorsign.abs.bf16x2 %0, %0, %1;" : "+r"(m) : "r"(a));
    }
    m = __reduce_max_sync(0xffffffffu, max(m & 0x7fffu, (m >> 16) & 0x7fffu));
    const uint32_t inv = (112u + min((m + 0x28u) >> 7, 141u)) * 0x00800080u;
    if (lane == 0) asm volatile("st.shared.u32 [%0], %1;" ::"r"(inv_addr), "r"(inv) : "memory");
    return inv;
}

#define K_OFF(i) ((uint32_t)((3 * ((g >> 1) + 4 * (g & 1)) + ((i) >> 1)) * 128 + ((t ^ ((3 * ((g >> 1) + 4 * (g & 1)) + ((i) >> 1)) & 7) ^ (((i) & 1) << 2)) << 4)))
#define V_OFF(i) ((uint32_t)((6 * t + (i)) * 128 + ((g ^ ((6 * t + (i)) & 7)) << 4)))
template <bool ISV, typename DST>
__device__ __forceinline__ void pack_tile(uint32_t tile, int tau, int nm, uint32_t inv, uint32_t xl, int lane, DST dst) {
    const int g = lane >> 2, t = lane & 3;
    const uint32_t scl = 254u * 0x00800080u - inv;
#pragma unroll 1
    for (int m = 0; m < nm; m++) {
        const int row = ISV ? 6 * t + 2 * m : 3 * ((g >> 1) + 4 * (g & 1)) + m;
        const uint32_t a0 = tile + row * 128 + (((ISV ? g : t) ^ (row & 7)) << 4), a1 = ISV ? (a0 ^ 16) + 128 : a0 ^ 64;
        uint32_t l[8], cw[4], ck = 0, cd = 0;
#pragma unroll
        for (int r = 0; r < 4; r++) {
            uint32_t w0, w1, w2, w3;
            lds128(((r & 1) ? a1 : a0) + (r >> 1) * 3072, w0, w1, w2, w3);
            const uint32_t y0 = bmul2(w0, scl), y1 = bmul2(w1, scl), y2 = bmul2(w2, scl), y3 = bmul2(w3, scl);
            cd |= bdiff2(y0, inv, w0) | bdiff2(y1, inv, w1);
            cd |= bdiff2(y2, inv, w2) | bdiff2(y3, inv, w3);
            const uint32_t ha = prmt(y0, y1, 0x7531), hb = prmt(y2, y3, 0x7531);
            l[2 * r] = prmt(y0, y1, 0x6420); l[2 * r + 1] = prmt(y2, y3, 0x6420);
            asm("lop3.b32 %0, %1, 0x87878787, %2, 0xe2;" : "=r"(cw[r]) : "r"(ha), "r"(__funnelshift_r(hb, hb, 4)));
            ck |= ha | hb;
        }
        const uint32_t bad = __ballot_sync(0xffffffffu, (ck & 0x78787878u) | cd);
        if (bad) {
            const int src = __ffs(bad) - 1;
            const uint32_t b0 = __shfl_sync(0xffffffffu, a0, src), b1 = __shfl_sync(0xffffffffu, a1, src), n0 = lds32(xl);
            const uint32_t ax = ((lane & 8) ? b1 : b0) + (lane >> 4) * 3072 + 2 * (lane & 7), x = lds16(ax), y = bmul2(x, scl);
            const bool out = (y & 0x7800u) | bdiff2(y, inv, x);
            const uint32_t n = n0 + __popc(__ballot_sync(0xffffffffu, out) << (31 - lane)) - 1;
            if (out) {
                asm volatile("st.shared.u16 [%0], %1;" ::"r"(ax), "h"((unsigned short)0) : "memory");
                if (n < XCAP) sts32(xl + 16 + 4 * n, f_(x << 16 | tau << 12 | src << 7 | m << 5 | lane));
            }
            if (lane == 31) sts32(xl, f_(n + 1));
            __syncwarp();
            if (n0 <= XCAP) { m--; continue; }
        }
        uint32_t d[3] = {a0, a1, a0 + 3072};
        dst(m, d);
        sts128(d[0], l[0], l[1], l[2], l[3]);
        sts128(d[1], l[4], l[5], l[6], l[7]);
        sts128(d[2], cw[0], cw[1], cw[2], cw[3]);
    }
}

struct Maps { CUtensorMap k, v, wq, wo, w1, w3, w2, vr; const void* vp; const void* kp; uint32_t zero; };
#define RT_SEL ((wu & 1) ? RT_MASK2 : RT_MASK)
#define PFK 5
#define Q_AT 3
#define WO_T0 33200
#define K5D 250
#define PK_AT 6

__device__ __forceinline__ void load_ffn(const Maps& maps, int b, uint32_t dst, uint32_t bar) {
    const bool gu = b < NG;
    mbar_expect_tx(bar, gu ? 61440 : 49152);
    tma3d(dst, gu ? (b < NG / 2 ? &maps.w1 : &maps.w3) : &maps.w2, gu ? 48 * (b & (NG / 2 - 1)) : 16 * (b - DN0), 0, 0, bar, FFN_POL);
}

__device__ __forceinline__ void load_wo(const Maps& maps, uint32_t dst, int h, int c, uint32_t bar, int nbox) {
#pragma unroll 1
    for (int i = 0; i < nbox; i++) {
        if (!(i & 1)) mbar_expect_tx(bar + 4 * i, i + 1 < nbox ? 20480 : 10240);
        tma3d(dst + i * 10240, &maps.wo, 0, 5 * c, h * DH + 32 * i, bar + 4 * (i & 6), POL_EF);
    }
}

__global__ void __launch_bounds__(NT, 1)
decode_kernel(const __grid_constant__ Maps maps, const __nv_bfloat16* __restrict__ x_in, __nv_bfloat16* __restrict__ out) {
    extern __shared__ __align__(1024) unsigned char smem[];
    const int tid = threadIdx.x, warp = tid >> 5, lane = tid & 31;
    const int wu = __shfl_sync(0xffffffffu, tid >> 5, 0);
    const int b = blockIdx.x, h = b >> 2, c = b & 3;
    const uint32_t sb = smem_u32(smem);
    const uint32_t qbar = sb + SM_BAR + 16 * 8, fbar = qbar + 8, wbar = qbar + 16;
    uint32_t* xs32 = reinterpret_cast<uint32_t*>(smem + SM_XS);
    float* rr = reinterpret_cast<float*>(smem + SM_R);
    float* misc = reinterpret_cast<float*>(smem + SM_MISC);

    PROF_T(0);
    {
        uint2 xv = make_uint2(0u, 0u);
        const uint32_t t_start = now_ns();
        if (elect_one()) {
            const uint32_t rb = sb + SM_BAR + wu * 16, xb = sb + SM_XBAR + wu * 8;
            mbar_init(rb, 1); mbar_init(rb + 8, 1); mbar_init(xb, 1);
            if (wu == 0) mbar_init(qbar, 1);
            asm volatile("fence.mbarrier_init.release.cluster;" ::: "memory");
            const int row = (h * SK + (SK - WIN) + c * 1024 + wu * 128) * 3;
            const uint32_t ring = sb + SM_RING + wu * 2 * TILE;
#pragma unroll
            for (int n = 0; n < 3; n++) {
                const uint32_t bar = ((IN_S1 >> n) & 1) ? rb + 8 : ((IN_S0 >> n) & 1) ? rb : xb;
                mbar_expect_tx(bar, TILE);
                tma2d(((IN_S1 >> n) & 1) ? ring + TILE : ((IN_S0 >> n) & 1) ? ring : sb + SM_B + wu * TILE, &maps.k, 0, row + 48 * n, bar, POL_EF);
                if (n == 0 && wu == 0) {
                    mbar_expect_tx(qbar, 61440);
                    tma3d(sb + SM_Q, &maps.wq, 0, 160 * c, 3 * h, qbar, POL_EF);
                }
            }
            if (wu == 1) {
                mbar_init(fbar, 1);
#pragma unroll
                for (int i = 0; i < 3; i++) mbar_init(wbar + 8 * i, 1);
                asm volatile("fence.mbarrier_init.release.cluster;" ::: "memory");
            }
            if (wu >= 2) {
                const CUtensorMap* mp = wu == 2 ? &maps.v : wu == 3 ? &maps.wo : wu == 4 ? &maps.w1 : wu == 5 ? &maps.w3 : wu == 6 ? &maps.w2 : &maps.vr;
                asm volatile("prefetch.tensormap [%0];" ::"l"(mp) : "memory");
            }
        }
        if (tid < 160) asm volatile("ld.global.nc.v2.u32 {%0,%1}, [%2];" : "=r"(xv.x), "=r"(xv.y) : "l"(x_in + 4 * tid) : "memory");
        if (tid == 96) { misc[2] = 0.f; misc[3] = 0.f; }
        if (lane == 1) *reinterpret_cast<uint2*>(smem + SM_XL + warp * XSTR) = make_uint2(0u, t_start + WO_T0);
        if (tid >= 128 && tid < 148) {
            const uint32_t v = tid < 138 ? ONES : 0u;
            reinterpret_cast<uint4*>(smem + SM_ONE)[tid - 128] = make_uint4(v, v, v, v);
        }
        if (tid < 160) { xs32[xpos(2 * tid)] = xv.x; xs32[xpos(2 * tid + 1)] = xv.y; }
        __syncthreads();
        PROF_T(14);
        if (b == 0 && tid >= 232) asm volatile("st.relaxed.gpu.global.u32 [%0], %1;" ::"l"(g_scr.ticket + tid - 232), "r"(0) : "memory");
        if (tid == 64 || (tid == 65 && b < 216 - NCTA)) st_pkt(&g_scr.acc[1][acc_pos(b + NCTA * (tid - 64))], 0, 0, 0, 0);
    }

    uint32_t kq[NQ][4];
    const float SC = 0.07216878364870322f * 1.4426950408889634f;

#pragma unroll 1
    for (int ph = 0; ph < 3; ph++) {
        const int layer = ph >> 1;
        const uint32_t tag = layer + 1;
        PROF_T(1 + layer * 16);
        if (ph) {
        {
            const int tl = opq(tid), warp = tl >> 5, lane = tl & 31, g = lane >> 2, t = lane & 3, mat = lane >> 3, r8 = lane & 7;
            const int kh = warp >> 2, mg = warp & 3;
            uint32_t aq[3];
#pragma unroll
            for (int i = 0; i < 3; i++) {
                const int ch = 6 * mg + 2 * i + (mat & 1);
                aq[i] = sb + SM_Q + (80 * kh + (mat >> 1) * 8 + r8) * 128 + (ch >> 3) * 20480 + (((ch & 7) ^ r8) << 4);
            }
#define PF_K5 if (layer == 1 && PFK) tile_keep(&maps.k, (h * SK + (SK - WIN) + c * 1024 + wu * 128 + PFK * 16) * 3);
            uint2 xv = make_uint2(0u, 0u);
            mbar_wait(qbar, 0);
            uint32_t pre[6][4];
#pragma unroll
            for (int n = 0; n < 6; n++) ldsm4t(aq[n % 3] + (n / 3) * 2048, pre[n]);
            if (layer == 1) {
                __syncthreads();
                if (elect_one()) {
                    const uint32_t bar = sb + SM_BAR + wu * 16;
                    asm volatile("mbarrier.expect_tx.relaxed.cta.shared::cta.b64 [%0], 1536;" ::"r"(bar) : "memory");
#pragma unroll
                    for (int k = 0; k < 3; k++)
                        tma2d(sb + SM_Q + v1_pos(3 * wu + k), &maps.vr, 0, (h * SK + (SK - WIN) + c * 1024 + wu * 128) / 2 + 8 + 2 * k, bar, POL_EF);
                }
            }
            const uint32_t pm = opq(g == 1 ? sb + SM_ONE : sb + SM_XS + 160 * (2 * c + kh) + 16 * t), pm2 = opq(pm + 128 - (g == 1 ? 0 : 8 * t));
            const uint32_t dq = opq(sb + SM_R + 8 * (kh * 192 + 48 * mg + g)), ds = opq(sb + SM_ST + 8 * warp + (lane < 16 ? 4 : 0));
            const bool wr = t == 0, ws = (lane & 15) == 0, lo = lane < 16;
            if (wu < 5) {
                const int p0 = xpos(2 * tl), p1 = xpos(2 * tl + 1);
                if (layer == 1) {
                    uint4 v;
                    for (int it = 0; it < SPIN_CAP; it++) { v = ld_pkt(&g_scr.ay[tl]); if (__all_sync(0xffffffffu, v.w == 1)) break; }
                    xv = make_uint2(v.x, v.y);
                    xs32[p0] = xv.x; xs32[p1] = xv.y;
                } else xv = make_uint2(xs32[p0], xs32[p1]);
            }
            if (layer) PC(24);
            __syncthreads();
            PF_K5
            if (layer) PC(25);
            PROF_T(13 + layer * 16);
            const float e0 = bf_lo(xv.x), e1 = bf_hi(xv.x), e2 = bf_lo(xv.y), e3 = bf_hi(xv.y);
            const float s1 = (e0 + e1) + (e2 + e3), s2 = (e0 * e0 + e1 * e1) + (e2 * e2 + e3 * e3);
            float sv = lo ? s1 : s2, cc[3][4];
            gemv15<2048>(cc, pre, [&](int i) { return aq[i]; }, pm, pm2, sv, lo ? s2 : s1);
            if (wr) {
#pragma unroll
                for (int i = 0; i < 3; i++) { sts64(dq + 128 * i, cc[i][0], cc[i][1]); sts64(dq + 128 * i + 64, cc[i][2], cc[i][3]); }
            }
            if (ws) sts32(ds, sv);
        }
        const uint32_t pa = opq(sb + SM_R + 32 * opq(tid)), st = opq(sb + SM_ST);
        uint4* const pq = opq(&g_scr.hx[b * 48 + opq(tid)]);
        if (layer) PC(26);
        __syncthreads();
        if (layer) PC(27);
        PROF_T(33 + layer * 16);
        if (wu < 2) {
            float mean, inv;
            ln_stats(st, mean, inv);
            const float4 a0 = lds4f(pa), a1 = lds4f(pa + 16), b0 = lds4f(pa + 1536), b1 = lds4f(pa + 1552);
            const float q0 = (a0.x + b0.x) - mean * (a0.y + b0.y), q1 = (a0.z + b0.z) - mean * (a0.w + b0.w);
            const float q2 = (a1.x + b1.x) - mean * (a1.y + b1.y), q3 = (a1.z + b1.z) - mean * (a1.w + b1.w);
            st_pktfp(pq, q0, q1, q2, q3, 1, tid < 48);
        }
        if (layer == 1 && tid >= 192 && tid < 194 && b < 108) st_pkt(&g_scr.acc[0][acc_pos(2 * b + opq(tid) - 192)], 0, 0, 0, 0);
        }
        if (layer) PC(28);
        if (layer == 1 && (wu & 2)) {
            idle(K5D);
            tile_load(sb + SM_Q + c_slot(wu), &maps.k, (h * SK + (SK - WIN) + c * 1024 + wu * 128 + 5 * 16) * 3, sb + SM_XBAR + wu * 8, 0, 0);
        }

        float sc0 = -INFINITY, sc1 = -INFINITY, sc2 = 0.f, sc3 = 0.f, mw;
        uint32_t pk0, pk1;
        float acc[3][4];
        {
            const uint32_t ring = sb + SM_RING + wu * 2 * TILE, rb = sb + SM_BAR + wu * 16;
            const uint32_t xtile = sb + SM_Q + c_slot(wu), xb = sb + SM_XBAR + wu * 8;
#define V_SEQ(n) ((int)(SEQ1 >> (4 * (n))) & 7)
#define SLOT1(n) (((IN_S1 >> (n)) & 1) ? ring + TILE : ((IN_S0 >> (n)) & 1) ? ring : sb + SM_B + wu * TILE)
#define BAR1(n) (((IN_S1 >> (n)) & 1) ? rb + 8 : ((IN_S0 >> (n)) & 1) ? rb : xb)
#define PAR1(n) ((PARITY1 >> (n)) & 1)
#define PAR2(n) ((PARITY2 >> (n)) & 1)
            const int row0 = (h * SK + (SK - WIN) + c * 1024 + wu * 128) * 3;
            auto issue1 = [&](int n, uint32_t dep, bool vph = false) {
                const CUtensorMap* mp = n < 8 ? &maps.k : &maps.v;
                const int tl = V_SEQ(n), row = row0 + tl * 48;
                const uint32_t dst = SLOT1(n), bar = BAR1(n);
                if (vph && wu < L1R && tl == 7 - (wu & 1)) {
                    tile_load_l1(dst, maps.vp, row, bar, opq(tid) & 31);
                    return;
                }
                tile_load(dst, mp, row, bar, dep, maps.zero);
                if ((RT_SEL >> (tl + (n & 8))) & 1) {
                    if (n != V0_AT + 1) tile_keep(mp, row);
                    else if ((opq(tid) & 31) < 8)
                        asm volatile("cp.async.bulk.prefetch.L2.global.L2::cache_hint [%0], 256, %1;"
                                     ::"l"(static_cast<const char*>(maps.vp) + (size_t)(row + 4 + 6 * (opq(tid) & 31)) * 128), "l"(POL_EN) : "memory");
                }
            };
            auto refill1 = [&](int s, uint32_t dep, bool vph = false) { issue1(s + (!vph || s < V0_AT ? 3 : 2), dep, vph); };
#define LANE_IDS const int tl = opq(tid), lane = tl & 31, g = lane >> 2, t = lane & 3; (void)tl; (void)lane; (void)g; (void)t;
            const uint32_t xl = sb + SM_XL + wu * XSTR;
            if (layer == 0) {
#pragma unroll 1
                for (int s = ph ? Q_AT : 0; s < (ph ? 5 : Q_AT); s++) {
                    LANE_IDS
                    const uint32_t tile = SLOT1(s);
                    mbar_wait(BAR1(s), PAR1(s));
                    const uint32_t scl = s == 0 ? pack_scale(tile, lane, xl + 8) : lds32(xl + 8);
                    pack_tile<false>(tile, s, 3, scl, xl, lane, [](int, uint32_t (&)[3]) {});
#pragma unroll
                    for (int n = 0; n < 5; n++) {
                        if (s == n) {
#pragma unroll
                            for (int m = 0; m < 3; m++) {
                                const uint32_t a = tile + K_OFF(2 * m);
                                lds128(a, kq[9 * n + 3 * m][0], kq[9 * n + 3 * m][1], kq[9 * n + 3 * m][2], kq[9 * n + 3 * m][3]);
                                lds128(a ^ 64, kq[9 * n + 3 * m + 1][0], kq[9 * n + 3 * m + 1][1], kq[9 * n + 3 * m + 1][2], kq[9 * n + 3 * m + 1][3]);
                                lds128(a + 3072, kq[9 * n + 3 * m + 2][0], kq[9 * n + 3 * m + 2][1], kq[9 * n + 3 * m + 2][2], kq[9 * n + 3 * m + 2][3]);
                            }
                        }
                    }
                    __syncwarp();
                    refill1(s, lds32(tile));
                }
                if (!ph) continue;
            }
            {
                if (wu < 2) {
                    const int tl = min(opq(tid), 47);
                    const int w = 2 * tl;
                    const uint32_t pos = opq(sb + SM_QS + 4 * (((w >> 2) & 3) * 24 + 2 * (w >> 4) + ((w >> 1) & 1)));
                    uint4 v[4];
                    float mean, inv;
                    ln_stats(opq(sb + SM_ST), mean, inv);
                    for (int it = 0; it < SPIN_CAP; it++) {
#pragma unroll
                        for (int k = 0; k < 4; k++) v[k] = ld_pkt(&g_scr.hx[(h * 4 + k) * 48 + tl]);
                        if (all_odd(v[0].w, v[1].w, v[2].w, v[3].w)) break;
                    }
                    sts32(pos, f_(pack2(inv * ((f_(v[0].x) + f_(v[1].x)) + (f_(v[2].x) + f_(v[3].x))), inv * ((f_(v[0].y) + f_(v[1].y)) + (f_(v[2].y) + f_(v[3].y))))));
                    sts32(pos + 48, f_(pack2(inv * ((f_(v[0].z) + f_(v[1].z)) + (f_(v[2].z) + f_(v[3].z))), inv * ((f_(v[0].w) + f_(v[1].w)) + (f_(v[2].w) + f_(v[3].w))))));
                }
            }
            if (layer) PC(29);
            __syncthreads();
            if (layer) PC(30);
            PROF_T(2 + layer * 16);
#define V1_REST(p) ((p) < 6 ? sb + SM_Q + v1_pos(3 * wu + ((p) >> 1)) + 256 * ((p) & 1) : ((sb + SM_R + wu * 784 + 127) & ~127u) - 1536 + 256 * (p))
#define V1_LOAD(bar) if (elect_one()) tma2d(V1_REST(6), &maps.vr, 0, row0 / 6 + 14, bar, POL_EF);
#define V1_EXPECT(bar) { if ((opq(tid) & 31) == 0) asm volatile("mbarrier.expect_tx.relaxed.cta.shared::cta.b64 [%0], 512;" ::"r"(bar) : "memory"); }
            if (layer == 1 && !(wu & 2)) tile_load(xtile, &maps.k, row0 + 5 * 48, xb, 0, 0);
            if (layer == 1 && wu >= 4) idle(STAG);
            {
                uint32_t qf[12];
                int t;
                {
                    const int lane = opq(tid) & 31;
                    t = lane & 3;
                    const uint32_t qa = sb + SM_QS + (2 * t + ((lane >> 2) & 1)) * 48;
#pragma unroll
                    for (int i = 0; i < 3; i++) lds128(qa + 16 * i, qf[4 * i], qf[4 * i + 1], qf[4 * i + 2], qf[4 * i + 3]);
                }
                const uint32_t sq = lds32(xl + 8) - 64u * 0x00800080u;
#pragma unroll
                for (int i = 0; i < 12; i++) qf[i] = bmul2(qf[i], sq);
#define KR_STEP(tau, m) \
                    _Pragma("unroll") for (int i = 2 * (m); i < 2 * (m) + 2; i++) { \
                        const int q0 = 9 * tau + 3 * (i >> 1), r = i & 1; \
                        uint32_t w[4]; \
                        unpack8(kq[q0][2 * r], kq[q0][2 * r + 1], kq[q0 + 2][r], w); \
                        mma16816(cA, w[0], w[1], w[2], w[3], qf[2 * i], qf[2 * i + 1]); \
                        unpack8(kq[q0 + 1][2 * r], kq[q0 + 1][2 * r + 1], kq[q0 + 2][2 + r], w); \
                        mma16816(cB, w[0], w[1], w[2], w[3], qf[2 * i], qf[2 * i + 1]); \
                    }
#define KR_BEGIN float cA[4] = {0.f, 0.f, 0.f, 0.f}, cB[4] = {0.f, 0.f, 0.f, 0.f};
#define KR_END(tau) \
                    const float sA = (cA[0] + cA[3]) * 18446744073709551616.f, sB = (cB[0] + cB[3]) * 18446744073709551616.f; \
                    if (t == (tau & 3)) { if (tau < 4) { sc0 = sA; sc1 = sB; } else { sc2 = sA; sc3 = sB; } }
#define KR_SCORES(tau) { KR_BEGIN KR_STEP(tau, 0) KR_STEP(tau, 1) KR_STEP(tau, 2) KR_END(tau) }
                uint32_t va[3];
                {
                    const int lane = opq(tid) & 31, g = lane >> 2, t = lane & 3;
#pragma unroll
                    for (int i = 0; i < 3; i++) va[i] = ring + V_OFF(2 * i);
                }
#define V_STG(n) _Pragma("unroll") for (int j = 3 * (n); j < 3 * (n) + 3; j++) { \
                    const int i = (j % 12) >> 1; \
                    lds128p(((i & 1) ? (va[i >> 1] ^ 16) + 128 : va[i >> 1]) + (j / 12) * TILE + (j & 1) * 3072, layer, kq[j][0], kq[j][1], kq[j][2], kq[j][3]); }
                uint32_t dep = 0;
                {
                    KR_BEGIN
                    KR_STEP(0, 0) V_STG(0) KR_STEP(0, 1) V_STG(1) KR_STEP(0, 2) V_STG(2)
                    KR_END(0)
                }
                {
                    KR_BEGIN
                    KR_STEP(1, 0) V_STG(3)
                    __syncwarp();
                    dep = lds32(ring);
                    if (layer == 1) tile_load(ring, &maps.k, row0 + 6 * 48, rb, dep, maps.zero);
                    KR_STEP(1, 1) V_STG(4) KR_STEP(1, 2) V_STG(5)
                    KR_END(1)
                }
                {
                    KR_BEGIN
                    KR_STEP(2, 0) V_STG(6) KR_STEP(2, 1) V_STG(7)
                    __syncwarp();
                    dep = lds32(ring + TILE);
                    KR_STEP(2, 2)
                    if (layer == 1) {
                        V1_EXPECT(rb + 8)
                        tile_load(ring + TILE, &maps.k, row0 + 7 * 48, rb + 8, dep, maps.zero);
                        V1_LOAD(rb + 8)
                    }
                    KR_END(2)
                }
#pragma unroll 1
                for (int s = 5; s < 8; s++) {
                    {
                        LANE_IDS
                        const uint32_t tile = !layer ? SLOT1(s) : s == 5 ? xtile : ring + (s - 6) * TILE, tb = !layer ? BAR1(s) : s == 5 ? xb : rb + (s - 6) * 8;
                        const float ur = f_((318u << 23) - (lds32(xl + 8) << 16));
                        mbar_wait(tb, layer ? PAR2(s - 5) : PAR1(s));
                        if (layer) PROF_T(29 + s);
                        float cA[4] = {0.f, 0.f, 0.f, 0.f}, cB[4] = {0.f, 0.f, 0.f, 0.f};
#pragma unroll
                        for (int i = 0; i < 6; i++) {
                            uint32_t a0, a1, a2, a3;
                            lds128(tile + K_OFF(i), a0, a1, a2, a3);
                            mma16816(cA, a0, a1, a2, a3, qf[2 * i], qf[2 * i + 1]);
                            lds128(tile + K_OFF(i) + 3072, a0, a1, a2, a3);
                            mma16816(cB, a0, a1, a2, a3, qf[2 * i], qf[2 * i + 1]);
                        }
                        __syncwarp();
                        const uint32_t last = lds32(tile);
                        if (layer) tile_load(tile, &maps.v, row0 + (s - 2) * 48, tb, last, maps.zero);
                        else refill1(s, last);
                        if (t == (s & 3)) { sc2 = (cA[0] + cA[3]) * ur; sc3 = (cB[0] + cB[3]) * ur; }
                    }
                    if (s == 5) KR_SCORES(3)
                    if (s == 6) {
                        KR_SCORES(4)
                        const int lane = opq(tid) & 31;
                        const uint32_t nx = min(lds32(xl), (uint32_t)XCAP);
#pragma unroll 1
                        for (uint32_t n = 0; n < nx; n++) {
                            const uint32_t id = lds32(xl + 16 + 4 * n);
                            const uint32_t qo = 96 * ((id >> 7) & 3) + 48 * ((id >> 1) & 1) + 16 * ((id >> 5) & 3) + (id & 12) + 2 * (id & 1);
                            const float cr = bf_hi(id) * f_(lds16(sb + SM_QS + qo) << 16);
                            const int d = (int)(16 * ((id >> 9) & 7) + 4 * ((id >> 12) & 3) + ((id >> 13) & 2) + ((id >> 4) & 1) + ((id >> 8) & 128)) - 4 * lane;
                            if (d == 0) sc0 += cr;
                            if (d == 1) sc1 += cr;
                            if (d == 2) sc2 += cr;
                            if (d == 3) sc3 += cr;
                        }
                    }
                }
#undef KR_SCORES
#undef KR_STEP
#undef KR_BEGIN
#undef KR_END
#undef V_STG
                {
                    LANE_IDS
                    if (lds32(xl) > XCAP || !__all_sync(0xffffffffu, (fabsf(sc0) + fabsf(sc1)) + (fabsf(sc2) + fabsf(sc3)) < INFINITY)) {
                        const uint32_t qa = sb + SM_QS + (2 * t + (g & 1)) * 48;
#pragma unroll
                        for (int i = 0; i < 3; i++) lds128(qa + 16 * i, qf[4 * i], qf[4 * i + 1], qf[4 * i + 2], qf[4 * i + 3]);
                        const uint4* kg = reinterpret_cast<const uint4*>(static_cast<const char*>(maps.kp) + (size_t)row0 * 128) + ((g >> 1) + 4 * (g & 1)) * 24 + t;
#pragma unroll 1
                        for (int s = 0; s < 8; s++) {
                            float cA[4] = {0.f, 0.f, 0.f, 0.f}, cB[4] = {0.f, 0.f, 0.f, 0.f};
#pragma unroll
                            for (int i = 0; i < 6; i++) {
                                uint4 u = ldg128(kg + s * 384 + 4 * i);
                                mma16816v(cA, u.x, u.y, u.z, u.w, qf[2 * i], qf[2 * i + 1]);
                                u = ldg128(kg + s * 384 + 4 * i + 192);
                                mma16816v(cB, u.x, u.y, u.z, u.w, qf[2 * i], qf[2 * i + 1]);
                            }
                            if (t == s) { sc0 = cA[0] + cA[3]; sc1 = cB[0] + cB[3]; }
                            if (t + 4 == s) { sc2 = cA[0] + cA[3]; sc3 = cB[0] + cB[3]; }
                        }
                    }
                }
            }
            mw = warp_max(fmaxf(fmaxf(sc0, sc1), fmaxf(sc2, sc3)));
            pk0 = pack2(ex2((sc0 - mw) * SC), ex2((sc1 - mw) * SC));
            pk1 = pack2(ex2((sc2 - mw) * SC), ex2((sc3 - mw) * SC));
            sc2 = (bf_lo(pk0) + bf_hi(pk0)) + (bf_lo(pk1) + bf_hi(pk1));
            sc2 = (float)__reduce_add_sync(0xffffffffu, __float2uint_rn(sc2 * 16777216.f)) * (1.0f / 16777216.f);
            if ((opq(tid) & 31) == 0) st_pkt2(&g_scr.mx[h * 32 + c * 8 + wu], __float_as_uint(mw), (__float_as_uint(sc2) & ~3u) | tag);
            auto head_factor = [&]() {
                const int lane = opq(tid) & 31;
                int it = 0;
                while (!__all_sync(0xffffffffu, (__float_as_uint(sc1) & 3u) == tag) && ++it < SPIN_CAP) {
                    const uint2 mv = ld_pkt2(&g_scr.mx[h * 32 + lane]); sc0 = f_(mv.x); sc1 = f_(mv.y);
                }
                const float e = ex2((sc0 - warp_max(sc0)) * SC);
                const uint32_t d = __reduce_add_sync(0xffffffffu, __float2uint_rn(sc1 * e * 524288.f));
                sc3 = __shfl_sync(0xffffffffu, e, c * 8 + wu) * 524288.f * rcp((float)d);
            };
#pragma unroll
            for (int s = 0; s < 3; s++) { acc[s][0] = acc[s][1] = acc[s][2] = acc[s][3] = 0.f; }
#define P_CONSTS \
                const uint32_t sel0 = g == 0 ? 0x4410u : (g == 1 ? 0x1044u : 0x4444u); \
                const uint32_t sel1 = g == 2 ? 0x4410u : (g == 3 ? 0x1044u : 0x4444u); \
                const int src00 = 4 * (t < 2 ? 4 * t : 4 * (t - 2) + 1);
#define P_FRAGS(tau) \
                const uint32_t pk = ((tau) & 4) ? pk1 : pk0; \
                const uint32_t w0 = __shfl_sync(0xffffffffu, pk, src00 + ((tau) & 3)); \
                const uint32_t w1 = __shfl_sync(0xffffffffu, pk, src00 + ((tau) & 3) + 8); \
                uint32_t pb[4][2]; \
                _Pragma("unroll") for (int j = 0; j < 4; j++) { \
                    const uint32_t src = ((j & 1) ? w1 : w0) >> ((j >> 1) * 16); \
                    pb[j][0] = __byte_perm(src, 0, sel0); pb[j][1] = __byte_perm(src, 0, sel1); \
                }
            if (layer == 0) {
#pragma unroll 1
                for (int s = 8; s < 16; s++) {
                    LANE_IDS
                    P_CONSTS
                    if (s == 13) { const uint2 mv = ld_pkt2(&g_scr.mx[h * 32 + lane]); sc0 = f_(mv.x); sc1 = f_(mv.y); }
                    P_FRAGS(V_SEQ(s))
                    mbar_wait(BAR1(s), PAR1(s));
                    const uint32_t tile = SLOT1(s);
#pragma unroll
                    for (int j = 0; j < 4; j++) {
#pragma unroll
                        for (int u = 0; u < 3; u++) {
                            uint32_t a0, a1, a2, a3;
                            lds128(tile + (j >> 1) * 3072 + V_OFF(3 * (j & 1) + u), a0, a1, a2, a3);
                            mma16816(acc[u], a0, a1, a2, a3, pb[j][0], pb[j][1]);

                        }
                    }
                    __syncwarp();
                    if (s < V0_AT || (s > V0_AT + 1 && s < 14)) refill1(s, lds32(tile), true);
                    if (s == V0_AT || s == V0_AT + 1) {
                        {
                            const uint32_t ar = sb + SM_R + wu * 784 + 32 * g + 16 * t;
                            if (t < 2) {
#pragma unroll
                                for (int u = 0; u < 3; u++) sts128(ar + 256 * u, __float_as_uint(acc[u][0]), __float_as_uint(acc[u][1]), __float_as_uint(acc[u][2]), __float_as_uint(acc[u][3]));
                            }
                        }
                        const uint32_t scl = s == V0_AT ? pack_scale(tile, lane, xl + 12) : lds32(xl + 12);
                        pack_tile<true>(tile, s + 8 - V0_AT, V0_AT + 3 - s, scl, xl, lane, [&](int m, uint32_t (&d)[3]) {
                            if (s != V0_AT && m == 0) {
#pragma unroll
                                for (int k = 0; k < 3; k++) d[k] = ring + 3072 + V_OFF(2 * k + 1);
                            }
                        });
                        if (s != V0_AT) {
                            lds128(tile + V_OFF(2), kq[45][0], kq[45][1], kq[45][2], kq[45][3]);
                            lds128(tile + V_OFF(3), kq[46][0], kq[46][1], kq[46][2], kq[46][3]);
                            lds128(tile + V_OFF(2) + 3072, kq[47][0], kq[47][1], kq[47][2], kq[47][3]);
                            __syncwarp();
                            issue1(V0_AT + 3, lds32(tile));
                        }
                        const int ln = opq(tid) & 31;
                        const uint32_t ar = sb + SM_R + wu * 784 + 8 * (ln & 28) + 16 * (ln & 1);
#pragma unroll
                        for (int u = 0; u < 3; u++) {
                            uint32_t a0, a1, a2, a3;
                            lds128(ar + 256 * u, a0, a1, a2, a3);
                            acc[u][0] = f_(a0); acc[u][1] = f_(a1); acc[u][2] = f_(a2); acc[u][3] = f_(a3);
                        }
                    }
                    if (s == 13) head_factor();
                    if (s >= 14 && elect_one()) {
                        if (atomicAdd(reinterpret_cast<unsigned*>(misc + 3), 1u) == 14u && (int)(now_ns() - lds32(xl + 4)) >= 0) {
                            PROF_X(47);
                            load_wo(maps, sb + SM_B, h, c, wbar, 6);
                            atomicAdd(reinterpret_cast<unsigned*>(misc + 3), 256u);
                        }
                    }
                }
            } else {
                LANE_IDS
                P_CONSTS
#pragma unroll
                for (int k = 0; k < 4; k++) lds128(V1_REST(t + 4 * (k >> 1)) + 16 * g + 128 * (k & 1), kq[36 + k][0], kq[36 + k][1], kq[36 + k][2], kq[36 + k][3]);
#pragma unroll 1
                for (int i = 3; i < 8; i++) {
                    const uint32_t tile = i > 3 ? ring + (i & 1) * TILE : xtile, tb = i > 3 ? rb + (i & 1) * 8 : xb;
                    if (i == 6) { const uint2 mv = ld_pkt2(&g_scr.mx[h * 32 + lane]); sc0 = f_(mv.x); sc1 = f_(mv.y); }
                    if (i == 7) head_factor();
                    if (i == PK_AT) {
                uint32_t nx, nk, ik, iv;
                lds128(xl, nx, nk, ik, iv);
                if (nx <= XCAP) {
                    const uint32_t pks = bmul2(pk0, iv);
#pragma unroll
                    for (int s = 0; s < 2; s++) {
                        const uint32_t pk1 = 0, pk0 = pks;
                        P_FRAGS(s)
#pragma unroll
                        for (int j = 0; j < 4; j++) {
#pragma unroll
                            for (int u = 0; u < 3; u++) {
                                const int i = 3 * (j & 1) + u, m = i >> 1, r = i & 1, hf = j >> 1;
                                if (s == 1 && m == 2) continue;
                                const int ql = s == 0 ? 4 * m + 2 * hf : m == 0 ? 3 + 4 * hf : 45 + hf, qc = s == 0 ? 4 * m + 1 : m == 0 ? 11 : 47;
                                uint32_t w[4];
                                unpack8(kq[ql][2 * r], kq[ql][2 * r + 1], kq[qc][2 * hf + r], w);
                                mma16816(acc[u], w[0], w[1], w[2], w[3], pb[j][0], pb[j][1]);
                            }
                        }
                    }
#pragma unroll 1
                    for (uint32_t n = 0; n < nx; n++) {
                        const uint32_t id = lds32(xl + 16 + 4 * n);
                        const int i = ((id >> 4) & 6) + ((id >> 3) & 1), key = ((id >> 6) & 6) + (i >= 3);
                        const uint32_t pw = __shfl_sync(0xffffffffu, pk0, 8 * (key & 3) + (key & 4) + ((id >> 12) & 3));
                        const float cr = bf_hi(id) * ((id & 16) ? bf_hi(pw) : bf_lo(pw));
                        const int d = (int)(64 * ((id >> 9) & 7) + 4 * (id & 4) + 4 * (i >= 3 ? i - 3 : i) + (id & 3) + ((~id >> 5) & 1024)) - 16 * lane;
#pragma unroll
                        for (int k = 0; k < 12; k++) if (d == k) acc[k >> 2][k & 3] += cr;
                    }
                } else {
                    const uint4* vg = reinterpret_cast<const uint4*>(static_cast<const char*>(maps.vp) + (size_t)row0 * 128) + 48 * t + g;
#pragma unroll 1
                    for (int s = 0; s < 2; s++) {
                        P_FRAGS(s)
#pragma unroll
                        for (int j = 0; j < 4; j++) {
#pragma unroll
                            for (int u = 0; u < 3; u++) {
                                if (s == 1 && (j & 1) && u) continue;
                                const uint4 w = ldg128(vg + 384 * s + 192 * (j >> 1) + 24 * (j & 1) + 8 * u);
                                mma16816v(acc[u], w.x, w.y, w.z, w.w, pb[j][0], pb[j][1]);
                            }
                        }
                    }
                }
#pragma unroll
                for (int s = 2; s > 0; s--) {
                    P_FRAGS(s)
#pragma unroll
                    for (int j = 0; j < 4; j++) {
#pragma unroll
                        for (int u = 0; u < 3; u++) {
                            if (s == 1 && !((j & 1) && u)) continue;
                            const int k = s == 2 ? 12 + 2 * (3 * (j & 1) + u) + (j >> 1) : 35 + (j >> 1) * 2 + u;
                            mma16816(acc[u], kq[k][0], kq[k][1], kq[k][2], kq[k][3], pb[j][0], pb[j][1]);
                        }
                    }
                }
                    }
                    P_FRAGS(i)
                    mbar_wait(tb, PAR2(i));
                    PROF_T(34 + i);
#pragma unroll
                    for (int k = 0; k < 6; k++) {
                        const uint32_t a = tile + V_OFF(k);
                        lds128(a, kq[24 + k][0], kq[24 + k][1], kq[24 + k][2], kq[24 + k][3]);
                        lds128(a + 3072, kq[30 + k][0], kq[30 + k][1], kq[30 + k][2], kq[30 + k][3]);
                    }
#pragma unroll
                    for (int j = 0; j < 4; j++) {
#pragma unroll
                        for (int u = 0; u < 3; u++) {
                            const int k = 24 + 6 * (j >> 1) + 3 * (j & 1) + u;
                            mma16816(acc[u], kq[k][0], kq[k][1], kq[k][2], kq[k][3], pb[j][0], pb[j][1]);
                        }
                    }
                    __syncwarp();
                    if (wu < L1R && i == 5 - (wu & 1)) tile_load_l1(tile, maps.vp, row0 + (i + 2) * 48, tb, lane);
                    else if (i == 4 || i == 5) tile_load(tile, &maps.v, row0 + (i + 2) * 48, tb, lds32(tile), maps.zero);
                    if (i == WO_AT1 && HAS_FFN && elect_one()) {
                        if (atomicAdd(reinterpret_cast<unsigned*>(misc + 2), 1u) == 7u) {
                            PROF_X(63);
                            load_wo(maps, sb + SM_Q, h, c, wbar, KEEP4 && __float_as_uint(misc[1]) >= DN0 ? 5 : 6);
                        }
                    }
                }
            }
#undef P_FRAGS
#undef P_CONSTS
#undef LANE_IDS
        }
        PROF_T(3 + layer * 16);
        PC(layer * 32 + 1);

        {
            const int lane = opq(tid) & 31;
            const uint32_t a = sb + SM_R + wu * 784 + 8 * (lane & 28) + 16 * (lane & 1);
#pragma unroll
            for (int u = 0; u < 3; u++) sts128p(a + 256 * u, acc[u][0] * sc3, acc[u][1] * sc3, acc[u][2] * sc3, acc[u][3] * sc3, lane & 2);
        }
        const uint32_t role1 = layer ? lds32(sb + SM_MISC + 4) : DN0 + NDN;
        const uint32_t pc = opq(sb + SM_R + 16 * opq(tid));
        uint4* const px0 = opq(&g_scr.hx[b * 48 + opq(tid)]);
        __syncthreads();
        PROF_T(4 + layer * 16);
        PC(layer * 32 + 2);
        float4 o = make_float4(0.f, 0.f, 0.f, 0.f);
        if (wu < 2) {
            float4 v[8];
#pragma unroll
            for (int w = 0; w < 8; w++) v[w] = lds4f(pc + w * 784);
            o.x = ((v[0].x + v[1].x) + (v[2].x + v[3].x)) + ((v[4].x + v[5].x) + (v[6].x + v[7].x));
            o.y = ((v[0].y + v[1].y) + (v[2].y + v[3].y)) + ((v[4].y + v[5].y) + (v[6].y + v[7].y));
            o.z = ((v[0].z + v[1].z) + (v[2].z + v[3].z)) + ((v[4].z + v[5].z) + (v[6].z + v[7].z));
            o.w = ((v[0].w + v[1].w) + (v[2].w + v[3].w)) + ((v[4].w + v[5].w) + (v[6].w + v[7].w));
            o.w = f_(__float_as_uint(o.w) & ~1u);
            st_pktp(px0, __float_as_uint(o.x), __float_as_uint(o.y), __float_as_uint(o.z), __float_as_uint(o.w), threadIdx.x < 48);
        }
        uint32_t ticket = 0;
        if (layer == 0 && tid == 224)
            asm volatile("atom.relaxed.gpu.global.inc.u32 %0, [%1], 0x7fffffff;" : "=r"(ticket) : "l"(g_scr.ticket + 8 + (b >> 3)) : "memory");
        if (layer == 0 && tid == 224 && lds32(sb + SM_MISC + 12) < 256u) {
            int it = 0;
            while ((int)(now_ns() - lds32(sb + SM_XL + 4)) < 0 && ++it < SPIN_CAP) {}
            PROF_X(47);
            load_wo(maps, sb + SM_B, h, c, wbar, 6);
        }
        uint32_t pr;
        uint4* pacc;
        {
            const int tid = opq(threadIdx.x), warp = tid >> 5, lane = tid & 31, g = lane >> 2, t = lane & 3, mat = lane >> 3, r8 = lane & 7;
            const int kg = warp >> 1, mg = warp & 1;
            const bool wo2 = role1 < DN0 + NDN;
            const uint32_t aw2 = 40960 + (wo2 && KEEP4 && role1 >= DN0 && kg >= 2 ? SM_B - SM_Q : 0);
            uint32_t aw[5];
#pragma unroll
            for (int i = 0; i < 5; i++) {
                const uint32_t lin = ((mat >> 1) * 8 + r8) * 320 + 64 * i + 32 * mg + 16 * (mat & 1);
                aw[i] = sb + (wo2 ? SM_Q : SM_B) + 5120 * kg + (lin ^ ((lin >> 3) & 48));
            }
#define CXE 0
            const uint32_t ao = pin(sb + SM_OS + 96 * kg + 16 * t), dw = pin(sb + SM_R + 16 * (16 * mg + g) + 4 * kg);
            pr = pin(sb + SM_R + 48 * tid); pacc = pin(&g_scr.acc[layer][acc_pos(54 * c + tid)]);
            const int w = 2 * min(tid, 47);
            const uint32_t d0 = pin(sb + SM_OS + 4 * (24 * ((w >> 3) & 3) + ((w >> 2) & 1) + (w < 64 ? 4 * (w & 3) + 2 * (w >> 5) : 16 + 2 * (w & 3))));
            const uint32_t d1 = pin(d0 + (w < 64 ? 16 : 8));
            const uint4* pp[3];
#pragma unroll
            for (int k = 0; k < 3; k++) pp[k] = pin(&g_scr.hx[(h * 4 + ((c + 1 + k) & 3)) * 48 + min(tid, 47)]);
            uint4 v3[3];
#pragma unroll
            for (int k = 0; k < 3; k++) v3[k] = make_uint4(0u, 0u, 0u, 1u);
            if ((PRE1 & 8) && layer) {
#pragma unroll
                for (int ks = 0; ks < 3; ks++) {
                    mbar_wait(wbar + 8 * ks, wo2);
#pragma unroll
                    for (int i = 0; i < 5; i++) ldsm4t(aw[i] + (ks == 2 ? aw2 : 20480 * ks), kq[3 * i + ks]);
                    if (ks == CXE && wu < 2) {
#pragma unroll
                        for (int k = 0; k < 3; k++) v3[k] = ld_pkt(pp[k]);
                    }
                }
                PROF_T(50);
            }
            if (wu < 2) {
                for (int it = 0; any_odd(v3[0].w, v3[1].w, v3[2].w) && it < SPIN_CAP; it++) {
#pragma unroll
                    for (int k = 0; k < 3; k++) v3[k] = ld_pkt(pp[k]);
                }
                o.x = (o.x + f_(v3[0].x)) + (f_(v3[1].x) + f_(v3[2].x)); o.y = (o.y + f_(v3[0].y)) + (f_(v3[1].y) + f_(v3[2].y));
                o.z = (o.z + f_(v3[0].z)) + (f_(v3[1].z) + f_(v3[2].z)); o.w = (o.w + f_(v3[0].w)) + (f_(v3[1].w) + f_(v3[2].w));
                sts32p(d0, f_(pack2(o.x, o.y)), tid >= 48);
                sts32p(d1, f_(pack2(o.z, o.w)), tid >= 48);
            }
            PC(layer * 32 + 3);
            __syncthreads();
            PROF_T(5 + layer * 16);
            PC(layer * 32 + 5);
            if (tid == 224 && layer == 0) {
                if (ticket >= 6 + ((b >> 3) & 1)) ticket = DN0 + NDN;
                else asm volatile("atom.relaxed.gpu.global.inc.u32 %0, [%1], 0x7fffffff;" : "=r"(ticket) : "l"(g_scr.ticket) : "memory");
            }
            uint32_t ob[6];
            lds128(ao, ob[0], ob[1], ob[2], ob[3]);
            lds64(ao + 64 - 8 * t, ob[4], ob[5]);
            float cc[5][4];
#pragma unroll
            for (int i = 0; i < 5; i++) cc[i][0] = cc[i][1] = cc[i][2] = cc[i][3] = 0.f;
            if ((PRE1 & 8) && layer) {
#pragma unroll
                for (int ks = 0; ks < 3; ks++) {
#pragma unroll
                    for (int i = 0; i < 5; i++) mma16816(cc[i], kq[3 * i + ks][0], kq[3 * i + ks][1], kq[3 * i + ks][2], kq[3 * i + ks][3], ob[2 * ks], ob[2 * ks + 1]);
                }
            } else {
#pragma unroll
                for (int ks = 0; ks < 3; ks++) {
                    mbar_wait(wbar + 8 * ks, wo2);
                    if (ks == 2) { PC(layer * 32 + 4); PROF_T(48 + layer * 2); }
                    uint32_t a[5][4];
#pragma unroll
                    for (int i = 0; i < 5; i++) ldsm4t(aw[i] + (ks == 2 ? aw2 : 20480 * ks), a[i]);
#pragma unroll
                    for (int i = 0; i < 5; i++) mma16816(cc[i], a[i][0], a[i][1], a[i][2], a[i][3], ob[2 * ks], ob[2 * ks + 1]);
                }
            }
            if (t == 0) {
#pragma unroll
                for (int i = 0; i < 5; i++) { sts32(dw + 512 * i, cc[i][0]); sts32(dw + 512 * i + 128, cc[i][2]); }
            }
        }
        PC(layer * 32 + 6);
        __syncthreads();
        PROF_T(6 + layer * 16);
        PC(layer * 32 + 7);
        if (tid < 54) {
            const float4 v0 = lds4f(pr), v1 = lds4f(pr + 16), v2 = lds4f(pr + 32);
            const float y0 = (v0.x + v0.y) + (v0.z + v0.w), y1 = (v1.x + v1.y) + (v1.z + v1.w), y2 = (v2.x + v2.y) + (v2.z + v2.w);
            red_pkt(pacc, y0, tid == 53 ? 0.f : y1, tid == 53 ? 0.f : y2);
        }
        if (tid == 224 && layer == 0) {
            misc[1] = __uint_as_float(ticket);
            if (ticket < DN0 + NDN && (ticket < NG || !DNTH)) load_ffn(maps, ticket, sb + SM_B, fbar);
        }
        PROF_T(7 + layer * 16);
        PC(layer * 32 + 8);
        __syncthreads();
        const int role = (int)__float_as_uint(misc[1]);
        PC(layer * 32 + 9);
        const uint32_t fbase = sb + SM_B;
        const uint32_t DONE32 = 0x42000000u;
        if (role < NG) {
            const int tid = opq(threadIdx.x), warp = tid >> 5, lane = tid & 31, g = lane >> 2, t = lane & 3, mat = lane >> 3, r8 = lane & 7;
            const uint32_t ag = fbase + (80 * warp + (mat >> 1) * 8 + r8) * 96 + (((mat & 1) ^ (r8 >> 2)) << 4);
            constexpr int GI = 32, GK = 16 * 96;
            const bool on = (g & 1) == (t >> 1), isx = on && g < 2;
            const uint32_t pm = opq(isx ? sb + SM_XS + 160 * warp + 16 * t : sb + (on ? SM_ONE : SM_ZERO)), pm2 = opq(pm + 128 - (isx ? 8 * t : 0));
            const uint32_t dg = opq(sb + SM_R + 4 * (2 * (warp * 48 + g) + t)), ds = opq(sb + SM_ST + 8 * warp + (lane < 16 ? 4 : 0));
            const bool ws = (lane & 15) == 0, lo = lane < 16;
            uint32_t pre[6][4];
            float s1 = 0.f, s2 = 0.f;
            {
                bool hx = false;
                int it = 0;
                const int cq = wu >> 1, odd = wu & 1, r = min(26 * odd + lane, 26 + 27 * odd), c0 = 3 * r - 80 * odd, k0 = 160 * cq + 3 * r;
                const uint4* px = &g_scr.acc[layer][acc_pos(54 * cq + r)];
                const bool act = lane <= 26 + odd;
                const bool on0 = act && c0 >= 0, on1 = act && c0 + 1 >= 0 && c0 + 1 < 80, on2 = act && c0 + 2 < 80;
                const uint32_t w0 = sb + SM_XS + 4 * xpos(k0 >> 1), w1 = sb + SM_XS + 4 * xpos(min((k0 >> 1) + 1, DM / 2 - 1));
                const uint32_t e0 = w0 + 2 * (k0 & 1), e1 = (k0 & 1) ? w1 : w0 + 2, e2 = w1 + 2 * (k0 & 1);
                auto sts16 = [](uint32_t a, uint32_t x, bool on) {
                    asm volatile("{\n.reg .pred p;\nsetp.ne.u32 p, %2, 0;\n@p st.shared.u16 [%0], %1;\n}" ::"r"(a), "h"((unsigned short)x), "r"((uint32_t)on) : "memory");
                };
                const float x0 = on0 ? f_(lds16(e0) << 16) : 0.f, x1 = on1 ? f_(lds16(e1) << 16) : 0.f, x2 = on2 ? f_(lds16(e2) << 16) : 0.f;
                auto take_x = [&](const uint4 v) {
                    if (__all_sync(0xffffffffu, v.w == DONE32)) {
                        hx = true;
                        const uint32_t a = pack2(f_(v.x), f_(v.y)), p = pack2(x0 + bf_lo(a), x1 + bf_hi(a)), q = pack2(x2 + bfr(f_(v.z)), 0.f);
                        sts16(e0, p, on0); sts16(e1, p >> 16, on1); sts16(e2, q, on2);
                        const float y0 = on0 ? bf_lo(p) : 0.f, y1 = on1 ? bf_hi(p) : 0.f, y2 = on2 ? bf_lo(q) : 0.f;
                        s1 = y0 + (y1 + y2); s2 = y0 * y0 + (y1 * y1 + y2 * y2);
                    }
                };
                auto try_x = [&]() { take_x(ld_pkt(px)); };
                while (!mbar_test(fbar, 0) && ++it < SPIN_CAP) { if (!hx) try_x(); }
                uint4 v0 = make_uint4(0u, 0u, 0u, 0u);
                if ((PRE1 & 4) && !hx) v0 = ld_pkt(px);
#pragma unroll
                for (int n = 0; n < 6; n++) ldsm4t(ag + (n % 3) * GI + (n / 3) * GK, pre[n]);
                if ((PRE1 & 1) && layer) {
#pragma unroll
                    for (int n = 6; n < 15; n++) ldsm4t(ag + (n % 3) * GI + (n / 3) * GK, kq[n - 6]);
                }
                if ((PRE1 & 4) && !hx) take_x(v0);
                PC(layer * 32 + 10);
                for (; !hx && it < SPIN_CAP; it++) try_x();
                PC(layer * 32 + 11);
            __syncwarp();
            PC(layer * 32 + 12);
            PROF_T(9 + layer * 16);
            float sv = lo ? s1 : s2, cc[3][4];
            if ((PRE1 & 1) && layer) gemv15r(cc, pre, kq, pm, pm2, sv, lo ? s2 : s1);
            else gemv15<GK>(cc, pre, [&](int i) { return ag + i * GI; }, pm, pm2, sv, lo ? s2 : s1);
#pragma unroll
            for (int i = 0; i < 3; i++) { sts32p(dg + 128 * i, cc[i][0] + cc[i][3], t & 2); sts32p(dg + 128 * i + 64, cc[i][1] + cc[i][2], t & 2); }
            if (ws) sts32(ds, sv);
            const uint32_t pg = opq(sb + SM_R + 8 * (24 * warp + (lane < 24 ? lane : 0))), st = opq(sb + SM_ST);
            uint4* const ph = opq(lane < 24 && lane % 6 == 0 ? &g_scr.ah[role * 8 + 4 * warp + lane / 6] : nullptr);
            PC(layer * 32 + 13);
            __syncthreads();
            PC(layer * 32 + 14);
            PROF_T(43 + layer * 16);
            if (wu < 2) {
                float mean, inv;
                ln_stats(st, mean, inv);
                float2 v[8];
#pragma unroll
                for (int w = 0; w < 8; w++) v[w] = lds2f(pg + w * 384);
                const float gx = ((v[0].x + v[1].x) + (v[2].x + v[3].x)) + ((v[4].x + v[5].x) + (v[6].x + v[7].x));
                const float gs = ((v[0].y + v[1].y) + (v[2].y + v[3].y)) + ((v[4].y + v[5].y) + (v[6].y + v[7].y));
                float ga = inv * (gx - mean * gs);
                if (role < NG / 2) { ga = bfr(ga); ga *= rcp(1.0f + ex2(-1.4426950408889634f * ga)); }
                const uint32_t wd = pack2(ga, __shfl_down_sync(0xffffffffu, ga, 1));
                const uint32_t wa = __shfl_down_sync(0xffffffffu, wd, 2), wb = __shfl_down_sync(0xffffffffu, wd, 4);
                if (ph) st_pkt(ph, wd, wa, wb, tag);
            }
            if (HOLD & 2) __syncthreads();
            }
            PROF_T(10 + layer * 16);
            PC(layer * 32 + 15);
        } else if (role < DN0 + NDN) {
            const int j = role - DN0;
            const int tid = opq(threadIdx.x), warp = tid >> 5, lane = tid & 31, g = lane >> 2, t = lane & 3, mat = lane >> 3, r8 = lane & 7;
            float xres = 0.f;
            uint32_t xr0 = 0, xr1 = 0;
            if (wu == 0) {
                const int col = 16 * j + (lane & 15), cc = col / 160, r = col - 160 * cc, e = r % 3;
                const uint4* px = &g_scr.acc[layer][acc_pos(54 * cc + r / 3)];
                const float x0 = __bfloat162float(reinterpret_cast<const __nv_bfloat16*>(xs32)[2 * xpos(col >> 1) + (col & 1)]);
                uint4 v;
                int it = 0;
                bool ld = DNTH && layer == 0;
                do {
                    v = ld_pkt(px);
                    if (ld && f_(__shfl_sync(0xffffffffu, v.w, 0)) >= (float)DNTH) { ld = false; if (lane == 0) load_ffn(maps, role, sb + SM_B, fbar); }
                } while (!__all_sync(0xffffffffu, v.w == DONE32) && ++it < SPIN_CAP);
                if (ld && lane == 0) load_ffn(maps, role, sb + SM_B, fbar);
                xres = x0 + bfr(f_(e == 0 ? v.x : (e == 1 ? v.y : v.z)));
                const int p4 = 4 * (lane & 3);
                xr0 = pack2(__shfl_sync(0xffffffffu, xres, p4), __shfl_sync(0xffffffffu, xres, p4 + 1));
                xr1 = pack2(__shfl_sync(0xffffffffu, xres, p4 + 2), __shfl_sync(0xffffffffu, xres, p4 + 3));
            }
            PC(layer * 32 + 17);
            PROF_T(9 + layer * 16);
            const uint32_t ad = fbase + (192 * warp + (mat >> 1) * 8 + r8) * 32 + (((mat & 1) ^ (r8 >> 2)) << 4);
            uint32_t* hs = reinterpret_cast<uint32_t*>(rr) + warp * 96;
            uint32_t pre[NPRE][4];
            {
                uint32_t pos[3];
#pragma unroll
                for (int i = 0; i < 3; i++) { const int w = 3 * lane + i; pos[i] = pin(sb + SM_R + 384 * warp + 4 * ((w & ~15) + 4 * (w & 3) + ((w >> 2) & 1) + ((w >> 2) & 2))); }
                uint4 v = make_uint4(0u, 0u, 0u, 0u), u = v;
                if (layer == 0) { v = ld_pkt(&g_scr.ah[tid]); u = ld_pkt(&g_scr.ah[256 + tid]); }
                mbar_wait(fbar, 0);
#pragma unroll
                for (int n = 0; n < NPRE; n++) ldsm4t(ad + n * 512, pre[n]);
                if ((PRE1 & 2) && layer) {
#pragma unroll
                    for (int n = NPRE; n < 12; n++) ldsm4t(ad + n * 512, kq[12 + n]);
                }
                PC(layer * 32 + 18);
                int it = 0;
                for (; any_ne(v.w, u.w, tag) && it < SPIN_CAP; it++) { v = ld_pkt(&g_scr.ah[tid]); u = ld_pkt(&g_scr.ah[256 + tid]); }
                PC(layer * 32 + 19);
                sts32(pos[0], f_(bmul2(v.x, u.x))); sts32(pos[1], f_(bmul2(v.y, u.y))); sts32(pos[2], f_(bmul2(v.z, u.z)));
            __syncwarp();
            PROF_T(11 + layer * 16);
            PC(layer * 32 + 20);
            float ca[4] = {0.f, 0.f, 0.f, 0.f}, cb[4] = {0.f, 0.f, 0.f, 0.f};
            if ((PRE1 & 2) && layer) {
                float cc[4] = {0.f, 0.f, 0.f, 0.f}, cd[4] = {0.f, 0.f, 0.f, 0.f};
#pragma unroll
                for (int jj = 0; jj < 6; jj++) {
                    const uint4 hv = *reinterpret_cast<const uint4*>(hs + 16 * jj + 4 * t);
                    const uint32_t (&f0)[4] = 2 * jj < NPRE ? pre[2 * jj < NPRE ? 2 * jj : 0] : kq[12 + 2 * jj];
                    const uint32_t (&f1)[4] = 2 * jj + 1 < NPRE ? pre[2 * jj + 1 < NPRE ? 2 * jj + 1 : 0] : kq[13 + 2 * jj];
                    if (jj & 1) { mma16816(cc, f0[0], f0[1], f0[2], f0[3], hv.x, hv.y); mma16816(cd, f1[0], f1[1], f1[2], f1[3], hv.z, hv.w); }
                    else { mma16816(ca, f0[0], f0[1], f0[2], f0[3], hv.x, hv.y); mma16816(cb, f1[0], f1[1], f1[2], f1[3], hv.z, hv.w); }
                }
#pragma unroll
                for (int e = 0; e < 4; e++) { ca[e] += cc[e]; cb[e] += cd[e]; }
            } else {
#pragma unroll
                for (int jj = 0; jj < 6; jj++) {
                    const uint4 hv = *reinterpret_cast<const uint4*>(hs + 16 * jj + 4 * t);
                    uint32_t a[4];
                    if (2 * jj < NPRE) { a[0] = pre[2 * jj][0]; a[1] = pre[2 * jj][1]; a[2] = pre[2 * jj][2]; a[3] = pre[2 * jj][3]; }
                    else ldsm4t(ad + 2 * jj * 512, a);
                    mma16816(ca, a[0], a[1], a[2], a[3], hv.x, hv.y);
                    if (2 * jj + 1 < NPRE) { a[0] = pre[2 * jj + 1][0]; a[1] = pre[2 * jj + 1][1]; a[2] = pre[2 * jj + 1][2]; a[3] = pre[2 * jj + 1][3]; }
                    else ldsm4t(ad + (2 * jj + 1) * 512, a);
                    mma16816(cb, a[0], a[1], a[2], a[3], hv.z, hv.w);
                }
            }
            if (t == 0) { rr[768 + warp * 16 + g] = ca[0] + cb[0]; rr[768 + warp * 16 + 8 + g] = ca[2] + cb[2]; }
            const uint32_t pd = opq(sb + SM_R + 3072 + 16 * (lane & 3));
            uint4* const py = opq(&g_scr.ay[j * 4 + lane]);
            uint2* const po = opq(reinterpret_cast<uint2*>(out + 16 * j) + lane);
            PC(layer * 32 + 21);
            __syncthreads();
            PC(layer * 32 + 22);
            if (wu == 0) {
                float4 p[8];
#pragma unroll
                for (int w = 0; w < 8; w++) p[w] = lds4f(pd + 64 * w);
                const uint32_t y0 = pack2(((p[0].x + p[1].x) + (p[2].x + p[3].x)) + ((p[4].x + p[5].x) + (p[6].x + p[7].x)),
                                          ((p[0].y + p[1].y) + (p[2].y + p[3].y)) + ((p[4].y + p[5].y) + (p[6].y + p[7].y)));
                const uint32_t y1 = pack2(((p[0].z + p[1].z) + (p[2].z + p[3].z)) + ((p[4].z + p[5].z) + (p[6].z + p[7].z)),
                                          ((p[0].w + p[1].w) + (p[2].w + p[3].w)) + ((p[4].w + p[5].w) + (p[6].w + p[7].w)));
                uint32_t wd, wn;
                asm("add.rn.bf16x2 %0, %1, %2;" : "=r"(wd) : "r"(xr0), "r"(y0));
                asm("add.rn.bf16x2 %0, %1, %2;" : "=r"(wn) : "r"(xr1), "r"(y1));
                asm volatile("{\n.reg .pred p;\nsetp.ne.u32 p, %3, 0;\n@p st.global.v2.u32 [%0], {%1,%2};\n}" ::"l"(po), "r"(wd), "r"(wn), "r"((uint32_t)(layer && tid < 4)) : "memory");
                st_pktp(py, wd, wn, 0, tag, tid < 4);
            }
            if (HOLD & 1) __syncthreads();
            }
            PROF_T(12 + layer * 16);
            PC(layer * 32 + 23);
        }
    }
}

typedef CUresult (*EncodeFn)(CUtensorMap*, CUtensorMapDataType, cuuint32_t, void*, const cuuint64_t*, const cuuint64_t*, const cuuint32_t*,
                             const cuuint32_t*, CUtensorMapInterleave, CUtensorMapSwizzle, CUtensorMapL2promotion, CUtensorMapFloatOOBfill);

void make_map(EncodeFn enc, CUtensorMap* m, const void* base, int rank, uint64_t d0, uint64_t d1, uint64_t d2, uint64_t s1, uint64_t s2,
              uint32_t b0, uint32_t b1, uint32_t b2, CUtensorMapSwizzle sw, CUtensorMapL2promotion pr = CU_TENSOR_MAP_L2_PROMOTION_NONE) {
    cuuint64_t dims[3] = {d0, d1, d2};
    cuuint64_t strides[2] = {s1, s2};
    cuuint32_t box[3] = {b0, b1, b2};
    cuuint32_t es[3] = {1, 1, 1};
    enc(m, CU_TENSOR_MAP_DATA_TYPE_BFLOAT16, rank, const_cast<void*>(base), dims, strides, box, es, CU_TENSOR_MAP_INTERLEAVE_NONE, sw,
        pr, CU_TENSOR_MAP_FLOAT_OOB_FILL_NONE);
}

}

extern "C" void kernel_launch(void* const* d_in, const int* in_sizes, int n_in, void* d_out, int out_size) {
    (void)in_sizes; (void)n_in; (void)out_size;
    static EncodeFn enc = nullptr;
    if (!enc) {
        void* fn = nullptr;
        cudaDriverEntryPointQueryResult qr;
        cudaGetDriverEntryPoint("cuTensorMapEncodeTiled", &fn, cudaEnableDefault, &qr);
        enc = reinterpret_cast<EncodeFn>(fn);
        cudaFuncSetAttribute(decode_kernel, cudaFuncAttributeMaxDynamicSharedMemorySize, SM_TOTAL);
    }
    Maps maps;
    make_map(enc, &maps.k, d_in[1], 2, 64, (uint64_t)NH * SK * 3, 1, 128, 0, 64, 48, 1, CU_TENSOR_MAP_SWIZZLE_128B);
    make_map(enc, &maps.v, d_in[2], 2, 64, (uint64_t)NH * SK * 3, 1, 128, 0, 64, 48, 1, CU_TENSOR_MAP_SWIZZLE_128B);
    make_map(enc, &maps.wq, d_in[3], 3, 64, DM, NH * DH / 64, NH * DH * 2, 128, 64, 160, 3, CU_TENSOR_MAP_SWIZZLE_128B);
    make_map(enc, &maps.wo, d_in[4], 3, 32, DM / 32, NH * DH, 64, DM * 2, 32, 5, 32, CU_TENSOR_MAP_SWIZZLE_64B);
    make_map(enc, &maps.vr, (const char*)d_in[2] + 512, 2, 128, (uint64_t)NH * SK / 2, 1, 768, 0, 128, 2, 1, CU_TENSOR_MAP_SWIZZLE_NONE);
    constexpr int GW = 48;
    make_map(enc, &maps.w1, d_in[6], 3, FF, 160, 4, FF * 2, 160 * FF * 2, GW, 160, 4, CU_TENSOR_MAP_SWIZZLE_NONE, FFN_PROMO);
    make_map(enc, &maps.w3, d_in[7], 3, FF, 160, 4, FF * 2, 160 * FF * 2, GW, 160, 4, CU_TENSOR_MAP_SWIZZLE_NONE, FFN_PROMO);
    make_map(enc, &maps.w2, d_in[8], 3, DM, 256, 6, DM * 2, 256 * DM * 2, 16, 256, 6, CU_TENSOR_MAP_SWIZZLE_32B, FFN_PROMO);
    maps.vp = d_in[2];
    maps.kp = d_in[1];
    maps.zero = 0;
    decode_kernel<<<NCTA, NT, SM_TOTAL, cudaStreamPerThread>>>(maps, (const __nv_bfloat16*)d_in[0], (__nv_bfloat16*)d_out);
}
```

```cpp
#include <cuda_runtime.h>
#include <cuda_bf16.h>
#include <cuda.h>
#include <stdint.h>
#include <math.h>

namespace {

constexpr int DM = 640;
constexpr int NH = 32;
constexpr int DH = 192;
constexpr int SK = 32768;
constexpr int WIN = 4096;
constexpr int FF = 1536;
constexpr int NCTA = 128;
constexpr int NT = 256;
constexpr int TILE = 6144;
constexpr int NG = 64;
constexpr int DN0 = 64;
constexpr int NDN = 40;

constexpr int SM_RING = 0;
constexpr int SM_B = 8 * 2 * TILE;
constexpr int SM_Q = SM_B + 61440;
__host__ __device__ constexpr int c_slot(int w) { return w < 2 ? 4096 + 10240 * w : 12288 + 6144 * w; }
__host__ __device__ constexpr int v1_pos(int n) { return 10240 * (n >> 3) + 512 * (n & 7); }
constexpr int SM_XS = SM_Q + 61440;
constexpr int SM_R = SM_XS + 1280;
constexpr int SM_ST = SM_R + 4096;
constexpr int SM_QS = SM_R + 6272;
constexpr int SM_OS = SM_QS + 384;
constexpr int SM_BAR = SM_OS + 384;
constexpr int SM_XBAR = SM_BAR + 24 * 8;
constexpr int SM_MISC = SM_XBAR + 8 * 8;
constexpr int SM_ONE = SM_MISC + 16;
constexpr int SM_ZERO = SM_ONE + 160;
constexpr int XCAP = 48;
constexpr int XSTR = 16 + 4 * XCAP;
constexpr int SM_XL = SM_ZERO + 160;
constexpr int SM_TOTAL = SM_XL + 8 * XSTR;
static_assert(SM_TOTAL <= 232448, "shared memory");

constexpr unsigned long long POL_EF = 0x12F0000000000000ull;
constexpr unsigned long long POL_EN = 0x16F0000000000000ull;

#define RT_MASK 0xF2E0u
#define RT_MASK2 0xEAE0u
#define WO_AT1 5
#define FFN_POL POL_EF
#define HAS_FFN (__float_as_uint(misc[1]) < DN0 + NDN)
#define NPRE 6

#define STAG 200
#define L1R 3
#define PRE1 13
#define HOLD 2
#define DNTH 27
constexpr int V0_AT = 8;
constexpr unsigned long long SEQ1 = 0x2765431076543210ull;
constexpr uint32_t IN_S1 = 0xAA49, IN_S0 = 0x124, PARITY1 = 0x6638, PARITY2 = 0xCE;
#define KEEP4 1
constexpr int NQ = 48;
constexpr int SPIN_CAP = 1 << 19;
constexpr uint32_t ONES = 0x3F803F80u;

__host__ __device__ constexpr int acc_pos(int p) { return (p >> 2) * 8 + (p & 3); }
struct alignas(4096) Scratch {
    uint4 hx[NCTA * 48];
    uint4 acc[2][512];
    uint4 ay[256];
    uint4 ah[NG * 8];
    uint2 mx[NH * 32];
    uint32_t ticket[32];
    uint32_t pad1[32];
};
__device__ Scratch g_scr;
#define PROF_T(i)
#define PROF_X(i)
#define PC(i)

__device__ __forceinline__ uint32_t smem_u32(const void* p) { return (uint32_t)__cvta_generic_to_shared(p); }
__device__ __forceinline__ void mbar_init(uint32_t bar, uint32_t cnt) {
    asm volatile("mbarrier.init.shared::cta.b64 [%0], %1;" ::"r"(bar), "r"(cnt) : "memory");
}
__device__ __forceinline__ void mbar_expect_tx(uint32_t bar, uint32_t bytes) {
    asm volatile("mbarrier.arrive.expect_tx.shared::cta.b64 _, [%0], %1;" ::"r"(bar), "r"(bytes) : "memory");
}
__device__ __forceinline__ bool mbar_test(uint32_t bar, uint32_t parity) {
    uint32_t done;
    asm volatile("{\n.reg .pred p;\nmbarrier.try_wait.parity.shared::cta.b64 p, [%1], %2;\nselp.u32 %0, 1, 0, p;\n}"
                 : "=r"(done) : "r"(bar), "r"(parity) : "memory");
    return done;
}
__device__ __forceinline__ void mbar_wait(uint32_t bar, uint32_t parity) {
    for (int it = 0; it < SPIN_CAP; it++) if (mbar_test(bar, parity)) break;
}
__device__ __forceinline__ void tma2d(uint32_t dst, const CUtensorMap* map, int c0, int c1, uint32_t bar, unsigned long long pol) {
    asm volatile("cp.async.bulk.tensor.2d.shared::cluster.global.mbarrier::complete_tx::bytes.L2::cache_hint [%0], [%1, {%3, %4}], [%2], %5;"
                 ::"r"(dst), "l"(map), "r"(bar), "r"(c0), "r"(c1), "l"(pol) : "memory");
}
__device__ __forceinline__ void tma3d(uint32_t dst, const CUtensorMap* map, int c0, int c1, int c2, uint32_t bar, unsigned long long pol) {
    asm volatile("cp.async.bulk.tensor.3d.shared::cluster.global.mbarrier::complete_tx::bytes.L2::cache_hint [%0], [%1, {%3, %4, %5}], [%2], %6;"
                 ::"r"(dst), "l"(map), "r"(bar), "r"(c0), "r"(c1), "r"(c2), "l"(pol) : "memory");
}
__device__ __forceinline__ void tile_load(uint32_t dst, const CUtensorMap* map, int row, uint32_t bar, uint32_t dep, uint32_t zero) {
    asm volatile("{\n.reg .pred p;\n.reg .b32 n;\nmad.lo.u32 n, %5, %6, 6144;\nelect.sync _|p, 0xffffffff;\n"
                 "@p mbarrier.arrive.expect_tx.shared::cta.b64 _, [%2], n;\n"
                 "@p cp.async.bulk.tensor.2d.shared::cluster.global.mbarrier::complete_tx::bytes.L2::cache_hint [%0], [%1, {0, %3}], [%2], %4;\n}"
                 ::"r"(dst), "l"(map), "r"(bar), "r"(row), "l"(POL_EF), "r"(dep), "r"(zero) : "memory");
}
__device__ __forceinline__ void tile_keep(const CUtensorMap* map, int row) {
    asm volatile("{\n.reg .pred p;\nelect.sync _|p, 0xffffffff;\n"
                 "@p cp.async.bulk.prefetch.tensor.2d.L2.global.L2::cache_hint [%0, {0, %1}], %2;\n}"
                 ::"l"(map), "r"(row), "l"(POL_EN) : "memory");
}
__device__ __forceinline__ void tile_load_l1(uint32_t dst, const void* base, int row, uint32_t bar, int lane) {
    const char* g = static_cast<const char*>(base) + (size_t)row * 128 + lane * 16;
    const uint32_t s0 = dst + (lane >> 3) * 128 + (((lane & 7) ^ (lane >> 3)) << 4), s1 = s0 ^ 64;
#pragma unroll
    for (int k = 0; k < 12; k++)
        asm volatile("cp.async.ca.shared.global.L2::cache_hint [%0], [%1], 16, %2;" ::"r"(((k & 1) ? s1 : s0) + k * 512), "l"(g + k * 512), "l"(POL_EF) : "memory");
    asm volatile("cp.async.mbarrier.arrive.shared::cta.b64 [%0];" ::"r"(bar) : "memory");
    __syncwarp();
    if (lane == 0) asm volatile("mbarrier.arrive.shared::cta.b64 _, [%0];" ::"r"(bar) : "memory");
}
__device__ __forceinline__ bool elect_one() {
    uint32_t p;
    asm volatile("{\n.reg .pred p;\nelect.sync _|p, 0xffffffff;\nselp.u32 %0, 1, 0, p;\n}" : "=r"(p));
    return p;
}
__device__ __forceinline__ void lds128(uint32_t addr, uint32_t& a, uint32_t& b, uint32_t& c, uint32_t& d) {
    asm volatile("ld.shared.v4.u32 {%0,%1,%2,%3}, [%4];" : "=r"(a), "=r"(b), "=r"(c), "=r"(d) : "r"(addr) : "memory");
}
__device__ __forceinline__ void lds128p(uint32_t addr, uint32_t on, uint32_t& a, uint32_t& b, uint32_t& c, uint32_t& d) {
    asm volatile("{\n.reg .pred p;\nsetp.ne.u32 p, %5, 0;\n@p ld.shared.v4.u32 {%0,%1,%2,%3}, [%4];\n}" : "+r"(a), "+r"(b), "+r"(c), "+r"(d) : "r"(addr), "r"(on) : "memory");
}
__device__ __forceinline__ void lds64(uint32_t addr, uint32_t& a, uint32_t& b) {
    asm volatile("ld.shared.v2.u32 {%0,%1}, [%2];" : "=r"(a), "=r"(b) : "r"(addr) : "memory");
}
__device__ __forceinline__ void ldsm4t(uint32_t addr, uint32_t (&a)[4]) {
    asm volatile("ldmatrix.sync.aligned.m8n8.x4.trans.shared.b16 {%0,%1,%2,%3}, [%4];" : "=r"(a[0]), "=r"(a[1]), "=r"(a[2]), "=r"(a[3]) : "r"(addr) : "memory");
}
__device__ __forceinline__ void mma16816(float (&c)[4], uint32_t a0, uint32_t a1, uint32_t a2, uint32_t a3, uint32_t b0, uint32_t b1) {
    asm("mma.sync.aligned.m16n8k16.row.col.f32.bf16.bf16.f32 {%0,%1,%2,%3}, {%4,%5,%6,%7}, {%8,%9}, {%0,%1,%2,%3};"
        : "+f"(c[0]), "+f"(c[1]), "+f"(c[2]), "+f"(c[3]) : "r"(a0), "r"(a1), "r"(a2), "r"(a3), "r"(b0), "r"(b1));
}
__device__ __forceinline__ void mma16816v(float (&c)[4], uint32_t a0, uint32_t a1, uint32_t a2, uint32_t a3, uint32_t b0, uint32_t b1) {
    asm volatile("mma.sync.aligned.m16n8k16.row.col.f32.bf16.bf16.f32 {%0,%1,%2,%3}, {%4,%5,%6,%7}, {%8,%9}, {%0,%1,%2,%3};"
        : "+f"(c[0]), "+f"(c[1]), "+f"(c[2]), "+f"(c[3]) : "r"(a0), "r"(a1), "r"(a2), "r"(a3), "r"(b0), "r"(b1));
}
__device__ __forceinline__ int xpos(int w) {
    const int seg = w / 40, r = w - 40 * seg;
    return 40 * seg + (r < 32 ? (r & 16) + 4 * (r & 3) + ((r >> 2) & 3) : 32 + 2 * (r & 3) + ((r >> 2) & 1));
}
#define NA_LD ""
#define NA_ST ""
__device__ __forceinline__ void st_pkt(uint4* p, uint32_t a, uint32_t b, uint32_t c, uint32_t d) {
    asm volatile("{\n.reg .b128 t;\n.reg .b64 lo, hi;\nmov.b64 lo, {%1,%2};\nmov.b64 hi, {%3,%4};\nmov.b128 t, {lo,hi};\nst.relaxed.gpu.global" NA_ST ".b128 [%0], t;\n}"
                 ::"l"(p), "r"(a), "r"(b), "r"(c), "r"(d) : "memory");
}
__device__ __forceinline__ void red_pkt(uint4* p, float a, float b, float c) {
    asm volatile("red.relaxed.gpu.global.add.v4.f32 [%0], {%1,%2,%3,%4};" ::"l"(p), "f"(a), "f"(b), "f"(c), "f"(1.0f) : "memory");
}
__device__ __forceinline__ void st_pktp(uint4* p, uint32_t a, uint32_t b, uint32_t c, uint32_t d, bool on) {
    asm volatile("{\n.reg .pred p;\n.reg .b128 t;\n.reg .b64 lo, hi;\nsetp.ne.u32 p, %5, 0;\nmov.b64 lo, {%1,%2};\nmov.b64 hi, {%3,%4};\nmov.b128 t, {lo,hi};\n"
                 "@p st.relaxed.gpu.global.b128 [%0], t;\n}" ::"l"(p), "r"(a), "r"(b), "r"(c), "r"(d), "r"((uint32_t)on) : "memory");
}
__device__ __forceinline__ void st_pktfp(uint4* p, float a, float b, float c, float d, uint32_t bit, bool on) {
    st_pktp(p, __float_as_uint(a), __float_as_uint(b), __float_as_uint(c), (__float_as_uint(d) & ~1u) | bit, on);
}
__device__ __forceinline__ uint4 ld_pkt(const uint4* p) {
    uint4 v;
    asm volatile("{\n.reg .b128 t;\n.reg .b64 lo, hi;\nld.relaxed.gpu.global" NA_LD ".b128 t, [%4];\nmov.b128 {lo,hi}, t;\nmov.b64 {%0,%1}, lo;\nmov.b64 {%2,%3}, hi;\n}"
                 : "=r"(v.x), "=r"(v.y), "=r"(v.z), "=r"(v.w) : "l"(p) : "memory");
    return v;
}
__device__ __forceinline__ bool all_odd(uint32_t a, uint32_t b, uint32_t c, uint32_t d) {
    uint32_t r;
    asm volatile("{\n.reg .pred p, q, t;\n.reg .b32 x;\nsetp.eq.b32 t, 0, 0;\nlop3.b32 x, %1, %2, %3, 0x80;\nlop3.and.b32 _|p, x, %4, 1, 0x80, t;\n"
                 "vote.sync.all.pred q, p, 0xffffffff;\nselp.u32 %0, 1, 0, q;\n}" : "=r"(r) : "r"(a), "r"(b), "r"(c), "r"(d));
    return r;
}
__device__ __forceinline__ bool any_odd(uint32_t a, uint32_t b, uint32_t c) {
    uint32_t r;
    asm volatile("{\n.reg .pred p, q, t;\n.reg .b32 x;\nsetp.eq.b32 t, 0, 0;\nlop3.b32 x, %1, %2, %3, 0xFE;\nlop3.and.b32 _|p, x, 1, 0, 0xC0, t;\n"
                 "vote.sync.any.pred q, p, 0xffffffff;\nselp.u32 %0, 1, 0, q;\n}" : "=r"(r) : "r"(a), "r"(b), "r"(c));
    return r;
}
__device__ __forceinline__ bool any_ne(uint32_t a, uint32_t b, uint32_t c) {
    uint32_t r;
    asm volatile("{\n.reg .pred p, q, t;\nsetp.eq.b32 t, 0, 0;\nlop3.and.b32 _|p, %1, %2, %3, 0x7E, t;\n"
                 "vote.sync.any.pred q, p, 0xffffffff;\nselp.u32 %0, 1, 0, q;\n}" : "=r"(r) : "r"(a), "r"(b), "r"(c));
    return r;
}
__device__ __forceinline__ uint2 ld_pkt2(const uint2* p) {
    unsigned long long v;
    asm volatile("ld.relaxed.gpu.global" NA_LD ".b64 %0, [%1];" : "=l"(v) : "l"(p) : "memory");
    return make_uint2((uint32_t)v, (uint32_t)(v >> 32));
}
__device__ __forceinline__ void st_pkt2(uint2* p, uint32_t a, uint32_t b) {
    asm volatile("st.relaxed.gpu.global" NA_ST ".b64 [%0], %1;" ::"l"(p), "l"((unsigned long long)a | ((unsigned long long)b << 32)) : "memory");
}
__device__ __forceinline__ float ex2(float x) { float y; asm("ex2.approx.ftz.f32 %0, %1;" : "=f"(y) : "f"(x)); return y; }
__device__ __forceinline__ float rcp(float x) { float y; asm("rcp.approx.ftz.f32 %0, %1;" : "=f"(y) : "f"(x)); return y; }
__device__ __forceinline__ uint32_t pack2(float lo, float hi) {
    uint32_t r; asm("cvt.rn.bf16x2.f32 %0, %1, %2;" : "=r"(r) : "f"(hi), "f"(lo)); return r;
}
__device__ __forceinline__ float bf_lo(uint32_t w) { return __uint_as_float(w << 16); }
__device__ __forceinline__ float bf_hi(uint32_t w) { return __uint_as_float(w & 0xffff0000u); }
__device__ __forceinline__ float bfr(float x) { return bf_lo(pack2(x, 0.f)); }
__device__ __forceinline__ float f_(uint32_t u) { return __uint_as_float(u); }

template <int SK, typename AddrF>
__device__ __forceinline__ void gemv15(float (&cc)[3][4], uint32_t (&pre)[6][4], AddrF ad, uint32_t px, uint32_t px2, float& sv, float so) {
    uint32_t x0[4], x1[4], a[3][4];
    asm volatile("ld.shared.v4.u32 {%0,%1,%2,%3}, [%20];\nld.shared.v4.u32 {%4,%5,%6,%7}, [%20+64];\n"
                 "ldmatrix.sync.aligned.m8n8.x4.trans.shared.b16 {%8,%9,%10,%11}, [%21];\n"
                 "ldmatrix.sync.aligned.m8n8.x4.trans.shared.b16 {%12,%13,%14,%15}, [%22];\n"
                 "ldmatrix.sync.aligned.m8n8.x4.trans.shared.b16 {%16,%17,%18,%19}, [%23];\nbar.warp.sync 0xffffffff;"
                 : "=r"(x0[0]), "=r"(x0[1]), "=r"(x0[2]), "=r"(x0[3]), "=r"(x1[0]), "=r"(x1[1]), "=r"(x1[2]), "=r"(x1[3]),
                   "=r"(a[0][0]), "=r"(a[0][1]), "=r"(a[0][2]), "=r"(a[0][3]), "=r"(a[1][0]), "=r"(a[1][1]), "=r"(a[1][2]), "=r"(a[1][3]),
                   "=r"(a[2][0]), "=r"(a[2][1]), "=r"(a[2][2]), "=r"(a[2][3])
                 : "r"(px), "r"(ad(0) + 2 * SK), "r"(ad(1) + 2 * SK), "r"(ad(2) + 2 * SK) : "memory");
    __syncwarp();
    sv += __shfl_xor_sync(0xffffffffu, so, 16);
#pragma unroll
    for (int i = 0; i < 3; i++) {
        cc[i][0] = cc[i][1] = cc[i][2] = cc[i][3] = 0.f;
        mma16816v(cc[i], pre[i][0], pre[i][1], pre[i][2], pre[i][3], x0[0], x0[1]);
    }
    sv += __shfl_xor_sync(0xffffffffu, sv, 8);
#pragma unroll
    for (int i = 0; i < 3; i++) {
        mma16816v(cc[i], pre[3 + i][0], pre[3 + i][1], pre[3 + i][2], pre[3 + i][3], x0[2], x0[3]);
        ldsm4t(ad(i) + 3 * SK, pre[i]);
    }
    lds64(px2, x0[0], x0[1]);
    __syncwarp();
    sv += __shfl_xor_sync(0xffffffffu, sv, 4);
#pragma unroll
    for (int i = 0; i < 3; i++) {
        mma16816v(cc[i], a[i][0], a[i][1], a[i][2], a[i][3], x1[0], x1[1]);
        ldsm4t(ad(i) + 4 * SK, pre[3 + i]);
    }
    __syncwarp();
    sv += __shfl_xor_sync(0xffffffffu, sv, 2);
#pragma unroll
    for (int i = 0; i < 3; i++) mma16816v(cc[i], pre[i][0], pre[i][1], pre[i][2], pre[i][3], x1[2], x1[3]);
    sv += __shfl_xor_sync(0xffffffffu, sv, 1);
#pragma unroll
    for (int i = 0; i < 3; i++) mma16816v(cc[i], pre[3 + i][0], pre[3 + i][1], pre[3 + i][2], pre[3 + i][3], x0[0], x0[1]);
}
__device__ __forceinline__ void gemv15r(float (&cc)[3][4], const uint32_t (&pre)[6][4], const uint32_t (&ext)[NQ][4], uint32_t px, uint32_t px2, float& sv, float so) {
    uint32_t x0[4], x1[4], x2[2];
    float cd[3][4];
    lds128(px, x0[0], x0[1], x0[2], x0[3]);
    lds128(px + 64, x1[0], x1[1], x1[2], x1[3]);
    lds64(px2, x2[0], x2[1]);
    sv += __shfl_xor_sync(0xffffffffu, so, 16);
#pragma unroll
    for (int i = 0; i < 3; i++) {
        cc[i][0] = cc[i][1] = cc[i][2] = cc[i][3] = cd[i][0] = cd[i][1] = cd[i][2] = cd[i][3] = 0.f;
        mma16816v(cc[i], pre[i][0], pre[i][1], pre[i][2], pre[i][3], x0[0], x0[1]);
        mma16816v(cd[i], pre[3 + i][0], pre[3 + i][1], pre[3 + i][2], pre[3 + i][3], x0[2], x0[3]);
    }
    sv += __shfl_xor_sync(0xffffffffu, sv, 8);
#pragma unroll
    for (int i = 0; i < 3; i++) {
        mma16816v(cc[i], ext[i][0], ext[i][1], ext[i][2], ext[i][3], x1[0], x1[1]);
        mma16816v(cd[i], ext[3 + i][0], ext[3 + i][1], ext[3 + i][2], ext[3 + i][3], x1[2], x1[3]);
    }
    sv += __shfl_xor_sync(0xffffffffu, sv, 4);
#pragma unroll
    for (int i = 0; i < 3; i++) mma16816v(cc[i], ext[6 + i][0], ext[6 + i][1], ext[6 + i][2], ext[6 + i][3], x2[0], x2[1]);
    sv += __shfl_xor_sync(0xffffffffu, sv, 2);
    sv += __shfl_xor_sync(0xffffffffu, sv, 1);
#pragma unroll
    for (int i = 0; i < 3; i++) { cc[i][0] += cd[i][0]; cc[i][1] += cd[i][1]; cc[i][2] += cd[i][2]; cc[i][3] += cd[i][3]; }
}

__device__ __forceinline__ float warp_max(float x) {
    int i = __float_as_int(x);
    i = __reduce_max_sync(0xffffffffu, i ^ ((i >> 31) & 0x7fffffff));
    return __int_as_float(i ^ ((i >> 31) & 0x7fffffff));
}
__device__ __forceinline__ void idle(uint32_t clk) {
    uint32_t t0, t;
    asm volatile("mov.u32 %0, %%clock;" : "=r"(t0) :: "memory");
    do asm volatile("mov.u32 %0, %%clock;" : "=r"(t) :: "memory"); while (t - t0 < clk);
}
__device__ __forceinline__ uint32_t now_ns() { uint32_t t; asm volatile("mov.u32 %0, %%globaltimer_lo;" : "=r"(t)); return t; }
__device__ __forceinline__ int opq(int x) { asm volatile("" : "+r"(x)); return x; }
__device__ __forceinline__ uint32_t opq(uint32_t x) { asm volatile("" : "+r"(x)); return x; }
__device__ __forceinline__ uint32_t pin(uint32_t x) { return __shfl_sync(0xffffffffu, x, threadIdx.x & 31); }
template <typename T> __device__ __forceinline__ T* pin(T* p) {
    const unsigned long long v = (unsigned long long)p;
    return (T*)((unsigned long long)pin((uint32_t)v) | (unsigned long long)pin((uint32_t)(v >> 32)) << 32);
}
template <typename T> __device__ __forceinline__ T* opq(T* p) { asm volatile("" : "+l"(p)); return p; }
__device__ __forceinline__ float4 lds4f(uint32_t a) { float4 v; asm volatile("ld.shared.v4.f32 {%0,%1,%2,%3}, [%4];" : "=f"(v.x), "=f"(v.y), "=f"(v.z), "=f"(v.w) : "r"(a) : "memory"); return v; }
__device__ __forceinline__ float2 lds2f(uint32_t a) { float2 v; asm volatile("ld.shared.v2.f32 {%0,%1}, [%2];" : "=f"(v.x), "=f"(v.y) : "r"(a) : "memory"); return v; }
__device__ __forceinline__ void ln_stats(uint32_t st, float& mean, float& inv) {
    const float4 a = lds4f(st), b = lds4f(st + 16), c = lds4f(st + 32), d = lds4f(st + 48);
    const float s2 = ((a.x + a.z) + (b.x + b.z)) + ((c.x + c.z) + (d.x + d.z));
    const float md = (((a.y + a.w) + (b.y + b.w)) + ((c.y + c.w) + (d.y + d.w))) * (1.0f / DM);
    const float var = fmaxf(s2 * (1.0f / DM) - md * md, 0.f);
    mean = bfr(md);
    asm("rsqrt.approx.ftz.f32 %0, %1;" : "=f"(inv) : "f"(var + 1e-5f));
}
__device__ __forceinline__ void sts32(uint32_t a, float v) { asm volatile("st.shared.f32 [%0], %1;" ::"r"(a), "f"(v) : "memory"); }
__device__ __forceinline__ void sts32p(uint32_t a, float v, uint32_t off) {
    asm volatile("{\n.reg .pred p;\nsetp.eq.u32 p, %2, 0;\n@p st.shared.f32 [%0], %1;\n}" ::"r"(a), "f"(v), "r"(off) : "memory");
}
__device__ __forceinline__ void sts128p(uint32_t a, float x, float y, float z, float w, uint32_t off) {
    asm volatile("{\n.reg .pred p;\nsetp.eq.u32 p, %5, 0;\n@p st.shared.v4.f32 [%0], {%1,%2,%3,%4};\n}" ::"r"(a), "f"(x), "f"(y), "f"(z), "f"(w), "r"(off) : "memory");
}
__device__ __forceinline__ void sts64(uint32_t a, float v, float w) { asm volatile("st.shared.v2.f32 [%0], {%1,%2};" ::"r"(a), "f"(v), "f"(w) : "memory"); }

__device__ __forceinline__ uint32_t prmt(uint32_t a, uint32_t b, uint32_t s) { uint32_t r; asm("prmt.b32 %0, %1, %2, %3;" : "=r"(r) : "r"(a), "r"(b), "r"(s)); return r; }
__device__ __forceinline__ uint32_t bmul2(uint32_t a, uint32_t b) { uint32_t r; asm("mul.rn.bf16x2 %0, %1, %2;" : "=r"(r) : "r"(a), "r"(b)); return r; }
__device__ __forceinline__ void sts128(uint32_t addr, uint32_t a, uint32_t b, uint32_t c, uint32_t d) {
    asm volatile("st.shared.v4.u32 [%0], {%1,%2,%3,%4};" ::"r"(addr), "r"(a), "r"(b), "r"(c), "r"(d) : "memory");
}
__device__ __forceinline__ uint4 ldg128(const uint4* p) {
    uint4 v;
    asm volatile("ld.volatile.global.v4.u32 {%0,%1,%2,%3}, [%4];" : "=r"(v.x), "=r"(v.y), "=r"(v.z), "=r"(v.w) : "l"(p) : "memory");
    return v;
}
__device__ __forceinline__ uint32_t lds32(uint32_t a) { uint32_t v; asm volatile("ld.shared.u32 %0, [%1];" : "=r"(v) : "r"(a) : "memory"); return v; }
__device__ __forceinline__ uint32_t lds16(uint32_t a) { unsigned short v; asm volatile("ld.shared.u16 %0, [%1];" : "=h"(v) : "r"(a) : "memory"); return v; }
__device__ __forceinline__ void unpack8(uint32_t la, uint32_t lb, uint32_t c, uint32_t (&w)[4]) {
    const uint32_t ha = c & 0x87878787u, hb = __funnelshift_l(c, c, 4) & 0x87878787u;
    w[0] = prmt(la, ha, 0x5140); w[1] = prmt(la, ha, 0x7362); w[2] = prmt(lb, hb, 0x5140); w[3] = prmt(lb, hb, 0x7362);
}
__device__ __forceinline__ uint32_t bdiff2(uint32_t y, uint32_t inv, uint32_t x) {
    uint32_t r;
    asm("{\n.reg .b32 n;\nneg.bf16x2 n, %3;\nfma.rn.bf16x2 %0, %1, %2, n;\n}" : "=r"(r) : "r"(y), "r"(inv), "r"(x));
    return r;
}
__device__ __forceinline__ uint32_t pack_scale(uint32_t tile, int lane, uint32_t inv_addr) {
    uint32_t m = 0;
#pragma unroll 1
    for (int k = 0; k < 12; k++) {
        uint32_t a, b, c, d;
        lds128(tile + k * 512 + lane * 16, a, b, c, d);
        asm("max.xorsign.abs.bf16x2 %0, %0, %1;" : "+r"(a) : "r"(b));
        asm("max.xorsign.abs.bf16x2 %0, %0, %1;" : "+r"(c) : "r"(d));
        asm("max.xorsign.abs.bf16x2 %0, %0, %1;" : "+r"(a) : "r"(c));
        asm("max.xorsign.abs.bf16x2 %0, %0, %1;" : "+r"(m) : "r"(a));
    }
    m = __reduce_max_sync(0xffffffffu, max(m & 0x7fffu, (m >> 16) & 0x7fffu));
    const uint32_t inv = (112u + min((m + 0x28u) >> 7, 141u)) * 0x00800080u;
    if (lane == 0) asm volatile("st.shared.u32 [%0], %1;" ::"r"(inv_addr), "r"(inv) : "memory");
    return inv;
}

#define K_OFF(i) ((uint32_t)((3 * ((g >> 1) + 4 * (g & 1)) + ((i) >> 1)) * 128 + ((t ^ ((3 * ((g >> 1) + 4 * (g & 1)) + ((i) >> 1)) & 7) ^ (((i) & 1) << 2)) << 4)))
#define V_OFF(i) ((uint32_t)((6 * t + (i)) * 128 + ((g ^ ((6 * t + (i)) & 7)) << 4)))
template <bool ISV, typename DST>
__device__ __forceinline__ void pack_tile(uint32_t tile, int tau, int nm, uint32_t inv, uint32_t xl, int lane, DST dst) {
    const int g = lane >> 2, t = lane & 3;
    const uint32_t scl = 254u * 0x00800080u - inv;
#pragma unroll 1
    for (int m = 0; m < nm; m++) {
        const int row = ISV ? 6 * t + 2 * m : 3 * ((g >> 1) + 4 * (g & 1)) + m;
        const uint32_t a0 = tile + row * 128 + (((ISV ? g : t) ^ (row & 7)) << 4), a1 = ISV ? (a0 ^ 16) + 128 : a0 ^ 64;
        uint32_t l[8], cw[4], ck = 0, cd = 0;
#pragma unroll
        for (int r = 0; r < 4; r++) {
            uint32_t w0, w1, w2, w3;
            lds128(((r & 1) ? a1 : a0) + (r >> 1) * 3072, w0, w1, w2, w3);
            const uint32_t y0 = bmul2(w0, scl), y1 = bmul2(w1, scl), y2 = bmul2(w2, scl), y3 = bmul2(w3, scl);
            cd |= bdiff2(y0, inv, w0) | bdiff2(y1, inv, w1);
            cd |= bdiff2(y2, inv, w2) | bdiff2(y3, inv, w3);
            const uint32_t ha = prmt(y0, y1, 0x7531), hb = prmt(y2, y3, 0x7531);
            l[2 * r] = prmt(y0, y1, 0x6420); l[2 * r + 1] = prmt(y2, y3, 0x6420);
            asm("lop3.b32 %0, %1, 0x87878787, %2, 0xe2;" : "=r"(cw[r]) : "r"(ha), "r"(__funnelshift_r(hb, hb, 4)));
            ck |= ha | hb;
        }
        const uint32_t bad = __ballot_sync(0xffffffffu, (ck & 0x78787878u) | cd);
        if (bad) {
            const int src = __ffs(bad) - 1;
            const uint32_t b0 = __shfl_sync(0xffffffffu, a0, src), b1 = __shfl_sync(0xffffffffu, a1, src), n0 = lds32(xl);
            const uint32_t ax = ((lane & 8) ? b1 : b0) + (lane >> 4) * 3072 + 2 * (lane & 7), x = lds16(ax), y = bmul2(x, scl);
            const bool out = (y & 0x7800u) | bdiff2(y, inv, x);
            const uint32_t n = n0 + __popc(__ballot_sync(0xffffffffu, out) << (31 - lane)) - 1;
            if (out) {
                asm volatile("st.shared.u16 [%0], %1;" ::"r"(ax), "h"((unsigned short)0) : "memory");
                if (n < XCAP) sts32(xl + 16 + 4 * n, f_(x << 16 | tau << 12 | src << 7 | m << 5 | lane));
            }
            if (lane == 31) sts32(xl, f_(n + 1));
            __syncwarp();
            if (n0 <= XCAP) { m--; continue; }
        }
        uint32_t d[3] = {a0, a1, a0 + 3072};
        dst(m, d);
        sts128(d[0], l[0], l[1], l[2], l[3]);
        sts128(d[1], l[4], l[5], l[6], l[7]);
        sts128(d[2], cw[0], cw[1], cw[2], cw[3]);
    }
}

struct Maps { CUtensorMap k, v, wq, wo, w1, w3, w2, vr; const void* vp; const void* kp; uint32_t zero; };
#define RT_SEL ((wu & 1) ? RT_MASK2 : RT_MASK)
#define PFK 5
#define Q_AT 3
#define WO_T0 33200
#define K5D 250
#define PK_AT 6

__device__ __forceinline__ void load_ffn(const Maps& maps, int b, uint32_t dst, uint32_t bar) {
    const bool gu = b < NG;
    mbar_expect_tx(bar, gu ? 61440 : 49152);
    tma3d(dst, gu ? (b < NG / 2 ? &maps.w1 : &maps.w3) : &maps.w2, gu ? 48 * (b & (NG / 2 - 1)) : 16 * (b - DN0), 0, 0, bar, FFN_POL);
}

__device__ __forceinline__ void load_wo(const Maps& maps, uint32_t dst, int h, int c, uint32_t bar, int nbox) {
#pragma unroll 1
    for (int i = 0; i < nbox; i++) {
        if (!(i & 1)) mbar_expect_tx(bar + 4 * i, i + 1 < nbox ? 20480 : 10240);
        tma3d(dst + i * 10240, &maps.wo, 0, 5 * c, h * DH + 32 * i, bar + 4 * (i & 6), POL_EF);
    }
}

__global__ void __launch_bounds__(NT, 1)
decode_kernel(const __grid_constant__ Maps maps, const __nv_bfloat16* __restrict__ x_in, __nv_bfloat16* __restrict__ out) {
    extern __shared__ __align__(1024) unsigned char smem[];
    const int tid = threadIdx.x, warp = tid >> 5, lane = tid & 31;
    const int wu = __shfl_sync(0xffffffffu, tid >> 5, 0);
    const int b = blockIdx.x, h = b >> 2, c = b & 3;
    const uint32_t sb = smem_u32(smem);
    const uint32_t qbar = sb + SM_BAR + 16 * 8, fbar = qbar + 8, wbar = qbar + 16;
    uint32_t* xs32 = reinterpret_cast<uint32_t*>(smem + SM_XS);
    float* rr = reinterpret_cast<float*>(smem + SM_R);
    float* misc = reinterpret_cast<float*>(smem + SM_MISC);

    PROF_T(0);
    {
        uint2 xv = make_uint2(0u, 0u);
        const uint32_t t_start = now_ns();
        if (elect_one()) {
            const uint32_t rb = sb + SM_BAR + wu * 16, xb = sb + SM_XBAR + wu * 8;
            mbar_init(rb, 1); mbar_init(rb + 8, 1); mbar_init(xb, 1);
            if (wu == 0) mbar_init(qbar, 1);
            asm volatile("fence.mbarrier_init.release.cluster;" ::: "memory");
            const int row = (h * SK + (SK - WIN) + c * 1024 + wu * 128) * 3;
            const uint32_t ring = sb + SM_RING + wu * 2 * TILE;
#pragma unroll
            for (int n = 0; n < 3; n++) {
                const uint32_t bar = ((IN_S1 >> n) & 1) ? rb + 8 : ((IN_S0 >> n) & 1) ? rb : xb;
                mbar_expect_tx(bar, TILE);
                tma2d(((IN_S1 >> n) & 1) ? ring + TILE : ((IN_S0 >> n) & 1) ? ring : sb + SM_B + wu * TILE, &maps.k, 0, row + 48 * n, bar, POL_EF);
                if (n == 0 && wu == 0) {
                    mbar_expect_tx(qbar, 61440);
                    tma3d(sb + SM_Q, &maps.wq, 0, 160 * c, 3 * h, qbar, POL_EF);
                }
            }
            if (wu == 1) {
                mbar_init(fbar, 1);
#pragma unroll
                for (int i = 0; i < 3; i++) mbar_init(wbar + 8 * i, 1);
                asm volatile("fence.mbarrier_init.release.cluster;" ::: "memory");
            }
            if (wu >= 2) {
                const CUtensorMap* mp = wu == 2 ? &maps.v : wu == 3 ? &maps.wo : wu == 4 ? &maps.w1 : wu == 5 ? &maps.w3 : wu == 6 ? &maps.w2 : &maps.vr;
                asm volatile("prefetch.tensormap [%0];" ::"l"(mp) : "memory");
            }
        }
        if (tid < 160) asm volatile("ld.global.nc.v2.u32 {%0,%1}, [%2];" : "=r"(xv.x), "=r"(xv.y) : "l"(x_in + 4 * tid) : "memory");
        if (tid == 96) { misc[2] = 0.f; misc[3] = 0.f; }
        if (lane == 1) *reinterpret_cast<uint2*>(smem + SM_XL + warp * XSTR) = make_uint2(0u, t_start + WO_T0);
        if (tid >= 128 && tid < 148) {
            const uint32_t v = tid < 138 ? ONES : 0u;
            reinterpret_cast<uint4*>(smem + SM_ONE)[tid - 128] = make_uint4(v, v, v, v);
        }
        if (tid < 160) { xs32[xpos(2 * tid)] = xv.x; xs32[xpos(2 * tid + 1)] = xv.y; }
        __syncthreads();
        PROF_T(14);
        if (b == 0 && tid >= 232) asm volatile("st.relaxed.gpu.global.u32 [%0], %1;" ::"l"(g_scr.ticket + tid - 232), "r"(0) : "memory");
        if (tid == 64 || (tid == 65 && b < 216 - NCTA)) st_pkt(&g_scr.acc[1][acc_pos(b + NCTA * (tid - 64))], 0, 0, 0, 0);
    }

    uint32_t kq[NQ][4];
    const float SC = 0.07216878364870322f * 1.4426950408889634f;

#pragma unroll 1
    for (int ph = 0; ph < 3; ph++) {
        const int layer = ph >> 1;
        const uint32_t tag = layer + 1;
        PROF_T(1 + layer * 16);
        if (ph) {
        {
            const int tl = opq(tid), warp = tl >> 5, lane = tl & 31, g = lane >> 2, t = lane & 3, mat = lane >> 3, r8 = lane & 7;
            const int kh = warp >> 2, mg = warp & 3;
            uint32_t aq[3];
#pragma unroll
            for (int i = 0; i < 3; i++) {
                const int ch = 6 * mg + 2 * i + (mat & 1);
                aq[i] = sb + SM_Q + (80 * kh + (mat >> 1) * 8 + r8) * 128 + (ch >> 3) * 20480 + (((ch & 7) ^ r8) << 4);
            }
#define PF_K5 if (layer == 1 && PFK) tile_keep(&maps.k, (h * SK + (SK - WIN) + c * 1024 + wu * 128 + PFK * 16) * 3);
            uint2 xv = make_uint2(0u, 0u);
            mbar_wait(qbar, 0);
            uint32_t pre[6][4];
#pragma unroll
            for (int n = 0; n < 6; n++) ldsm4t(aq[n % 3] + (n / 3) * 2048, pre[n]);
            if (layer == 1) {
                __syncthreads();
                if (elect_one()) {
                    const uint32_t bar = sb + SM_BAR + wu * 16;
                    asm volatile("mbarrier.expect_tx.relaxed.cta.shared::cta.b64 [%0], 1536;" ::"r"(bar) : "memory");
#pragma unroll
                    for (int k = 0; k < 3; k++)
                        tma2d(sb + SM_Q + v1_pos(3 * wu + k), &maps.vr, 0, (h * SK + (SK - WIN) + c * 1024 + wu * 128) / 2 + 8 + 2 * k, bar, POL_EF);
                }
            }
            const uint32_t pm = opq(g == 1 ? sb + SM_ONE : sb + SM_XS + 160 * (2 * c + kh) + 16 * t), pm2 = opq(pm + 128 - (g == 1 ? 0 : 8 * t));
            const uint32_t dq = opq(sb + SM_R + 8 * (kh * 192 + 48 * mg + g)), ds = opq(sb + SM_ST + 8 * warp + (lane < 16 ? 4 : 0));
            const bool wr = t == 0, ws = (lane & 15) == 0, lo = lane < 16;
            if (wu < 5) {
                const int p0 = xpos(2 * tl), p1 = xpos(2 * tl + 1);
                if (layer == 1) {
                    uint4 v;
                    for (int it = 0; it < SPIN_CAP; it++) { v = ld_pkt(&g_scr.ay[tl]); if (__all_sync(0xffffffffu, v.w == 1)) break; }
                    xv = make_uint2(v.x, v.y);
                    xs32[p0] = xv.x; xs32[p1] = xv.y;
                } else xv = make_uint2(xs32[p0], xs32[p1]);
            }
            if (layer) PC(24);
            __syncthreads();
            PF_K5
            if (layer) PC(25);
            PROF_T(13 + layer * 16);
            const float e0 = bf_lo(xv.x), e1 = bf_hi(xv.x), e2 = bf_lo(xv.y), e3 = bf_hi(xv.y);
            const float s1 = (e0 + e1) + (e2 + e3), s2 = (e0 * e0 + e1 * e1) + (e2 * e2 + e3 * e3);
            float sv = lo ? s1 : s2, cc[3][4];
            gemv15<2048>(cc, pre, [&](int i) { return aq[i]; }, pm, pm2, sv, lo ? s2 : s1);
            if (wr) {
#pragma unroll
                for (int i = 0; i < 3; i++) { sts64(dq + 128 * i, cc[i][0], cc[i][1]); sts64(dq + 128 * i + 64, cc[i][2], cc[i][3]); }
            }
            if (ws) sts32(ds, sv);
        }
        const uint32_t pa = opq(sb + SM_R + 32 * opq(tid)), st = opq(sb + SM_ST);
        uint4* const pq = opq(&g_scr.hx[b * 48 + opq(tid)]);
        if (layer) PC(26);
        __syncthreads();
        if (layer) PC(27);
        PROF_T(33 + layer * 16);
        if (wu < 2) {
            float mean, inv;
            ln_stats(st, mean, inv);
            const float4 a0 = lds4f(pa), a1 = lds4f(pa + 16), b0 = lds4f(pa + 1536), b1 = lds4f(pa + 1552);
            const float q0 = (a0.x + b0.x) - mean * (a0.y + b0.y), q1 = (a0.z + b0.z) - mean * (a0.w + b0.w);
            const float q2 = (a1.x + b1.x) - mean * (a1.y + b1.y), q3 = (a1.z + b1.z) - mean * (a1.w + b1.w);
            st_pktfp(pq, q0, q1, q2, q3, 1, tid < 48);
        }
        if (layer == 1 && tid >= 192 && tid < 194 && b < 108) st_pkt(&g_scr.acc[0][acc_pos(2 * b + opq(tid) - 192)], 0, 0, 0, 0);
        }
        if (layer) PC(28);
        if (layer == 1 && (wu & 2)) {
            idle(K5D);
            tile_load(sb + SM_Q + c_slot(wu), &maps.k, (h * SK + (SK - WIN) + c * 1024 + wu * 128 + 5 * 16) * 3, sb + SM_XBAR + wu * 8, 0, 0);
        }

        float sc0 = -INFINITY, sc1 = -INFINITY, sc2 = 0.f, sc3 = 0.f, mw;
        uint32_t pk0, pk1;
        float acc[3][4];
        {
            const uint32_t ring = sb + SM_RING + wu * 2 * TILE, rb = sb + SM_BAR + wu * 16;
            const uint32_t xtile = sb + SM_Q + c_slot(wu), xb = sb + SM_XBAR + wu * 8;
#define V_SEQ(n) ((int)(SEQ1 >> (4 * (n))) & 7)
#define SLOT1(n) (((IN_S1 >> (n)) & 1) ? ring + TILE : ((IN_S0 >> (n)) & 1) ? ring : sb + SM_B + wu * TILE)
#define BAR1(n) (((IN_S1 >> (n)) & 1) ? rb + 8 : ((IN_S0 >> (n)) & 1) ? rb : xb)
#define PAR1(n) ((PARITY1 >> (n)) & 1)
#define PAR2(n) ((PARITY2 >> (n)) & 1)
            const int row0 = (h * SK + (SK - WIN) + c * 1024 + wu * 128) * 3;
            auto issue1 = [&](int n, uint32_t dep, bool vph = false) {
                const CUtensorMap* mp = n < 8 ? &maps.k : &maps.v;
                const int tl = V_SEQ(n), row = row0 + tl * 48;
                const uint32_t dst = SLOT1(n), bar = BAR1(n);
                if (vph && wu < L1R && tl == 7 - (wu & 1)) {
                    tile_load_l1(dst, maps.vp, row, bar, opq(tid) & 31);
                    return;
                }
                tile_load(dst, mp, row, bar, dep, maps.zero);
                if ((RT_SEL >> (tl + (n & 8))) & 1) {
                    if (n != V0_AT + 1) tile_keep(mp, row);
                    else if ((opq(tid) & 31) < 8)
                        asm volatile("cp.async.bulk.prefetch.L2.global.L2::cache_hint [%0], 256, %1;"
                                     ::"l"(static_cast<const char*>(maps.vp) + (size_t)(row + 4 + 6 * (opq(tid) & 31)) * 128), "l"(POL_EN) : "memory");
                }
            };
            auto refill1 = [&](int s, uint32_t dep, bool vph = false) { issue1(s + (!vph || s < V0_AT ? 3 : 2), dep, vph); };
#define LANE_IDS const int tl = opq(tid), lane = tl & 31, g = lane >> 2, t = lane & 3; (void)tl; (void)lane; (void)g; (void)t;
            const uint32_t xl = sb + SM_XL + wu * XSTR;
            if (layer == 0) {
#pragma unroll 1
                for (int s = ph ? Q_AT : 0; s < (ph ? 5 : Q_AT); s++) {
                    LANE_IDS
                    const uint32_t tile = SLOT1(s);
                    mbar_wait(BAR1(s), PAR1(s));
                    const uint32_t scl = s == 0 ? pack_scale(tile, lane, xl + 8) : lds32(xl + 8);
                    pack_tile<false>(tile, s, 3, scl, xl, lane, [](int, uint32_t (&)[3]) {});
#pragma unroll
                    for (int n = 0; n < 5; n++) {
                        if (s == n) {
#pragma unroll
                            for (int m = 0; m < 3; m++) {
                                const uint32_t a = tile + K_OFF(2 * m);
                                lds128(a, kq[9 * n + 3 * m][0], kq[9 * n + 3 * m][1], kq[9 * n + 3 * m][2], kq[9 * n + 3 * m][3]);
                                lds128(a ^ 64, kq[9 * n + 3 * m + 1][0], kq[9 * n + 3 * m + 1][1], kq[9 * n + 3 * m + 1][2], kq[9 * n + 3 * m + 1][3]);
                                lds128(a + 3072, kq[9 * n + 3 * m + 2][0], kq[9 * n + 3 * m + 2][1], kq[9 * n + 3 * m + 2][2], kq[9 * n + 3 * m + 2][3]);
                            }
                        }
                    }
                    __syncwarp();
                    refill1(s, lds32(tile));
                }
                if (!ph) continue;
            }
            {
                if (wu < 2) {
                    const int tl = min(opq(tid), 47);
                    const int w = 2 * tl;
                    const uint32_t pos = opq(sb + SM_QS + 4 * (((w >> 2) & 3) * 24 + 2 * (w >> 4) + ((w >> 1) & 1)));
                    uint4 v[4];
                    float mean, inv;
                    ln_stats(opq(sb + SM_ST), mean, inv);
                    for (int it = 0; it < SPIN_CAP; it++) {
#pragma unroll
                        for (int k = 0; k < 4; k++) v[k] = ld_pkt(&g_scr.hx[(h * 4 + k) * 48 + tl]);
                        if (all_odd(v[0].w, v[1].w, v[2].w, v[3].w)) break;
                    }
                    sts32(pos, f_(pack2(inv * ((f_(v[0].x) + f_(v[1].x)) + (f_(v[2].x) + f_(v[3].x))), inv * ((f_(v[0].y) + f_(v[1].y)) + (f_(v[2].y) + f_(v[3].y))))));
                    sts32(pos + 48, f_(pack2(inv * ((f_(v[0].z) + f_(v[1].z)) + (f_(v[2].z) + f_(v[3].z))), inv * ((f_(v[0].w) + f_(v[1].w)) + (f_(v[2].w) + f_(v[3].w))))));
                }
            }
            if (layer) PC(29);
            __syncthreads();
            if (layer) PC(30);
            PROF_T(2 + layer * 16);
#define V1_REST(p) ((p) < 6 ? sb + SM_Q + v1_pos(3 * wu + ((p) >> 1)) + 256 * ((p) & 1) : ((sb + SM_R + wu * 784 + 127) & ~127u) - 1536 + 256 * (p))
#define V1_LOAD(bar) if (elect_one()) tma2d(V1_REST(6), &maps.vr, 0, row0 / 6 + 14, bar, POL_EF);
#define V1_EXPECT(bar) { if ((opq(tid) & 31) == 0) asm volatile("mbarrier.expect_tx.relaxed.cta.shared::cta.b64 [%0], 512;" ::"r"(bar) : "memory"); }
            if (layer == 1 && !(wu & 2)) tile_load(xtile, &maps.k, row0 + 5 * 48, xb, 0, 0);
            if (layer == 1 && wu >= 4) idle(STAG);
            {
                uint32_t qf[12];
                int t;
                {
                    const int lane = opq(tid) & 31;
                    t = lane & 3;
                    const uint32_t qa = sb + SM_QS + (2 * t + ((lane >> 2) & 1)) * 48;
#pragma unroll
                    for (int i = 0; i < 3; i++) lds128(qa + 16 * i, qf[4 * i], qf[4 * i + 1], qf[4 * i + 2], qf[4 * i + 3]);
                }
                const uint32_t sq = lds32(xl + 8) - 64u * 0x00800080u;
#pragma unroll
                for (int i = 0; i < 12; i++) qf[i] = bmul2(qf[i], sq);
#define KR_STEP(tau, m) \
                    _Pragma("unroll") for (int i = 2 * (m); i < 2 * (m) + 2; i++) { \
                        const int q0 = 9 * tau + 3 * (i >> 1), r = i & 1; \
                        uint32_t w[4]; \
                        unpack8(kq[q0][2 * r], kq[q0][2 * r + 1], kq[q0 + 2][r], w); \
                        mma16816(cA, w[0], w[1], w[2], w[3], qf[2 * i], qf[2 * i + 1]); \
                        unpack8(kq[q0 + 1][2 * r], kq[q0 + 1][2 * r + 1], kq[q0 + 2][2 + r], w); \
                        mma16816(cB, w[0], w[1], w[2], w[3], qf[2 * i], qf[2 * i + 1]); \
                    }
#define KR_BEGIN float cA[4] = {0.f, 0.f, 0.f, 0.f}, cB[4] = {0.f, 0.f, 0.f, 0.f};
#define KR_END(tau) \
                    const float sA = (cA[0] + cA[3]) * 18446744073709551616.f, sB = (cB[0] + cB[3]) * 18446744073709551616.f; \
                    if (t == (tau & 3)) { if (tau < 4) { sc0 = sA; sc1 = sB; } else { sc2 = sA; sc3 = sB; } }
#define KR_SCORES(tau) { KR_BEGIN KR_STEP(tau, 0) KR_STEP(tau, 1) KR_STEP(tau, 2) KR_END(tau) }
                uint32_t va[3];
                {
                    const int lane = opq(tid) & 31, g = lane >> 2, t = lane & 3;
#pragma unroll
                    for (int i = 0; i < 3; i++) va[i] = ring + V_OFF(2 * i);
                }
#define V_STG(n) _Pragma("unroll") for (int j = 3 * (n); j < 3 * (n) + 3; j++) { \
                    const int i = (j % 12) >> 1; \
                    lds128p(((i & 1) ? (va[i >> 1] ^ 16) + 128 : va[i >> 1]) + (j / 12) * TILE + (j & 1) * 3072, layer, kq[j][0], kq[j][1], kq[j][2], kq[j][3]); }
                uint32_t dep = 0;
                {
                    KR_BEGIN
                    KR_STEP(0, 0) V_STG(0) KR_STEP(0, 1) V_STG(1) KR_STEP(0, 2) V_STG(2)
                    KR_END(0)
                }
                {
                    KR_BEGIN
                    KR_STEP(1, 0) V_STG(3)
                    __syncwarp();
                    dep = lds32(ring);
                    if (layer == 1) tile_load(ring, &maps.k, row0 + 6 * 48, rb, dep, maps.zero);
                    KR_STEP(1, 1) V_STG(4) KR_STEP(1, 2) V_STG(5)
                    KR_END(1)
                }
                {
                    KR_BEGIN
                    KR_STEP(2, 0) V_STG(6) KR_STEP(2, 1) V_STG(7)
                    __syncwarp();
                    dep = lds32(ring + TILE);
                    KR_STEP(2, 2)
                    if (layer == 1) {
                        V1_EXPECT(rb + 8)
                        tile_load(ring + TILE, &maps.k, row0 + 7 * 48, rb + 8, dep, maps.zero);
                        V1_LOAD(rb + 8)
                    }
                    KR_END(2)
                }
#pragma unroll 1
                for (int s = 5; s < 8; s++) {
                    {
                        LANE_IDS
                        const uint32_t tile = !layer ? SLOT1(s) : s == 5 ? xtile : ring + (s - 6) * TILE, tb = !layer ? BAR1(s) : s == 5 ? xb : rb + (s - 6) * 8;
                        const float ur = f_((318u << 23) - (lds32(xl + 8) << 16));
                        mbar_wait(tb, layer ? PAR2(s - 5) : PAR1(s));
                        if (layer) PROF_T(29 + s);
                        float cA[4] = {0.f, 0.f, 0.f, 0.f}, cB[4] = {0.f, 0.f, 0.f, 0.f};
#pragma unroll
                        for (int i = 0; i < 6; i++) {
                            uint32_t a0, a1, a2, a3;
                            lds128(tile + K_OFF(i), a0, a1, a2, a3);
                            mma16816(cA, a0, a1, a2, a3, qf[2 * i], qf[2 * i + 1]);
                            lds128(tile + K_OFF(i) + 3072, a0, a1, a2, a3);
                            mma16816(cB, a0, a1, a2, a3, qf[2 * i], qf[2 * i + 1]);
                        }
                        __syncwarp();
                        const uint32_t last = lds32(tile);
                        if (layer) tile_load(tile, &maps.v, row0 + (s - 2) * 48, tb, last, maps.zero);
                        else refill1(s, last);
                        if (t == (s & 3)) { sc2 = (cA[0] + cA[3]) * ur; sc3 = (cB[0] + cB[3]) * ur; }
                    }
                    if (s == 5) KR_SCORES(3)
                    if (s == 6) {
                        KR_SCORES(4)
                        const int lane = opq(tid) & 31;
                        const uint32_t nx = min(lds32(xl), (uint32_t)XCAP);
#pragma unroll 1
                        for (uint32_t n = 0; n < nx; n++) {
                            const uint32_t id = lds32(xl + 16 + 4 * n);
                            const uint32_t qo = 96 * ((id >> 7) & 3) + 48 * ((id >> 1) & 1) + 16 * ((id >> 5) & 3) + (id & 12) + 2 * (id & 1);
                            const float cr = bf_hi(id) * f_(lds16(sb + SM_QS + qo) << 16);
                            const int d = (int)(16 * ((id >> 9) & 7) + 4 * ((id >> 12) & 3) + ((id >> 13) & 2) + ((id >> 4) & 1) + ((id >> 8) & 128)) - 4 * lane;
                            if (d == 0) sc0 += cr;
                            if (d == 1) sc1 += cr;
                            if (d == 2) sc2 += cr;
                            if (d == 3) sc3 += cr;
                        }
                    }
                }
#undef KR_SCORES
#undef KR_STEP
#undef KR_BEGIN
#undef KR_END
#undef V_STG
                {
                    LANE_IDS
                    if (lds32(xl) > XCAP || !__all_sync(0xffffffffu, (fabsf(sc0) + fabsf(sc1)) + (fabsf(sc2) + fabsf(sc3)) < INFINITY)) {
                        const uint32_t qa = sb + SM_QS + (2 * t + (g & 1)) * 48;
#pragma unroll
                        for (int i = 0; i < 3; i++) lds128(qa + 16 * i, qf[4 * i], qf[4 * i + 1], qf[4 * i + 2], qf[4 * i + 3]);
                        const uint4* kg = reinterpret_cast<const uint4*>(static_cast<const char*>(maps.kp) + (size_t)row0 * 128) + ((g >> 1) + 4 * (g & 1)) * 24 + t;
#pragma unroll 1
                        for (int s = 0; s < 8; s++) {
                            float cA[4] = {0.f, 0.f, 0.f, 0.f}, cB[4] = {0.f, 0.f, 0.f, 0.f};
#pragma unroll
                            for (int i = 0; i < 6; i++) {
                                uint4 u = ldg128(kg + s * 384 + 4 * i);
                                mma16816v(cA, u.x, u.y, u.z, u.w, qf[2 * i], qf[2 * i + 1]);
                                u = ldg128(kg + s * 384 + 4 * i + 192);
                                mma16816v(cB, u.x, u.y, u.z, u.w, qf[2 * i], qf[2 * i + 1]);
                            }
                            if (t == s) { sc0 = cA[0] + cA[3]; sc1 = cB[0] + cB[3]; }
                            if (t + 4 == s) { sc2 = cA[0] + cA[3]; sc3 = cB[0] + cB[3]; }
                        }
                    }
                }
            }
            mw = warp_max(fmaxf(fmaxf(sc0, sc1), fmaxf(sc2, sc3)));
            pk0 = pack2(ex2((sc0 - mw) * SC), ex2((sc1 - mw) * SC));
            pk1 = pack2(ex2((sc2 - mw) * SC), ex2((sc3 - mw) * SC));
            sc2 = (bf_lo(pk0) + bf_hi(pk0)) + (bf_lo(pk1) + bf_hi(pk1));
            sc2 = (float)__reduce_add_sync(0xffffffffu, __float2uint_rn(sc2 * 16777216.f)) * (1.0f / 16777216.f);
            if ((opq(tid) & 31) == 0) st_pkt2(&g_scr.mx[h * 32 + c * 8 + wu], __float_as_uint(mw), (__float_as_uint(sc2) & ~3u) | tag);
            auto head_factor = [&]() {
                const int lane = opq(tid) & 31;
                int it = 0;
                while (!__all_sync(0xffffffffu, (__float_as_uint(sc1) & 3u) == tag) && ++it < SPIN_CAP) {
                    const uint2 mv = ld_pkt2(&g_scr.mx[h * 32 + lane]); sc0 = f_(mv.x); sc1 = f_(mv.y);
                }
                const float e = ex2((sc0 - warp_max(sc0)) * SC);
                const uint32_t d = __reduce_add_sync(0xffffffffu, __float2uint_rn(sc1 * e * 524288.f));
                sc3 = __shfl_sync(0xffffffffu, e, c * 8 + wu) * 524288.f * rcp((float)d);
            };
#pragma unroll
            for (int s = 0; s < 3; s++) { acc[s][0] = acc[s][1] = acc[s][2] = acc[s][3] = 0.f; }
#define P_CONSTS \
                const uint32_t sel0 = g == 0 ? 0x4410u : (g == 1 ? 0x1044u : 0x4444u); \
                const uint32_t sel1 = g == 2 ? 0x4410u : (g == 3 ? 0x1044u : 0x4444u); \
                const int src00 = 4 * (t < 2 ? 4 * t : 4 * (t - 2) + 1);
#define P_FRAGS(tau) \
                const uint32_t pk = ((tau) & 4) ? pk1 : pk0; \
                const uint32_t w0 = __shfl_sync(0xffffffffu, pk, src00 + ((tau) & 3)); \
                const uint32_t w1 = __shfl_sync(0xffffffffu, pk, src00 + ((tau) & 3) + 8); \
                uint32_t pb[4][2]; \
                _Pragma("unroll") for (int j = 0; j < 4; j++) { \
                    const uint32_t src = ((j & 1) ? w1 : w0) >> ((j >> 1) * 16); \
                    pb[j][0] = __byte_perm(src, 0, sel0); pb[j][1] = __byte_perm(src, 0, sel1); \
                }
            if (layer == 0) {
#pragma unroll 1
                for (int s = 8; s < 16; s++) {
                    LANE_IDS
                    P_CONSTS
                    if (s == 13) { const uint2 mv = ld_pkt2(&g_scr.mx[h * 32 + lane]); sc0 = f_(mv.x); sc1 = f_(mv.y); }
                    P_FRAGS(V_SEQ(s))
                    mbar_wait(BAR1(s), PAR1(s));
                    const uint32_t tile = SLOT1(s);
#pragma unroll
                    for (int j = 0; j < 4; j++) {
#pragma unroll
                        for (int u = 0; u < 3; u++) {
                            uint32_t a0, a1, a2, a3;
                            lds128(tile + (j >> 1) * 3072 + V_OFF(3 * (j & 1) + u), a0, a1, a2, a3);
                            mma16816(acc[u], a0, a1, a2, a3, pb[j][0], pb[j][1]);

                        }
                    }
                    __syncwarp();
                    if (s < V0_AT || (s > V0_AT + 1 && s < 14)) refill1(s, lds32(tile), true);
                    if (s == V0_AT || s == V0_AT + 1) {
                        {
                            const uint32_t ar = sb + SM_R + wu * 784 + 32 * g + 16 * t;
                            if (t < 2) {
#pragma unroll
                                for (int u = 0; u < 3; u++) sts128(ar + 256 * u, __float_as_uint(acc[u][0]), __float_as_uint(acc[u][1]), __float_as_uint(acc[u][2]), __float_as_uint(acc[u][3]));
                            }
                        }
                        const uint32_t scl = s == V0_AT ? pack_scale(tile, lane, xl + 12) : lds32(xl + 12);
                        pack_tile<true>(tile, s + 8 - V0_AT, V0_AT + 3 - s, scl, xl, lane, [&](int m, uint32_t (&d)[3]) {
                            if (s != V0_AT && m == 0) {
#pragma unroll
                                for (int k = 0; k < 3; k++) d[k] = ring + 3072 + V_OFF(2 * k + 1);
                            }
                        });
                        if (s != V0_AT) {
                            lds128(tile + V_OFF(2), kq[45][0], kq[45][1], kq[45][2], kq[45][3]);
                            lds128(tile + V_OFF(3), kq[46][0], kq[46][1], kq[46][2], kq[46][3]);
                            lds128(tile + V_OFF(2) + 3072, kq[47][0], kq[47][1], kq[47][2], kq[47][3]);
                            __syncwarp();
                            issue1(V0_AT + 3, lds32(tile));
                        }
                        const int ln = opq(tid) & 31;
                        const uint32_t ar = sb + SM_R + wu * 784 + 8 * (ln & 28) + 16 * (ln & 1);
#pragma unroll
                        for (int u = 0; u < 3; u++) {
                            uint32_t a0, a1, a2, a3;
                            lds128(ar + 256 * u, a0, a1, a2, a3);
                            acc[u][0] = f_(a0); acc[u][1] = f_(a1); acc[u][2] = f_(a2); acc[u][3] = f_(a3);
                        }
                    }
                    if (s == 13) head_factor();
                    if (s >= 14 && elect_one()) {
                        if (atomicAdd(reinterpret_cast<unsigned*>(misc + 3), 1u) == 14u && (int)(now_ns() - lds32(xl + 4)) >= 0) {
                            PROF_X(47);
                            load_wo(maps, sb + SM_B, h, c, wbar, 6);
                            atomicAdd(reinterpret_cast<unsigned*>(misc + 3), 256u);
                        }
                    }
                }
            } else {
                LANE_IDS
                P_CONSTS
#pragma unroll
                for (int k = 0; k < 4; k++) lds128(V1_REST(t + 4 * (k >> 1)) + 16 * g + 128 * (k & 1), kq[36 + k][0], kq[36 + k][1], kq[36 + k][2], kq[36 + k][3]);
#pragma unroll 1
                for (int i = 3; i < 8; i++) {
                    const uint32_t tile = i > 3 ? ring + (i & 1) * TILE : xtile, tb = i > 3 ? rb + (i & 1) * 8 : xb;
                    if (i == 6) { const uint2 mv = ld_pkt2(&g_scr.mx[h * 32 + lane]); sc0 = f_(mv.x); sc1 = f_(mv.y); }
                    if (i == 7) head_factor();
                    if (i == PK_AT) {
                uint32_t nx, nk, ik, iv;
                lds128(xl, nx, nk, ik, iv);
                if (nx <= XCAP) {
                    const uint32_t pks = bmul2(pk0, iv);
#pragma unroll
                    for (int s = 0; s < 2; s++) {
                        const uint32_t pk1 = 0, pk0 = pks;
                        P_FRAGS(s)
#pragma unroll
                        for (int j = 0; j < 4; j++) {
#pragma unroll
                            for (int u = 0; u < 3; u++) {
                                const int i = 3 * (j & 1) + u, m = i >> 1, r = i & 1, hf = j >> 1;
                                if (s == 1 && m == 2) continue;
                                const int ql = s == 0 ? 4 * m + 2 * hf : m == 0 ? 3 + 4 * hf : 45 + hf, qc = s == 0 ? 4 * m + 1 : m == 0 ? 11 : 47;
                                uint32_t w[4];
                                unpack8(kq[ql][2 * r], kq[ql][2 * r + 1], kq[qc][2 * hf + r], w);
                                mma16816(acc[u], w[0], w[1], w[2], w[3], pb[j][0], pb[j][1]);
                            }
                        }
                    }
#pragma unroll 1
                    for (uint32_t n = 0; n < nx; n++) {
                        const uint32_t id = lds32(xl + 16 + 4 * n);
                        const int i = ((id >> 4) & 6) + ((id >> 3) & 1), key = ((id >> 6) & 6) + (i >= 3);
                        const uint32_t pw = __shfl_sync(0xffffffffu, pk0, 8 * (key & 3) + (key & 4) + ((id >> 12) & 3));
                        const float cr = bf_hi(id) * ((id & 16) ? bf_hi(pw) : bf_lo(pw));
                        const int d = (int)(64 * ((id >> 9) & 7) + 4 * (id & 4) + 4 * (i >= 3 ? i - 3 : i) + (id & 3) + ((~id >> 5) & 1024)) - 16 * lane;
#pragma unroll
                        for (int k = 0; k < 12; k++) if (d == k) acc[k >> 2][k & 3] += cr;
                    }
                } else {
                    const uint4* vg = reinterpret_cast<const uint4*>(static_cast<const char*>(maps.vp) + (size_t)row0 * 128) + 48 * t + g;
#pragma unroll 1
                    for (int s = 0; s < 2; s++) {
                        P_FRAGS(s)
#pragma unroll
                        for (int j = 0; j < 4; j++) {
#pragma unroll
                            for (int u = 0; u < 3; u++) {
                                if (s == 1 && (j & 1) && u) continue;
                                const uint4 w = ldg128(vg + 384 * s + 192 * (j >> 1) + 24 * (j & 1) + 8 * u);
                                mma16816v(acc[u], w.x, w.y, w.z, w.w, pb[j][0], pb[j][1]);
                            }
                        }
                    }
                }
#pragma unroll
                for (int s = 2; s > 0; s--) {
                    P_FRAGS(s)
#pragma unroll
                    for (int j = 0; j < 4; j++) {
#pragma unroll
                        for (int u = 0; u < 3; u++) {
                            if (s == 1 && !((j & 1) && u)) continue;
                            const int k = s == 2 ? 12 + 2 * (3 * (j & 1) + u) + (j >> 1) : 35 + (j >> 1) * 2 + u;
                            mma16816(acc[u], kq[k][0], kq[k][1], kq[k][2], kq[k][3], pb[j][0], pb[j][1]);
                        }
                    }
                }
                    }
                    P_FRAGS(i)
                    mbar_wait(tb, PAR2(i));
                    PROF_T(34 + i);
#pragma unroll
                    for (int k = 0; k < 6; k++) {
                        const uint32_t a = tile + V_OFF(k);
                        lds128(a, kq[24 + k][0], kq[24 + k][1], kq[24 + k][2], kq[24 + k][3]);
                        lds128(a + 3072, kq[30 + k][0], kq[30 + k][1], kq[30 + k][2], kq[30 + k][3]);
                    }
#pragma unroll
                    for (int j = 0; j < 4; j++) {
#pragma unroll
                        for (int u = 0; u < 3; u++) {
                            const int k = 24 + 6 * (j >> 1) + 3 * (j & 1) + u;
                            mma16816(acc[u], kq[k][0], kq[k][1], kq[k][2], kq[k][3], pb[j][0], pb[j][1]);
                        }
                    }
                    __syncwarp();
                    if (wu < L1R && i == 5 - (wu & 1)) tile_load_l1(tile, maps.vp, row0 + (i + 2) * 48, tb, lane);
                    else if (i == 4 || i == 5) tile_load(tile, &maps.v, row0 + (i + 2) * 48, tb, lds32(tile), maps.zero);
                    if (i == WO_AT1 && HAS_FFN && elect_one()) {
                        if (atomicAdd(reinterpret_cast<unsigned*>(misc + 2), 1u) == 7u) {
                            PROF_X(63);
                            load_wo(maps, sb + SM_Q, h, c, wbar, KEEP4 && __float_as_uint(misc[1]) >= DN0 ? 5 : 6);
                        }
                    }
                }
            }
#undef P_FRAGS
#undef P_CONSTS
#undef LANE_IDS
        }
        PROF_T(3 + layer * 16);
        PC(layer * 32 + 1);

        {
            const int lane = opq(tid) & 31;
            const uint32_t a = sb + SM_R + wu * 784 + 8 * (lane & 28) + 16 * (lane & 1);
#pragma unroll
            for (int u = 0; u < 3; u++) sts128p(a + 256 * u, acc[u][0] * sc3, acc[u][1] * sc3, acc[u][2] * sc3, acc[u][3] * sc3, lane & 2);
        }
        const uint32_t role1 = layer ? lds32(sb + SM_MISC + 4) : DN0 + NDN;
        const uint32_t pc = opq(sb + SM_R + 16 * opq(tid));
        uint4* const px0 = opq(&g_scr.hx[b * 48 + opq(tid)]);
        __syncthreads();
        PROF_T(4 + layer * 16);
        PC(layer * 32 + 2);
        float4 o = make_float4(0.f, 0.f, 0.f, 0.f);
        if (wu < 2) {
            float4 v[8];
#pragma unroll
            for (int w = 0; w < 8; w++) v[w] = lds4f(pc + w * 784);
            o.x = ((v[0].x + v[1].x) + (v[2].x + v[3].x)) + ((v[4].x + v[5].x) + (v[6].x + v[7].x));
            o.y = ((v[0].y + v[1].y) + (v[2].y + v[3].y)) + ((v[4].y + v[5].y) + (v[6].y + v[7].y));
            o.z = ((v[0].z + v[1].z) + (v[2].z + v[3].z)) + ((v[4].z + v[5].z) + (v[6].z + v[7].z));
            o.w = ((v[0].w + v[1].w) + (v[2].w + v[3].w)) + ((v[4].w + v[5].w) + (v[6].w + v[7].w));
            o.w = f_(__float_as_uint(o.w) & ~1u);
            st_pktp(px0, __float_as_uint(o.x), __float_as_uint(o.y), __float_as_uint(o.z), __float_as_uint(o.w), threadIdx.x < 48);
        }
        uint32_t ticket = 0;
        if (layer == 0 && tid == 224)
            asm volatile("atom.relaxed.gpu.global.inc.u32 %0, [%1], 0x7fffffff;" : "=r"(ticket) : "l"(g_scr.ticket + 8 + (b >> 3)) : "memory");
        if (layer == 0 && tid == 224 && lds32(sb + SM_MISC + 12) < 256u) {
            int it = 0;
            while ((int)(now_ns() - lds32(sb + SM_XL + 4)) < 0 && ++it < SPIN_CAP) {}
            PROF_X(47);
            load_wo(maps, sb + SM_B, h, c, wbar, 6);
        }
        uint32_t pr;
        uint4* pacc;
        {
            const int tid = opq(threadIdx.x), warp = tid >> 5, lane = tid & 31, g = lane >> 2, t = lane & 3, mat = lane >> 3, r8 = lane & 7;
            const int kg = warp >> 1, mg = warp & 1;
            const bool wo2 = role1 < DN0 + NDN;
            const uint32_t aw2 = 40960 + (wo2 && KEEP4 && role1 >= DN0 && kg >= 2 ? SM_B - SM_Q : 0);
            uint32_t aw[5];
#pragma unroll
            for (int i = 0; i < 5; i++) {
                const uint32_t lin = ((mat >> 1) * 8 + r8) * 320 + 64 * i + 32 * mg + 16 * (mat & 1);
                aw[i] = sb + (wo2 ? SM_Q : SM_B) + 5120 * kg + (lin ^ ((lin >> 3) & 48));
            }
#define CXE 0
            const uint32_t ao = pin(sb + SM_OS + 96 * kg + 16 * t), dw = pin(sb + SM_R + 16 * (16 * mg + g) + 4 * kg);
            pr = pin(sb + SM_R + 48 * tid); pacc = pin(&g_scr.acc[layer][acc_pos(54 * c + tid)]);
            const int w = 2 * min(tid, 47);
            const uint32_t d0 = pin(sb + SM_OS + 4 * (24 * ((w >> 3) & 3) + ((w >> 2) & 1) + (w < 64 ? 4 * (w & 3) + 2 * (w >> 5) : 16 + 2 * (w & 3))));
            const uint32_t d1 = pin(d0 + (w < 64 ? 16 : 8));
            const uint4* pp[3];
#pragma unroll
            for (int k = 0; k < 3; k++) pp[k] = pin(&g_scr.hx[(h * 4 + ((c + 1 + k) & 3)) * 48 + min(tid, 47)]);
            uint4 v3[3];
#pragma unroll
            for (int k = 0; k < 3; k++) v3[k] = make_uint4(0u, 0u, 0u, 1u);
            if ((PRE1 & 8) && layer) {
#pragma unroll
                for (int ks = 0; ks < 3; ks++) {
                    mbar_wait(wbar + 8 * ks, wo2);
#pragma unroll
                    for (int i = 0; i < 5; i++) ldsm4t(aw[i] + (ks == 2 ? aw2 : 20480 * ks), kq[3 * i + ks]);
                    if (ks == CXE && wu < 2) {
#pragma unroll
                        for (int k = 0; k < 3; k++) v3[k] = ld_pkt(pp[k]);
                    }
                }
                PROF_T(50);
            }
            if (wu < 2) {
                for (int it = 0; any_odd(v3[0].w, v3[1].w, v3[2].w) && it < SPIN_CAP; it++) {
#pragma unroll
                    for (int k = 0; k < 3; k++) v3[k] = ld_pkt(pp[k]);
                }
                o.x = (o.x + f_(v3[0].x)) + (f_(v3[1].x) + f_(v3[2].x)); o.y = (o.y + f_(v3[0].y)) + (f_(v3[1].y) + f_(v3[2].y));
                o.z = (o.z + f_(v3[0].z)) + (f_(v3[1].z) + f_(v3[2].z)); o.w = (o.w + f_(v3[0].w)) + (f_(v3[1].w) + f_(v3[2].w));
                sts32p(d0, f_(pack2(o.x, o.y)), tid >= 48);
                sts32p(d1, f_(pack2(o.z, o.w)), tid >= 48);
            }
            PC(layer * 32 + 3);
            __syncthreads();
            PROF_T(5 + layer * 16);
            PC(layer * 32 + 5);
            if (tid == 224 && layer == 0) {
                if (ticket >= 6 + ((b >> 3) & 1)) ticket = DN0 + NDN;
                else asm volatile("atom.relaxed.gpu.global.inc.u32 %0, [%1], 0x7fffffff;" : "=r"(ticket) : "l"(g_scr.ticket) : "memory");
            }
            uint32_t ob[6];
            lds128(ao, ob[0], ob[1], ob[2], ob[3]);
            lds64(ao + 64 - 8 * t, ob[4], ob[5]);
            float cc[5][4];
#pragma unroll
            for (int i = 0; i < 5; i++) cc[i][0] = cc[i][1] = cc[i][2] = cc[i][3] = 0.f;
            if ((PRE1 & 8) && layer) {
#pragma unroll
                for (int ks = 0; ks < 3; ks++) {
#pragma unroll
                    for (int i = 0; i < 5; i++) mma16816(cc[i], kq[3 * i + ks][0], kq[3 * i + ks][1], kq[3 * i + ks][2], kq[3 * i + ks][3], ob[2 * ks], ob[2 * ks + 1]);
                }
            } else {
#pragma unroll
                for (int ks = 0; ks < 3; ks++) {
                    mbar_wait(wbar + 8 * ks, wo2);
                    if (ks == 2) { PC(layer * 32 + 4); PROF_T(48 + layer * 2); }
                    uint32_t a[5][4];
#pragma unroll
                    for (int i = 0; i < 5; i++) ldsm4t(aw[i] + (ks == 2 ? aw2 : 20480 * ks), a[i]);
#pragma unroll
                    for (int i = 0; i < 5; i++) mma16816(cc[i], a[i][0], a[i][1], a[i][2], a[i][3], ob[2 * ks], ob[2 * ks + 1]);
                }
            }
            if (t == 0) {
#pragma unroll
                for (int i = 0; i < 5; i++) { sts32(dw + 512 * i, cc[i][0]); sts32(dw + 512 * i + 128, cc[i][2]); }
            }
        }
        PC(layer * 32 + 6);
        __syncthreads();
        PROF_T(6 + layer * 16);
        PC(layer * 32 + 7);
        if (tid < 54) {
            const float4 v0 = lds4f(pr), v1 = lds4f(pr + 16), v2 = lds4f(pr + 32);
            const float y0 = (v0.x + v0.y) + (v0.z + v0.w), y1 = (v1.x + v1.y) + (v1.z + v1.w), y2 = (v2.x + v2.y) + (v2.z + v2.w);
            red_pkt(pacc, y0, tid == 53 ? 0.f : y1, tid == 53 ? 0.f : y2);
        }
        if (tid == 224 && layer == 0) {
            misc[1] = __uint_as_float(ticket);
            if (ticket < DN0 + NDN && (ticket < NG || !DNTH)) load_ffn(maps, ticket, sb + SM_B, fbar);
        }
        PROF_T(7 + layer * 16);
        PC(layer * 32 + 8);
        __syncthreads();
        const int role = (int)__float_as_uint(misc[1]);
        PC(layer * 32 + 9);
        const uint32_t fbase = sb + SM_B;
        const uint32_t DONE32 = 0x42000000u;
        if (role < NG) {
            const int tid = opq(threadIdx.x), warp = tid >> 5, lane = tid & 31, g = lane >> 2, t = lane & 3, mat = lane >> 3, r8 = lane & 7;
            const uint32_t ag = fbase + (80 * warp + (mat >> 1) * 8 + r8) * 96 + (((mat & 1) ^ (r8 >> 2)) << 4);
            constexpr int GI = 32, GK = 16 * 96;
            const bool on = (g & 1) == (t >> 1), isx = on && g < 2;
            const uint32_t pm = opq(isx ? sb + SM_XS + 160 * warp + 16 * t : sb + (on ? SM_ONE : SM_ZERO)), pm2 = opq(pm + 128 - (isx ? 8 * t : 0));
            const uint32_t dg = opq(sb + SM_R + 4 * (2 * (warp * 48 + g) + t)), ds = opq(sb + SM_ST + 8 * warp + (lane < 16 ? 4 : 0));
            const bool ws = (lane & 15) == 0, lo = lane < 16;
            uint32_t pre[6][4];
            float s1 = 0.f, s2 = 0.f;
            {
                bool hx = false;
                int it = 0;
                const int cq = wu >> 1, odd = wu & 1, r = min(26 * odd + lane, 26 + 27 * odd), c0 = 3 * r - 80 * odd, k0 = 160 * cq + 3 * r;
                const uint4* px = &g_scr.acc[layer][acc_pos(54 * cq + r)];
                const bool act = lane <= 26 + odd;
                const bool on0 = act && c0 >= 0, on1 = act && c0 + 1 >= 0 && c0 + 1 < 80, on2 = act && c0 + 2 < 80;
                const uint32_t w0 = sb + SM_XS + 4 * xpos(k0 >> 1), w1 = sb + SM_XS + 4 * xpos(min((k0 >> 1) + 1, DM / 2 - 1));
                const uint32_t e0 = w0 + 2 * (k0 & 1), e1 = (k0 & 1) ? w1 : w0 + 2, e2 = w1 + 2 * (k0 & 1);
                auto sts16 = [](uint32_t a, uint32_t x, bool on) {
                    asm volatile("{\n.reg .pred p;\nsetp.ne.u32 p, %2, 0;\n@p st.shared.u16 [%0], %1;\n}" ::"r"(a), "h"((unsigned short)x), "r"((uint32_t)on) : "memory");
                };
                const float x0 = on0 ? f_(lds16(e0) << 16) : 0.f, x1 = on1 ? f_(lds16(e1) << 16) : 0.f, x2 = on2 ? f_(lds16(e2) << 16) : 0.f;
                auto take_x = [&](const uint4 v) {
                    if (__all_sync(0xffffffffu, v.w == DONE32)) {
                        hx = true;
                        const uint32_t a = pack2(f_(v.x), f_(v.y)), p = pack2(x0 + bf_lo(a), x1 + bf_hi(a)), q = pack2(x2 + bfr(f_(v.z)), 0.f);
                        sts16(e0, p, on0); sts16(e1, p >> 16, on1); sts16(e2, q, on2);
                        const float y0 = on0 ? bf_lo(p) : 0.f, y1 = on1 ? bf_hi(p) : 0.f, y2 = on2 ? bf_lo(q) : 0.f;
                        s1 = y0 + (y1 + y2); s2 = y0 * y0 + (y1 * y1 + y2 * y2);
                    }
                };
                auto try_x = [&]() { take_x(ld_pkt(px)); };
                while (!mbar_test(fbar, 0) && ++it < SPIN_CAP) { if (!hx) try_x(); }
                uint4 v0 = make_uint4(0u, 0u, 0u, 0u);
                if ((PRE1 & 4) && !hx) v0 = ld_pkt(px);
#pragma unroll
                for (int n = 0; n < 6; n++) ldsm4t(ag + (n % 3) * GI + (n / 3) * GK, pre[n]);
                if ((PRE1 & 1) && layer) {
#pragma unroll
                    for (int n = 6; n < 15; n++) ldsm4t(ag + (n % 3) * GI + (n / 3) * GK, kq[n - 6]);
                }
                if ((PRE1 & 4) && !hx) take_x(v0);
                PC(layer * 32 + 10);
                for (; !hx && it < SPIN_CAP; it++) try_x();
                PC(layer * 32 + 11);
            __syncwarp();
            PC(layer * 32 + 12);
            PROF_T(9 + layer * 16);
            float sv = lo ? s1 : s2, cc[3][4];
            if ((PRE1 & 1) && layer) gemv15r(cc, pre, kq, pm, pm2, sv, lo ? s2 : s1);
            else gemv15<GK>(cc, pre, [&](int i) { return ag + i * GI; }, pm, pm2, sv, lo ? s2 : s1);
#pragma unroll
            for (int i = 0; i < 3; i++) { sts32p(dg + 128 * i, cc[i][0] + cc[i][3], t & 2); sts32p(dg + 128 * i + 64, cc[i][1] + cc[i][2], t & 2); }
            if (ws) sts32(ds, sv);
            const uint32_t pg = opq(sb + SM_R + 8 * (24 * warp + (lane < 24 ? lane : 0))), st = opq(sb + SM_ST);
            uint4* const ph = opq(lane < 24 && lane % 6 == 0 ? &g_scr.ah[role * 8 + 4 * warp + lane / 6] : nullptr);
            PC(layer * 32 + 13);
            __syncthreads();
            PC(layer * 32 + 14);
            PROF_T(43 + layer * 16);
            if (wu < 2) {
                float mean, inv;
                ln_stats(st, mean, inv);
                float2 v[8];
#pragma unroll
                for (int w = 0; w < 8; w++) v[w] = lds2f(pg + w * 384);
                const float gx = ((v[0].x + v[1].x) + (v[2].x + v[3].x)) + ((v[4].x + v[5].x) + (v[6].x + v[7].x));
                const float gs = ((v[0].y + v[1].y) + (v[2].y + v[3].y)) + ((v[4].y + v[5].y) + (v[6].y + v[7].y));
                float ga = inv * (gx - mean * gs);
                if (role < NG / 2) { ga = bfr(ga); ga *= rcp(1.0f + ex2(-1.4426950408889634f * ga)); }
                const uint32_t wd = pack2(ga, __shfl_down_sync(0xffffffffu, ga, 1));
                const uint32_t wa = __shfl_down_sync(0xffffffffu, wd, 2), wb = __shfl_down_sync(0xffffffffu, wd, 4);
                if (ph) st_pkt(ph, wd, wa, wb, tag);
            }
            if (HOLD & 2) __syncthreads();
            }
            PROF_T(10 + layer * 16);
            PC(layer * 32 + 15);
        } else if (role < DN0 + NDN) {
            const int j = role - DN0;
            const int tid = opq(threadIdx.x), warp = tid >> 5, lane = tid & 31, g = lane >> 2, t = lane & 3, mat = lane >> 3, r8 = lane & 7;
            float xres = 0.f;
            uint32_t xr0 = 0, xr1 = 0;
            if (wu == 0) {
                const int col = 16 * j + (lane & 15), cc = col / 160, r = col - 160 * cc, e = r % 3;
                const uint4* px = &g_scr.acc[layer][acc_pos(54 * cc + r / 3)];
                const float x0 = __bfloat162float(reinterpret_cast<const __nv_bfloat16*>(xs32)[2 * xpos(col >> 1) + (col & 1)]);
                uint4 v;
                int it = 0;
                bool ld = DNTH && layer == 0;
                do {
                    v = ld_pkt(px);
                    if (ld && f_(__shfl_sync(0xffffffffu, v.w, 0)) >= (float)DNTH) { ld = false; if (lane == 0) load_ffn(maps, role, sb + SM_B, fbar); }
                } while (!__all_sync(0xffffffffu, v.w == DONE32) && ++it < SPIN_CAP);
                if (ld && lane == 0) load_ffn(maps, role, sb + SM_B, fbar);
                xres = x0 + bfr(f_(e == 0 ? v.x : (e == 1 ? v.y : v.z)));
                const int p4 = 4 * (lane & 3);
                xr0 = pack2(__shfl_sync(0xffffffffu, xres, p4), __shfl_sync(0xffffffffu, xres, p4 + 1));
                xr1 = pack2(__shfl_sync(0xffffffffu, xres, p4 + 2), __shfl_sync(0xffffffffu, xres, p4 + 3));
            }
            PC(layer * 32 + 17);
            PROF_T(9 + layer * 16);
            const uint32_t ad = fbase + (192 * warp + (mat >> 1) * 8 + r8) * 32 + (((mat & 1) ^ (r8 >> 2)) << 4);
            uint32_t* hs = reinterpret_cast<uint32_t*>(rr) + warp * 96;
            uint32_t pre[NPRE][4];
            {
                uint32_t pos[3];
#pragma unroll
                for (int i = 0; i < 3; i++) { const int w = 3 * lane + i; pos[i] = pin(sb + SM_R + 384 * warp + 4 * ((w & ~15) + 4 * (w & 3) + ((w >> 2) & 1) + ((w >> 2) & 2))); }
                uint4 v = make_uint4(0u, 0u, 0u, 0u), u = v;
                if (layer == 0) { v = ld_pkt(&g_scr.ah[tid]); u = ld_pkt(&g_scr.ah[256 + tid]); }
                mbar_wait(fbar, 0);
#pragma unroll
                for (int n = 0; n < NPRE; n++) ldsm4t(ad + n * 512, pre[n]);
                if ((PRE1 & 2) && layer) {
#pragma unroll
                    for (int n = NPRE; n < 12; n++) ldsm4t(ad + n * 512, kq[12 + n]);
                }
                PC(layer * 32 + 18);
                int it = 0;
                for (; any_ne(v.w, u.w, tag) && it < SPIN_CAP; it++) { v = ld_pkt(&g_scr.ah[tid]); u = ld_pkt(&g_scr.ah[256 + tid]); }
                PC(layer * 32 + 19);
                sts32(pos[0], f_(bmul2(v.x, u.x))); sts32(pos[1], f_(bmul2(v.y, u.y))); sts32(pos[2], f_(bmul2(v.z, u.z)));
            __syncwarp();
            PROF_T(11 + layer * 16);
            PC(layer * 32 + 20);
            float ca[4] = {0.f, 0.f, 0.f, 0.f}, cb[4] = {0.f, 0.f, 0.f, 0.f};
            if ((PRE1 & 2) && layer) {
                float cc[4] = {0.f, 0.f, 0.f, 0.f}, cd[4] = {0.f, 0.f, 0.f, 0.f};
#pragma unroll
                for (int jj = 0; jj < 6; jj++) {
                    const uint4 hv = *reinterpret_cast<const uint4*>(hs + 16 * jj + 4 * t);
                    const uint32_t (&f0)[4] = 2 * jj < NPRE ? pre[2 * jj < NPRE ? 2 * jj : 0] : kq[12 + 2 * jj];
                    const uint32_t (&f1)[4] = 2 * jj + 1 < NPRE ? pre[2 * jj + 1 < NPRE ? 2 * jj + 1 : 0] : kq[13 + 2 * jj];
                    if (jj & 1) { mma16816(cc, f0[0], f0[1], f0[2], f0[3], hv.x, hv.y); mma16816(cd, f1[0], f1[1], f1[2], f1[3], hv.z, hv.w); }
                    else { mma16816(ca, f0[0], f0[1], f0[2], f0[3], hv.x, hv.y); mma16816(cb, f1[0], f1[1], f1[2], f1[3], hv.z, hv.w); }
                }
#pragma unroll
                for (int e = 0; e < 4; e++) { ca[e] += cc[e]; cb[e] += cd[e]; }
            } else {
#pragma unroll
                for (int jj = 0; jj < 6; jj++) {
                    const uint4 hv = *reinterpret_cast<const uint4*>(hs + 16 * jj + 4 * t);
                    uint32_t a[4];
                    if (2 * jj < NPRE) { a[0] = pre[2 * jj][0]; a[1] = pre[2 * jj][1]; a[2] = pre[2 * jj][2]; a[3] = pre[2 * jj][3]; }
                    else ldsm4t(ad + 2 * jj * 512, a);
                    mma16816(ca, a[0], a[1], a[2], a[3], hv.x, hv.y);
                    if (2 * jj + 1 < NPRE) { a[0] = pre[2 * jj + 1][0]; a[1] = pre[2 * jj + 1][1]; a[2] = pre[2 * jj + 1][2]; a[3] = pre[2 * jj + 1][3]; }
                    else ldsm4t(ad + (2 * jj + 1) * 512, a);
                    mma16816(cb, a[0], a[1], a[2], a[3], hv.z, hv.w);
                }
            }
            if (t == 0) { rr[768 + warp * 16 + g] = ca[0] + cb[0]; rr[768 + warp * 16 + 8 + g] = ca[2] + cb[2]; }
            const uint32_t pd = opq(sb + SM_R + 3072 + 16 * (lane & 3));
            uint4* const py = opq(&g_scr.ay[j * 4 + lane]);
            uint2* const po = opq(reinterpret_cast<uint2*>(out + 16 * j) + lane);
            PC(layer * 32 + 21);
            __syncthreads();
            PC(layer * 32 + 22);
            if (wu == 0) {
                float4 p[8];
#pragma unroll
                for (int w = 0; w < 8; w++) p[w] = lds4f(pd + 64 * w);
                const uint32_t y0 = pack2(((p[0].x + p[1].x) + (p[2].x + p[3].x)) + ((p[4].x + p[5].x) + (p[6].x + p[7].x)),
                                          ((p[0].y + p[1].y) + (p[2].y + p[3].y)) + ((p[4].y + p[5].y) + (p[6].y + p[7].y)));
                const uint32_t y1 = pack2(((p[0].z + p[1].z) + (p[2].z + p[3].z)) + ((p[4].z + p[5].z) + (p[6].z + p[7].z)),
                                          ((p[0].w + p[1].w) + (p[2].w + p[3].w)) + ((p[4].w + p[5].w) + (p[6].w + p[7].w)));
                uint32_t wd, wn;
                asm("add.rn.bf16x2 %0, %1, %2;" : "=r"(wd) : "r"(xr0), "r"(y0));
                asm("add.rn.bf16x2 %0, %1, %2;" : "=r"(wn) : "r"(xr1), "r"(y1));
                asm volatile("{\n.reg .pred p;\nsetp.ne.u32 p, %3, 0;\n@p st.global.v2.u32 [%0], {%1,%2};\n}" ::"l"(po), "r"(wd), "r"(wn), "r"((uint32_t)(layer && tid < 4)) : "memory");
                st_pktp(py, wd, wn, 0, tag, tid < 4);
            }
            if (HOLD & 1) __syncthreads();
            }
            PROF_T(12 + layer * 16);
            PC(layer * 32 + 23);
        }
    }
}

typedef CUresult (*EncodeFn)(CUtensorMap*, CUtensorMapDataType, cuuint32_t, void*, const cuuint64_t*, const cuuint64_t*, const cuuint32_t*,
                             const cuuint32_t*, CUtensorMapInterleave, CUtensorMapSwizzle, CUtensorMapL2promotion, CUtensorMapFloatOOBfill);

void make_map(EncodeFn enc, CUtensorMap* m, const void* base, int rank, uint64_t d0, uint64_t d1, uint64_t d2, uint64_t s1, uint64_t s2,
              uint32_t b0, uint32_t b1, uint32_t b2, CUtensorMapSwizzle sw, CUtensorMapL2promotion pr = CU_TENSOR_MAP_L2_PROMOTION_NONE) {
    cuuint64_t dims[3] = {d0, d1, d2};
    cuuint64_t strides[2] = {s1, s2};
    cuuint32_t box[3] = {b0, b1, b2};
    cuuint32_t es[3] = {1, 1, 1};
    enc(m, CU_TENSOR_MAP_DATA_TYPE_BFLOAT16, rank, const_cast<void*>(base), dims, strides, box, es, CU_TENSOR_MAP_INTERLEAVE_NONE, sw,
        pr, CU_TENSOR_MAP_FLOAT_OOB_FILL_NONE);
}

}

extern "C" void kernel_launch(void* const* d_in, const int* in_sizes, int n_in, void* d_out, int out_size) {
    (void)in_sizes; (void)n_in; (void)out_size;
    static EncodeFn enc = nullptr;
    if (!enc) {
        void* fn = nullptr;
        cudaDriverEntryPointQueryResult qr;
        cudaGetDriverEntryPoint("cuTensorMapEncodeTiled", &fn, cudaEnableDefault, &qr);
        enc = reinterpret_cast<EncodeFn>(fn);
        cudaFuncSetAttribute(decode_kernel, cudaFuncAttributeMaxDynamicSharedMemorySize, SM_TOTAL);
    }
    Maps maps;
    make_map(enc, &maps.k, d_in[1], 2, 64, (uint64_t)NH * SK * 3, 1, 128, 0, 64, 48, 1, CU_TENSOR_MAP_SWIZZLE_128B);
    make_map(enc, &maps.v, d_in[2], 2, 64, (uint64_t)NH * SK * 3, 1, 128, 0, 64, 48, 1, CU_TENSOR_MAP_SWIZZLE_128B);
    make_map(enc, &maps.wq, d_in[3], 3, 64, DM, NH * DH / 64, NH * DH * 2, 128, 64, 160, 3, CU_TENSOR_MAP_SWIZZLE_128B);
    make_map(enc, &maps.wo, d_in[4], 3, 32, DM / 32, NH * DH, 64, DM * 2, 32, 5, 32, CU_TENSOR_MAP_SWIZZLE_64B);
    make_map(enc, &maps.vr, (const char*)d_in[2] + 512, 2, 128, (uint64_t)NH * SK / 2, 1, 768, 0, 128, 2, 1, CU_TENSOR_MAP_SWIZZLE_NONE);
    constexpr int GW = 48;
    make_map(enc, &maps.w1, d_in[6], 3, FF, 160, 4, FF * 2, 160 * FF * 2, GW, 160, 4, CU_TENSOR_MAP_SWIZZLE_NONE);
    make_map(enc, &maps.w3, d_in[7], 3, FF, 160, 4, FF * 2, 160 * FF * 2, GW, 160, 4, CU_TENSOR_MAP_SWIZZLE_NONE);
    make_map(enc, &maps.w2, d_in[8], 3, DM, 256, 6, DM * 2, 256 * DM * 2, 16, 256, 6, CU_TENSOR_MAP_SWIZZLE_32B, CU_TENSOR_MAP_L2_PROMOTION_L2_128B);
    maps.vp = d_in[2];
    maps.kp = d_in[1];
    maps.zero = 0;
    decode_kernel<<<NCTA, NT, SM_TOTAL, cudaStreamPerThread>>>(maps, (const __nv_bfloat16*)d_in[0], (__nv_bfloat16*)d_out);
}
```

```cpp
#include <cuda_runtime.h>
#include <cuda_bf16.h>
#include <cuda.h>
#include <stdint.h>
#include <math.h>

namespace {

constexpr int DM = 640;
constexpr int NH = 32;
constexpr int DH = 192;
constexpr int SK = 32768;
constexpr int WIN = 4096;
constexpr int FF = 1536;
constexpr int NCTA = 128;
constexpr int NT = 256;
constexpr int TILE = 6144;
constexpr int NG = 64;
constexpr int DN0 = 64;
constexpr int NDN = 40;

constexpr int SM_RING = 0;
constexpr int SM_B = 8 * 2 * TILE;
constexpr int SM_Q = SM_B + 61440;
__host__ __device__ constexpr int c_slot(int w) { return w < 2 ? 4096 + 10240 * w : 12288 + 6144 * w; }
__host__ __device__ constexpr int v1_pos(int n) { return 10240 * (n >> 3) + 512 * (n & 7); }
constexpr int SM_XS = SM_Q + 61440;
constexpr int SM_R = SM_XS + 1280;
constexpr int SM_ST = SM_R + 4096;
constexpr int SM_QS = SM_R + 6272;
constexpr int SM_OS = SM_QS + 384;
constexpr int SM_BAR = SM_OS + 384;
constexpr int SM_XBAR = SM_BAR + 24 * 8;
constexpr int SM_MISC = SM_XBAR + 8 * 8;
constexpr int SM_ONE = SM_MISC + 16;
constexpr int SM_ZERO = SM_ONE + 160;
constexpr int XCAP = 48;
constexpr int XSTR = 16 + 4 * XCAP;
constexpr int SM_XL = SM_ZERO + 160;
constexpr int SM_TOTAL = SM_XL + 8 * XSTR;
static_assert(SM_TOTAL <= 232448, "shared memory");

constexpr unsigned long long POL_EF = 0x12F0000000000000ull;
constexpr unsigned long long POL_EN = 0x16F0000000000000ull;

#define RT_MASK 0xF2E0u
#define RT_MASK2 0xEAE0u
#define RT_MASK3 0xFAE0u
#define WO_AT1 5
#define FFN_POL POL_EF
#define HAS_FFN (__float_as_uint(misc[1]) < DN0 + NDN)
#define WO_KEEP 2
#define NPRE 6

#define STAG 200
#define L1R 3
#define PRE1 13
#define HOLD 2
#define DNTH 27
constexpr int V0_AT = 8;
constexpr unsigned long long SEQ1 = 0x2765431076543210ull;
constexpr uint32_t IN_S1 = 0xAA49, IN_S0 = 0x124, PARITY1 = 0x6638, PARITY2 = 0xCE;
#define KEEP4 1
constexpr int NQ = 48;
constexpr int SPIN_CAP = 1 << 19;
constexpr uint32_t ONES = 0x3F803F80u;

__host__ __device__ constexpr int acc_pos(int p) { return (p >> 2) * 8 + (p & 3); }
struct alignas(4096) Scratch {
    uint4 hx[NCTA * 48];
    uint4 acc[2][512];
    uint4 ay[256];
    uint4 ah[NG * 8];
    uint2 mx[NH * 32];
    uint32_t ticket[32];
    uint32_t pad1[32];
};
__device__ Scratch g_scr;
#define PROF_T(i)
#define PROF_X(i)
#define PC(i)

__device__ __forceinline__ uint32_t smem_u32(const void* p) { return (uint32_t)__cvta_generic_to_shared(p); }
__device__ __forceinline__ void mbar_init(uint32_t bar, uint32_t cnt) {
    asm volatile("mbarrier.init.shared::cta.b64 [%0], %1;" ::"r"(bar), "r"(cnt) : "memory");
}
__device__ __forceinline__ void mbar_expect_tx(uint32_t bar, uint32_t bytes) {
    asm volatile("mbarrier.arrive.expect_tx.shared::cta.b64 _, [%0], %1;" ::"r"(bar), "r"(bytes) : "memory");
}
__device__ __forceinline__ bool mbar_test(uint32_t bar, uint32_t parity) {
    uint32_t done;
    asm volatile("{\n.reg .pred p;\nmbarrier.try_wait.parity.shared::cta.b64 p, [%1], %2;\nselp.u32 %0, 1, 0, p;\n}"
                 : "=r"(done) : "r"(bar), "r"(parity) : "memory");
    return done;
}
__device__ __forceinline__ void mbar_wait(uint32_t bar, uint32_t parity) {
    for (int it = 0; it < SPIN_CAP; it++) if (mbar_test(bar, parity)) break;
}
__device__ __forceinline__ void tma2d(uint32_t dst, const CUtensorMap* map, int c0, int c1, uint32_t bar, unsigned long long pol) {
    asm volatile("cp.async.bulk.tensor.2d.shared::cluster.global.mbarrier::complete_tx::bytes.L2::cache_hint [%0], [%1, {%3, %4}], [%2], %5;"
                 ::"r"(dst), "l"(map), "r"(bar), "r"(c0), "r"(c1), "l"(pol) : "memory");
}
__device__ __forceinline__ void tma3d(uint32_t dst, const CUtensorMap* map, int c0, int c1, int c2, uint32_t bar, unsigned long long pol) {
    asm volatile("cp.async.bulk.tensor.3d.shared::cluster.global.mbarrier::complete_tx::bytes.L2::cache_hint [%0], [%1, {%3, %4, %5}], [%2], %6;"
                 ::"r"(dst), "l"(map), "r"(bar), "r"(c0), "r"(c1), "r"(c2), "l"(pol) : "memory");
}
__device__ __forceinline__ void tile_load(uint32_t dst, const CUtensorMap* map, int row, uint32_t bar, uint32_t dep, uint32_t zero) {
    asm volatile("{\n.reg .pred p;\n.reg .b32 n;\nmad.lo.u32 n, %5, %6, 6144;\nelect.sync _|p, 0xffffffff;\n"
                 "@p mbarrier.arrive.expect_tx.shared::cta.b64 _, [%2], n;\n"
                 "@p cp.async.bulk.tensor.2d.shared::cluster.global.mbarrier::complete_tx::bytes.L2::cache_hint [%0], [%1, {0, %3}], [%2], %4;\n}"
                 ::"r"(dst), "l"(map), "r"(bar), "r"(row), "l"(POL_EF), "r"(dep), "r"(zero) : "memory");
}
__device__ __forceinline__ void tile_keep(const CUtensorMap* map, int row) {
    asm volatile("{\n.reg .pred p;\nelect.sync _|p, 0xffffffff;\n"
                 "@p cp.async.bulk.prefetch.tensor.2d.L2.global.L2::cache_hint [%0, {0, %1}], %2;\n}"
                 ::"l"(map), "r"(row), "l"(POL_EN) : "memory");
}
__device__ __forceinline__ void tile_load_l1(uint32_t dst, const void* base, int row, uint32_t bar, int lane) {
    const char* g = static_cast<const char*>(base) + (size_t)row * 128 + lane * 16;
    const uint32_t s0 = dst + (lane >> 3) * 128 + (((lane & 7) ^ (lane >> 3)) << 4), s1 = s0 ^ 64;
#pragma unroll
    for (int k = 0; k < 12; k++)
        asm volatile("cp.async.ca.shared.global.L2::cache_hint [%0], [%1], 16, %2;" ::"r"(((k & 1) ? s1 : s0) + k * 512), "l"(g + k * 512), "l"(POL_EF) : "memory");
    asm volatile("cp.async.mbarrier.arrive.shared::cta.b64 [%0];" ::"r"(bar) : "memory");
    __syncwarp();
    if (lane == 0) asm volatile("mbarrier.arrive.shared::cta.b64 _, [%0];" ::"r"(bar) : "memory");
}
__device__ __forceinline__ bool elect_one() {
    uint32_t p;
    asm volatile("{\n.reg .pred p;\nelect.sync _|p, 0xffffffff;\nselp.u32 %0, 1, 0, p;\n}" : "=r"(p));
    return p;
}
__device__ __forceinline__ void lds128(uint32_t addr, uint32_t& a, uint32_t& b, uint32_t& c, uint32_t& d) {
    asm volatile("ld.shared.v4.u32 {%0,%1,%2,%3}, [%4];" : "=r"(a), "=r"(b), "=r"(c), "=r"(d) : "r"(addr) : "memory");
}
__device__ __forceinline__ void lds128p(uint32_t addr, uint32_t on, uint32_t& a, uint32_t& b, uint32_t& c, uint32_t& d) {
    asm volatile("{\n.reg .pred p;\nsetp.ne.u32 p, %5, 0;\n@p ld.shared.v4.u32 {%0,%1,%2,%3}, [%4];\n}" : "+r"(a), "+r"(b), "+r"(c), "+r"(d) : "r"(addr), "r"(on) : "memory");
}
__device__ __forceinline__ void lds64(uint32_t addr, uint32_t& a, uint32_t& b) {
    asm volatile("ld.shared.v2.u32 {%0,%1}, [%2];" : "=r"(a), "=r"(b) : "r"(addr) : "memory");
}
__device__ __forceinline__ void ldsm4t(uint32_t addr, uint32_t (&a)[4]) {
    asm volatile("ldmatrix.sync.aligned.m8n8.x4.trans.shared.b16 {%0,%1,%2,%3}, [%4];" : "=r"(a[0]), "=r"(a[1]), "=r"(a[2]), "=r"(a[3]) : "r"(addr) : "memory");
}
__device__ __forceinline__ void mma16816(float (&c)[4], uint32_t a0, uint32_t a1, uint32_t a2, uint32_t a3, uint32_t b0, uint32_t b1) {
    asm("mma.sync.aligned.m16n8k16.row.col.f32.bf16.bf16.f32 {%0,%1,%2,%3}, {%4,%5,%6,%7}, {%8,%9}, {%0,%1,%2,%3};"
        : "+f"(c[0]), "+f"(c[1]), "+f"(c[2]), "+f"(c[3]) : "r"(a0), "r"(a1), "r"(a2), "r"(a3), "r"(b0), "r"(b1));
}
__device__ __forceinline__ void mma16816v(float (&c)[4], uint32_t a0, uint32_t a1, uint32_t a2, uint32_t a3, uint32_t b0, uint32_t b1) {
    asm volatile("mma.sync.aligned.m16n8k16.row.col.f32.bf16.bf16.f32 {%0,%1,%2,%3}, {%4,%5,%6,%7}, {%8,%9}, {%0,%1,%2,%3};"
        : "+f"(c[0]), "+f"(c[1]), "+f"(c[2]), "+f"(c[3]) : "r"(a0), "r"(a1), "r"(a2), "r"(a3), "r"(b0), "r"(b1));
}
__device__ __forceinline__ int xpos(int w) {
    const int seg = w / 40, r = w - 40 * seg;
    return 40 * seg + (r < 32 ? (r & 16) + 4 * (r & 3) + ((r >> 2) & 3) : 32 + 2 * (r & 3) + ((r >> 2) & 1));
}
#define NA_LD ""
#define NA_ST ""
__device__ __forceinline__ void st_pkt(uint4* p, uint32_t a, uint32_t b, uint32_t c, uint32_t d) {
    asm volatile("{\n.reg .b128 t;\n.reg .b64 lo, hi;\nmov.b64 lo, {%1,%2};\nmov.b64 hi, {%3,%4};\nmov.b128 t, {lo,hi};\nst.relaxed.gpu.global" NA_ST ".b128 [%0], t;\n}"
                 ::"l"(p), "r"(a), "r"(b), "r"(c), "r"(d) : "memory");
}
__device__ __forceinline__ void red_pkt(uint4* p, float a, float b, float c) {
    asm volatile("red.relaxed.gpu.global.add.v4.f32 [%0], {%1,%2,%3,%4};" ::"l"(p), "f"(a), "f"(b), "f"(c), "f"(1.0f) : "memory");
}
__device__ __forceinline__ void st_pktp(uint4* p, uint32_t a, uint32_t b, uint32_t c, uint32_t d, bool on) {
    asm volatile("{\n.reg .pred p;\n.reg .b128 t;\n.reg .b64 lo, hi;\nsetp.ne.u32 p, %5, 0;\nmov.b64 lo, {%1,%2};\nmov.b64 hi, {%3,%4};\nmov.b128 t, {lo,hi};\n"
                 "@p st.relaxed.gpu.global.b128 [%0], t;\n}" ::"l"(p), "r"(a), "r"(b), "r"(c), "r"(d), "r"((uint32_t)on) : "memory");
}
__device__ __forceinline__ void st_pktfp(uint4* p, float a, float b, float c, float d, uint32_t bit, bool on) {
    st_pktp(p, __float_as_uint(a), __float_as_uint(b), __float_as_uint(c), (__float_as_uint(d) & ~1u) | bit, on);
}
__device__ __forceinline__ uint4 ld_pkt(const uint4* p) {
    uint4 v;
    asm volatile("{\n.reg .b128 t;\n.reg .b64 lo, hi;\nld.relaxed.gpu.global" NA_LD ".b128 t, [%4];\nmov.b128 {lo,hi}, t;\nmov.b64 {%0,%1}, lo;\nmov.b64 {%2,%3}, hi;\n}"
                 : "=r"(v.x), "=r"(v.y), "=r"(v.z), "=r"(v.w) : "l"(p) : "memory");
    return v;
}
__device__ __forceinline__ bool all_odd(uint32_t a, uint32_t b, uint32_t c, uint32_t d) {
    uint32_t r;
    asm volatile("{\n.reg .pred p, q, t;\n.reg .b32 x;\nsetp.eq.b32 t, 0, 0;\nlop3.b32 x, %1, %2, %3, 0x80;\nlop3.and.b32 _|p, x, %4, 1, 0x80, t;\n"
                 "vote.sync.all.pred q, p, 0xffffffff;\nselp.u32 %0, 1, 0, q;\n}" : "=r"(r) : "r"(a), "r"(b), "r"(c), "r"(d));
    return r;
}
__device__ __forceinline__ bool any_odd(uint32_t a, uint32_t b, uint32_t c) {
    uint32_t r;
    asm volatile("{\n.reg .pred p, q, t;\n.reg .b32 x;\nsetp.eq.b32 t, 0, 0;\nlop3.b32 x, %1, %2, %3, 0xFE;\nlop3.and.b32 _|p, x, 1, 0, 0xC0, t;\n"
                 "vote.sync.any.pred q, p, 0xffffffff;\nselp.u32 %0, 1, 0, q;\n}" : "=r"(r) : "r"(a), "r"(b), "r"(c));
    return r;
}
__device__ __forceinline__ bool any_ne(uint32_t a, uint32_t b, uint32_t c) {
    uint32_t r;
    asm volatile("{\n.reg .pred p, q, t;\nsetp.eq.b32 t, 0, 0;\nlop3.and.b32 _|p, %1, %2, %3, 0x7E, t;\n"
                 "vote.sync.any.pred q, p, 0xffffffff;\nselp.u32 %0, 1, 0, q;\n}" : "=r"(r) : "r"(a), "r"(b), "r"(c));
    return r;
}
__device__ __forceinline__ uint2 ld_pkt2(const uint2* p) {
    unsigned long long v;
    asm volatile("ld.relaxed.gpu.global" NA_LD ".b64 %0, [%1];" : "=l"(v) : "l"(p) : "memory");
    return make_uint2((uint32_t)v, (uint32_t)(v >> 32));
}
__device__ __forceinline__ void st_pkt2(uint2* p, uint32_t a, uint32_t b) {
    asm volatile("st.relaxed.gpu.global" NA_ST ".b64 [%0], %1;" ::"l"(p), "l"((unsigned long long)a | ((unsigned long long)b << 32)) : "memory");
}
__device__ __forceinline__ float ex2(float x) { float y; asm("ex2.approx.ftz.f32 %0, %1;" : "=f"(y) : "f"(x)); return y; }
__device__ __forceinline__ float rcp(float x) { float y; asm("rcp.approx.ftz.f32 %0, %1;" : "=f"(y) : "f"(x)); return y; }
__device__ __forceinline__ uint32_t pack2(float lo, float hi) {
    uint32_t r; asm("cvt.rn.bf16x2.f32 %0, %1, %2;" : "=r"(r) : "f"(hi), "f"(lo)); return r;
}
__device__ __forceinline__ float bf_lo(uint32_t w) { return __uint_as_float(w << 16); }
__device__ __forceinline__ float bf_hi(uint32_t w) { return __uint_as_float(w & 0xffff0000u); }
__device__ __forceinline__ float bfr(float x) { return bf_lo(pack2(x, 0.f)); }
__device__ __forceinline__ float f_(uint32_t u) { return __uint_as_float(u); }

template <int SK, typename AddrF>
__device__ __forceinline__ void gemv15(float (&cc)[3][4], uint32_t (&pre)[6][4], AddrF ad, uint32_t px, uint32_t px2, float& sv, float so) {
    uint32_t x0[4], x1[4], a[3][4];
    asm volatile("ld.shared.v4.u32 {%0,%1,%2,%3}, [%20];\nld.shared.v4.u32 {%4,%5,%6,%7}, [%20+64];\n"
                 "ldmatrix.sync.aligned.m8n8.x4.trans.shared.b16 {%8,%9,%10,%11}, [%21];\n"
                 "ldmatrix.sync.aligned.m8n8.x4.trans.shared.b16 {%12,%13,%14,%15}, [%22];\n"
                 "ldmatrix.sync.aligned.m8n8.x4.trans.shared.b16 {%16,%17,%18,%19}, [%23];\nbar.warp.sync 0xffffffff;"
                 : "=r"(x0[0]), "=r"(x0[1]), "=r"(x0[2]), "=r"(x0[3]), "=r"(x1[0]), "=r"(x1[1]), "=r"(x1[2]), "=r"(x1[3]),
                   "=r"(a[0][0]), "=r"(a[0][1]), "=r"(a[0][2]), "=r"(a[0][3]), "=r"(a[1][0]), "=r"(a[1][1]), "=r"(a[1][2]), "=r"(a[1][3]),
                   "=r"(a[2][0]), "=r"(a[2][1]), "=r"(a[2][2]), "=r"(a[2][3])
                 : "r"(px), "r"(ad(0) + 2 * SK), "r"(ad(1) + 2 * SK), "r"(ad(2) + 2 * SK) : "memory");
    __syncwarp();
    sv += __shfl_xor_sync(0xffffffffu, so, 16);
#pragma unroll
    for (int i = 0; i < 3; i++) {
        cc[i][0] = cc[i][1] = cc[i][2] = cc[i][3] = 0.f;
        mma16816v(cc[i], pre[i][0], pre[i][1], pre[i][2], pre[i][3], x0[0], x0[1]);
    }
    sv += __shfl_xor_sync(0xffffffffu, sv, 8);
#pragma unroll
    for (int i = 0; i < 3; i++) {
        mma16816v(cc[i], pre[3 + i][0], pre[3 + i][1], pre[3 + i][2], pre[3 + i][3], x0[2], x0[3]);
        ldsm4t(ad(i) + 3 * SK, pre[i]);
    }
    lds64(px2, x0[0], x0[1]);
    __syncwarp();
    sv += __shfl_xor_sync(0xffffffffu, sv, 4);
#pragma unroll
    for (int i = 0; i < 3; i++) {
        mma16816v(cc[i], a[i][0], a[i][1], a[i][2], a[i][3], x1[0], x1[1]);
        ldsm4t(ad(i) + 4 * SK, pre[3 + i]);
    }
    __syncwarp();
    sv += __shfl_xor_sync(0xffffffffu, sv, 2);
#pragma unroll
    for (int i = 0; i < 3; i++) mma16816v(cc[i], pre[i][0], pre[i][1], pre[i][2], pre[i][3], x1[2], x1[3]);
    sv += __shfl_xor_sync(0xffffffffu, sv, 1);
#pragma unroll
    for (int i = 0; i < 3; i++) mma16816v(cc[i], pre[3 + i][0], pre[3 + i][1], pre[3 + i][2], pre[3 + i][3], x0[0], x0[1]);
}
__device__ __forceinline__ void gemv15r(float (&cc)[3][4], const uint32_t (&pre)[6][4], const uint32_t (&ext)[NQ][4], uint32_t px, uint32_t px2, float& sv, float so) {
    uint32_t x0[4], x1[4], x2[2];
    float cd[3][4];
    lds128(px, x0[0], x0[1], x0[2], x0[3]);
    lds128(px + 64, x1[0], x1[1], x1[2], x1[3]);
    lds64(px2, x2[0], x2[1]);
    sv += __shfl_xor_sync(0xffffffffu, so, 16);
#pragma unroll
    for (int i = 0; i < 3; i++) {
        cc[i][0] = cc[i][1] = cc[i][2] = cc[i][3] = cd[i][0] = cd[i][1] = cd[i][2] = cd[i][3] = 0.f;
        mma16816v(cc[i], pre[i][0], pre[i][1], pre[i][2], pre[i][3], x0[0], x0[1]);
        mma16816v(cd[i], pre[3 + i][0], pre[3 + i][1], pre[3 + i][2], pre[3 + i][3], x0[2], x0[3]);
    }
    sv += __shfl_xor_sync(0xffffffffu, sv, 8);
#pragma unroll
    for (int i = 0; i < 3; i++) {
        mma16816v(cc[i], ext[i][0], ext[i][1], ext[i][2], ext[i][3], x1[0], x1[1]);
        mma16816v(cd[i], ext[3 + i][0], ext[3 + i][1], ext[3 + i][2], ext[3 + i][3], x1[2], x1[3]);
    }
    sv += __shfl_xor_sync(0xffffffffu, sv, 4);
#pragma unroll
    for (int i = 0; i < 3; i++) mma16816v(cc[i], ext[6 + i][0], ext[6 + i][1], ext[6 + i][2], ext[6 + i][3], x2[0], x2[1]);
    sv += __shfl_xor_sync(0xffffffffu, sv, 2);
    sv += __shfl_xor_sync(0xffffffffu, sv, 1);
#pragma unroll
    for (int i = 0; i < 3; i++) { cc[i][0] += cd[i][0]; cc[i][1] += cd[i][1]; cc[i][2] += cd[i][2]; cc[i][3] += cd[i][3]; }
}

__device__ __forceinline__ float warp_max(float x) {
    int i = __float_as_int(x);
    i = __reduce_max_sync(0xffffffffu, i ^ ((i >> 31) & 0x7fffffff));
    return __int_as_float(i ^ ((i >> 31) & 0x7fffffff));
}
__device__ __forceinline__ void idle(uint32_t clk) {
    uint32_t t0, t;
    asm volatile("mov.u32 %0, %%clock;" : "=r"(t0) :: "memory");
    do asm volatile("mov.u32 %0, %%clock;" : "=r"(t) :: "memory"); while (t - t0 < clk);
}
__device__ __forceinline__ uint32_t now_ns() { uint32_t t; asm volatile("mov.u32 %0, %%globaltimer_lo;" : "=r"(t)); return t; }
__device__ __forceinline__ int opq(int x) { asm volatile("" : "+r"(x)); return x; }
__device__ __forceinline__ uint32_t opq(uint32_t x) { asm volatile("" : "+r"(x)); return x; }
__device__ __forceinline__ uint32_t pin(uint32_t x) { return __shfl_sync(0xffffffffu, x, threadIdx.x & 31); }
template <typename T> __device__ __forceinline__ T* pin(T* p) {
    const unsigned long long v = (unsigned long long)p;
    return (T*)((unsigned long long)pin((uint32_t)v) | (unsigned long long)pin((uint32_t)(v >> 32)) << 32);
}
template <typename T> __device__ __forceinline__ T* opq(T* p) { asm volatile("" : "+l"(p)); return p; }
__device__ __forceinline__ float4 lds4f(uint32_t a) { float4 v; asm volatile("ld.shared.v4.f32 {%0,%1,%2,%3}, [%4];" : "=f"(v.x), "=f"(v.y), "=f"(v.z), "=f"(v.w) : "r"(a) : "memory"); return v; }
__device__ __forceinline__ float2 lds2f(uint32_t a) { float2 v; asm volatile("ld.shared.v2.f32 {%0,%1}, [%2];" : "=f"(v.x), "=f"(v.y) : "r"(a) : "memory"); return v; }
__device__ __forceinline__ void ln_stats(uint32_t st, float& mean, float& inv) {
    const float4 a = lds4f(st), b = lds4f(st + 16), c = lds4f(st + 32), d = lds4f(st + 48);
    const float s2 = ((a.x + a.z) + (b.x + b.z)) + ((c.x + c.z) + (d.x + d.z));
    const float md = (((a.y + a.w) + (b.y + b.w)) + ((c.y + c.w) + (d.y + d.w))) * (1.0f / DM);
    const float var = fmaxf(s2 * (1.0f / DM) - md * md, 0.f);
    mean = bfr(md);
    asm("rsqrt.approx.ftz.f32 %0, %1;" : "=f"(inv) : "f"(var + 1e-5f));
}
__device__ __forceinline__ void sts32(uint32_t a, float v) { asm volatile("st.shared.f32 [%0], %1;" ::"r"(a), "f"(v) : "memory"); }
__device__ __forceinline__ void sts32p(uint32_t a, float v, uint32_t off) {
    asm volatile("{\n.reg .pred p;\nsetp.eq.u32 p, %2, 0;\n@p st.shared.f32 [%0], %1;\n}" ::"r"(a), "f"(v), "r"(off) : "memory");
}
__device__ __forceinline__ void sts128p(uint32_t a, float x, float y, float z, float w, uint32_t off) {
    asm volatile("{\n.reg .pred p;\nsetp.eq.u32 p, %5, 0;\n@p st.shared.v4.f32 [%0], {%1,%2,%3,%4};\n}" ::"r"(a), "f"(x), "f"(y), "f"(z), "f"(w), "r"(off) : "memory");
}
__device__ __forceinline__ void sts64(uint32_t a, float v, float w) { asm volatile("st.shared.v2.f32 [%0], {%1,%2};" ::"r"(a), "f"(v), "f"(w) : "memory"); }

__device__ __forceinline__ uint32_t prmt(uint32_t a, uint32_t b, uint32_t s) { uint32_t r; asm("prmt.b32 %0, %1, %2, %3;" : "=r"(r) : "r"(a), "r"(b), "r"(s)); return r; }
__device__ __forceinline__ uint32_t bmul2(uint32_t a, uint32_t b) { uint32_t r; asm("mul.rn.bf16x2 %0, %1, %2;" : "=r"(r) : "r"(a), "r"(b)); return r; }
__device__ __forceinline__ void sts128(uint32_t addr, uint32_t a, uint32_t b, uint32_t c, uint32_t d) {
    asm volatile("st.shared.v4.u32 [%0], {%1,%2,%3,%4};" ::"r"(addr), "r"(a), "r"(b), "r"(c), "r"(d) : "memory");
}
__device__ __forceinline__ uint4 ldg128(const uint4* p) {
    uint4 v;
    asm volatile("ld.volatile.global.v4.u32 {%0,%1,%2,%3}, [%4];" : "=r"(v.x), "=r"(v.y), "=r"(v.z), "=r"(v.w) : "l"(p) : "memory");
    return v;
}
__device__ __forceinline__ uint32_t lds32(uint32_t a) { uint32_t v; asm volatile("ld.shared.u32 %0, [%1];" : "=r"(v) : "r"(a) : "memory"); return v; }
__device__ __forceinline__ uint32_t lds16(uint32_t a) { unsigned short v; asm volatile("ld.shared.u16 %0, [%1];" : "=h"(v) : "r"(a) : "memory"); return v; }
__device__ __forceinline__ void unpack8(uint32_t la, uint32_t lb, uint32_t c, uint32_t (&w)[4]) {
    const uint32_t ha = c & 0x87878787u, hb = __funnelshift_l(c, c, 4) & 0x87878787u;
    w[0] = prmt(la, ha, 0x5140); w[1] = prmt(la, ha, 0x7362); w[2] = prmt(lb, hb, 0x5140); w[3] = prmt(lb, hb, 0x7362);
}
__device__ __forceinline__ uint32_t bdiff2(uint32_t y, uint32_t inv, uint32_t x) {
    uint32_t r;
    asm("{\n.reg .b32 n;\nneg.bf16x2 n, %3;\nfma.rn.bf16x2 %0, %1, %2, n;\n}" : "=r"(r) : "r"(y), "r"(inv), "r"(x));
    return r;
}
__device__ __forceinline__ uint32_t pack_scale(uint32_t tile, int lane, uint32_t inv_addr) {
    uint32_t m = 0;
#pragma unroll 1
    for (int k = 0; k < 12; k++) {
        uint32_t a, b, c, d;
        lds128(tile + k * 512 + lane * 16, a, b, c, d);
        asm("max.xorsign.abs.bf16x2 %0, %0, %1;" : "+r"(a) : "r"(b));
        asm("max.xorsign.abs.bf16x2 %0, %0, %1;" : "+r"(c) : "r"(d));
        asm("max.xorsign.abs.bf16x2 %0, %0, %1;" : "+r"(a) : "r"(c));
        asm("max.xorsign.abs.bf16x2 %0, %0, %1;" : "+r"(m) : "r"(a));
    }
    m = __reduce_max_sync(0xffffffffu, max(m & 0x7fffu, (m >> 16) & 0x7fffu));
    const uint32_t inv = (112u + min((m + 0x28u) >> 7, 141u)) * 0x00800080u;
    if (lane == 0) asm volatile("st.shared.u32 [%0], %1;" ::"r"(inv_addr), "r"(inv) : "memory");
    return inv;
}

#define K_OFF(i) ((uint32_t)((3 * ((g >> 1) + 4 * (g & 1)) + ((i) >> 1)) * 128 + ((t ^ ((3 * ((g >> 1) + 4 * (g & 1)) + ((i) >> 1)) & 7) ^ (((i) & 1) << 2)) << 4)))
#define V_OFF(i) ((uint32_t)((6 * t + (i)) * 128 + ((g ^ ((6 * t + (i)) & 7)) << 4)))
template <bool ISV, typename DST>
__device__ __forceinline__ void pack_tile(uint32_t tile, int tau, int nm, uint32_t inv, uint32_t xl, int lane, DST dst) {
    const int g = lane >> 2, t = lane & 3;
    const uint32_t scl = 254u * 0x00800080u - inv;
#pragma unroll 1
    for (int m = 0; m < nm; m++) {
        const int row = ISV ? 6 * t + 2 * m : 3 * ((g >> 1) + 4 * (g & 1)) + m;
        const uint32_t a0 = tile + row * 128 + (((ISV ? g : t) ^ (row & 7)) << 4), a1 = ISV ? (a0 ^ 16) + 128 : a0 ^ 64;
        uint32_t l[8], cw[4], ck = 0, cd = 0;
#pragma unroll
        for (int r = 0; r < 4; r++) {
            uint32_t w0, w1, w2, w3;
            lds128(((r & 1) ? a1 : a0) + (r >> 1) * 3072, w0, w1, w2, w3);
            const uint32_t y0 = bmul2(w0, scl), y1 = bmul2(w1, scl), y2 = bmul2(w2, scl), y3 = bmul2(w3, scl);
            cd |= bdiff2(y0, inv, w0) | bdiff2(y1, inv, w1);
            cd |= bdiff2(y2, inv, w2) | bdiff2(y3, inv, w3);
            const uint32_t ha = prmt(y0, y1, 0x7531), hb = prmt(y2, y3, 0x7531);
            l[2 * r] = prmt(y0, y1, 0x6420); l[2 * r + 1] = prmt(y2, y3, 0x6420);
            asm("lop3.b32 %0, %1, 0x87878787, %2, 0xe2;" : "=r"(cw[r]) : "r"(ha), "r"(__funnelshift_r(hb, hb, 4)));
            ck |= ha | hb;
        }
        const uint32_t bad = __ballot_sync(0xffffffffu, (ck & 0x78787878u) | cd);
        if (bad) {
            const int src = __ffs(bad) - 1;
            const uint32_t b0 = __shfl_sync(0xffffffffu, a0, src), b1 = __shfl_sync(0xffffffffu, a1, src), n0 = lds32(xl);
            const uint32_t ax = ((lane & 8) ? b1 : b0) + (lane >> 4) * 3072 + 2 * (lane & 7), x = lds16(ax), y = bmul2(x, scl);
            const bool out = (y & 0x7800u) | bdiff2(y, inv, x);
            const uint32_t n = n0 + __popc(__ballot_sync(0xffffffffu, out) << (31 - lane)) - 1;
            if (out) {
                asm volatile("st.shared.u16 [%0], %1;" ::"r"(ax), "h"((unsigned short)0) : "memory");
                if (n < XCAP) sts32(xl + 16 + 4 * n, f_(x << 16 | tau << 12 | src << 7 | m << 5 | lane));
            }
            if (lane == 31) sts32(xl, f_(n + 1));
            __syncwarp();
            if (n0 <= XCAP) { m--; continue; }
        }
        uint32_t d[3] = {a0, a1, a0 + 3072};
        dst(m, d);
        sts128(d[0], l[0], l[1], l[2], l[3]);
        sts128(d[1], l[4], l[5], l[6], l[7]);
        sts128(d[2], cw[0], cw[1], cw[2], cw[3]);
    }
}

struct Maps { CUtensorMap k, v, wq, wo, w1, w3, w2, vr; const void* vp; const void* kp; uint32_t zero; };
#define RT_SEL (wu >= 6 ? RT_MASK3 : (wu & 1) ? RT_MASK2 : RT_MASK)
#define PFK 5
#define Q_AT 3
#define WO_T0 33000
#define K5D 250
#define PK_AT 6

__device__ __forceinline__ void load_ffn(const Maps& maps, int b, uint32_t dst, uint32_t bar) {
    const bool gu = b < NG;
    mbar_expect_tx(bar, gu ? 61440 : 49152);
    tma3d(dst, gu ? (b < NG / 2 ? &maps.w1 : &maps.w3) : &maps.w2, gu ? 48 * (b & (NG / 2 - 1)) : 16 * (b - DN0), 0, 0, bar, FFN_POL);
}

__device__ __forceinline__ void load_wo(const Maps& maps, uint32_t dst, int h, int c, uint32_t bar, int nbox, int keep) {
#pragma unroll 1
    for (int i = 0; i < nbox; i++) {
        if (!(i & 1)) mbar_expect_tx(bar + 4 * i, i + 1 < nbox ? 20480 : 10240);
        tma3d(dst + i * 10240, &maps.wo, 0, 5 * c, h * DH + 32 * i, bar + 4 * (i & 6), POL_EF);
        if (i == keep)
            asm volatile("cp.async.bulk.prefetch.tensor.3d.L2.global.L2::cache_hint [%0, {%1, %2, %3}], %4;"
                         ::"l"(&maps.wo), "r"(0), "r"(5 * c), "r"(h * DH + 32 * i), "l"(POL_EN) : "memory");
    }
}

__global__ void __launch_bounds__(NT, 1)
decode_kernel(const __grid_constant__ Maps maps, const __nv_bfloat16* __restrict__ x_in, __nv_bfloat16* __restrict__ out) {
    extern __shared__ __align__(1024) unsigned char smem[];
    const int tid = threadIdx.x, warp = tid >> 5, lane = tid & 31;
    const int wu = __shfl_sync(0xffffffffu, tid >> 5, 0);
    const int b = blockIdx.x, h = b >> 2, c = b & 3;
    const uint32_t sb = smem_u32(smem);
    const uint32_t qbar = sb + SM_BAR + 16 * 8, fbar = qbar + 8, wbar = qbar + 16;
    uint32_t* xs32 = reinterpret_cast<uint32_t*>(smem + SM_XS);
    float* rr = reinterpret_cast<float*>(smem + SM_R);
    float* misc = reinterpret_cast<float*>(smem + SM_MISC);

    PROF_T(0);
    {
        uint2 xv = make_uint2(0u, 0u);
        const uint32_t t_start = now_ns();
        if (elect_one()) {
            const uint32_t rb = sb + SM_BAR + wu * 16, xb = sb + SM_XBAR + wu * 8;
            mbar_init(rb, 1); mbar_init(rb + 8, 1); mbar_init(xb, 1);
            if (wu == 0) mbar_init(qbar, 1);
            asm volatile("fence.mbarrier_init.release.cluster;" ::: "memory");
            const int row = (h * SK + (SK - WIN) + c * 1024 + wu * 128) * 3;
            const uint32_t ring = sb + SM_RING + wu * 2 * TILE;
#pragma unroll
            for (int n = 0; n < 3; n++) {
                const uint32_t bar = ((IN_S1 >> n) & 1) ? rb + 8 : ((IN_S0 >> n) & 1) ? rb : xb;
                mbar_expect_tx(bar, TILE);
                tma2d(((IN_S1 >> n) & 1) ? ring + TILE : ((IN_S0 >> n) & 1) ? ring : sb + SM_B + wu * TILE, &maps.k, 0, row + 48 * n, bar, POL_EF);
                if (n == 0 && wu == 0) {
                    mbar_expect_tx(qbar, 61440);
                    tma3d(sb + SM_Q, &maps.wq, 0, 160 * c, 3 * h, qbar, POL_EF);
                }
            }
            if (wu == 1) {
                mbar_init(fbar, 1);
#pragma unroll
                for (int i = 0; i < 3; i++) mbar_init(wbar + 8 * i, 1);
                asm volatile("fence.mbarrier_init.release.cluster;" ::: "memory");
            }
            if (wu >= 2) {
                const CUtensorMap* mp = wu == 2 ? &maps.v : wu == 3 ? &maps.wo : wu == 4 ? &maps.w1 : wu == 5 ? &maps.w3 : wu == 6 ? &maps.w2 : &maps.vr;
                asm volatile("prefetch.tensormap [%0];" ::"l"(mp) : "memory");
            }
        }
        if (tid < 160) asm volatile("ld.global.nc.v2.u32 {%0,%1}, [%2];" : "=r"(xv.x), "=r"(xv.y) : "l"(x_in + 4 * tid) : "memory");
        if (tid == 96) { misc[2] = 0.f; misc[3] = 0.f; }
        if (lane == 1) *reinterpret_cast<uint2*>(smem + SM_XL + warp * XSTR) = make_uint2(0u, t_start + WO_T0);
        if (tid >= 128 && tid < 148) {
            const uint32_t v = tid < 138 ? ONES : 0u;
            reinterpret_cast<uint4*>(smem + SM_ONE)[tid - 128] = make_uint4(v, v, v, v);
        }
        if (tid < 160) { xs32[xpos(2 * tid)] = xv.x; xs32[xpos(2 * tid + 1)] = xv.y; }
        __syncthreads();
        PROF_T(14);
        if (b == 0 && tid >= 232) asm volatile("st.relaxed.gpu.global.u32 [%0], %1;" ::"l"(g_scr.ticket + tid - 232), "r"(0) : "memory");
        if (tid == 64 || (tid == 65 && b < 216 - NCTA)) st_pkt(&g_scr.acc[1][acc_pos(b + NCTA * (tid - 64))], 0, 0, 0, 0);
    }

    uint32_t kq[NQ][4];
    const float SC = 0.07216878364870322f * 1.4426950408889634f;

#pragma unroll 1
    for (int ph = 0; ph < 3; ph++) {
        const int layer = ph >> 1;
        const uint32_t tag = layer + 1;
        PROF_T(1 + layer * 16);
        if (ph) {
        {
            const int tl = opq(tid), warp = tl >> 5, lane = tl & 31, g = lane >> 2, t = lane & 3, mat = lane >> 3, r8 = lane & 7;
            const int kh = warp >> 2, mg = warp & 3;
            uint32_t aq[3];
#pragma unroll
            for (int i = 0; i < 3; i++) {
                const int ch = 6 * mg + 2 * i + (mat & 1);
                aq[i] = sb + SM_Q + (80 * kh + (mat >> 1) * 8 + r8) * 128 + (ch >> 3) * 20480 + (((ch & 7) ^ r8) << 4);
            }
#define PF_K5 if (layer == 1 && PFK) tile_keep(&maps.k, (h * SK + (SK - WIN) + c * 1024 + wu * 128 + PFK * 16) * 3);
            uint2 xv = make_uint2(0u, 0u);
            mbar_wait(qbar, 0);
            uint32_t pre[6][4];
#pragma unroll
            for (int n = 0; n < 6; n++) ldsm4t(aq[n % 3] + (n / 3) * 2048, pre[n]);
            if (layer == 1) {
                __syncthreads();
                if (elect_one()) {
                    const uint32_t bar = sb + SM_BAR + wu * 16;
                    asm volatile("mbarrier.expect_tx.relaxed.cta.shared::cta.b64 [%0], 1536;" ::"r"(bar) : "memory");
#pragma unroll
                    for (int k = 0; k < 3; k++)
                        tma2d(sb + SM_Q + v1_pos(3 * wu + k), &maps.vr, 0, (h * SK + (SK - WIN) + c * 1024 + wu * 128) / 2 + 8 + 2 * k, bar, POL_EF);
                }
            }
            const uint32_t pm = opq(g == 1 ? sb + SM_ONE : sb + SM_XS + 160 * (2 * c + kh) + 16 * t), pm2 = opq(pm + 128 - (g == 1 ? 0 : 8 * t));
            const uint32_t dq = opq(sb + SM_R + 8 * (kh * 192 + 48 * mg + g)), ds = opq(sb + SM_ST + 8 * warp + (lane < 16 ? 4 : 0));
            const bool wr = t == 0, ws = (lane & 15) == 0, lo = lane < 16;
            if (wu < 5) {
                const int p0 = xpos(2 * tl), p1 = xpos(2 * tl + 1);
                if (layer == 1) {
                    uint4 v;
                    for (int it = 0; it < SPIN_CAP; it++) { v = ld_pkt(&g_scr.ay[tl]); if (__all_sync(0xffffffffu, v.w == 1)) break; }
                    xv = make_uint2(v.x, v.y);
                    xs32[p0] = xv.x; xs32[p1] = xv.y;
                } else xv = make_uint2(xs32[p0], xs32[p1]);
            }
            if (layer) PC(24);
            __syncthreads();
            PF_K5
            if (layer) PC(25);
            PROF_T(13 + layer * 16);
            const float e0 = bf_lo(xv.x), e1 = bf_hi(xv.x), e2 = bf_lo(xv.y), e3 = bf_hi(xv.y);
            const float s1 = (e0 + e1) + (e2 + e3), s2 = (e0 * e0 + e1 * e1) + (e2 * e2 + e3 * e3);
            float sv = lo ? s1 : s2, cc[3][4];
            gemv15<2048>(cc, pre, [&](int i) { return aq[i]; }, pm, pm2, sv, lo ? s2 : s1);
            if (wr) {
#pragma unroll
                for (int i = 0; i < 3; i++) { sts64(dq + 128 * i, cc[i][0], cc[i][1]); sts64(dq + 128 * i + 64, cc[i][2], cc[i][3]); }
            }
            if (ws) sts32(ds, sv);
        }
        const uint32_t pa = opq(sb + SM_R + 32 * opq(tid)), st = opq(sb + SM_ST);
        uint4* const pq = opq(&g_scr.hx[b * 48 + opq(tid)]);
        if (layer) PC(26);
        __syncthreads();
        if (layer) PC(27);
        PROF_T(33 + layer * 16);
        if (wu < 2) {
            float mean, inv;
            ln_stats(st, mean, inv);
            const float4 a0 = lds4f(pa), a1 = lds4f(pa + 16), b0 = lds4f(pa + 1536), b1 = lds4f(pa + 1552);
            const float q0 = (a0.x + b0.x) - mean * (a0.y + b0.y), q1 = (a0.z + b0.z) - mean * (a0.w + b0.w);
            const float q2 = (a1.x + b1.x) - mean * (a1.y + b1.y), q3 = (a1.z + b1.z) - mean * (a1.w + b1.w);
            st_pktfp(pq, q0, q1, q2, q3, 1, tid < 48);
        }
        if (layer == 1 && tid >= 192 && tid < 194 && b < 108) st_pkt(&g_scr.acc[0][acc_pos(2 * b + opq(tid) - 192)], 0, 0, 0, 0);
        }
        if (layer) PC(28);
        if (layer == 1 && (wu & 2)) {
            idle(K5D);
            tile_load(sb + SM_Q + c_slot(wu), &maps.k, (h * SK + (SK - WIN) + c * 1024 + wu * 128 + 5 * 16) * 3, sb + SM_XBAR + wu * 8, 0, 0);
        }

        float sc0 = -INFINITY, sc1 = -INFINITY, sc2 = 0.f, sc3 = 0.f, mw;
        uint32_t pk0, pk1;
        float acc[3][4];
        {
            const uint32_t ring = sb + SM_RING + wu * 2 * TILE, rb = sb + SM_BAR + wu * 16;
            const uint32_t xtile = sb + SM_Q + c_slot(wu), xb = sb + SM_XBAR + wu * 8;
#define V_SEQ(n) ((int)(SEQ1 >> (4 * (n))) & 7)
#define SLOT1(n) (((IN_S1 >> (n)) & 1) ? ring + TILE : ((IN_S0 >> (n)) & 1) ? ring : sb + SM_B + wu * TILE)
#define BAR1(n) (((IN_S1 >> (n)) & 1) ? rb + 8 : ((IN_S0 >> (n)) & 1) ? rb : xb)
#define PAR1(n) ((PARITY1 >> (n)) & 1)
#define PAR2(n) ((PARITY2 >> (n)) & 1)
            const int row0 = (h * SK + (SK - WIN) + c * 1024 + wu * 128) * 3;
            auto issue1 = [&](int n, uint32_t dep, bool vph = false) {
                const CUtensorMap* mp = n < 8 ? &maps.k : &maps.v;
                const int tl = V_SEQ(n), row = row0 + tl * 48;
                const uint32_t dst = SLOT1(n), bar = BAR1(n);
                if (vph && wu < L1R && tl == 7 - (wu & 1)) {
                    tile_load_l1(dst, maps.vp, row, bar, opq(tid) & 31);
                    return;
                }
                tile_load(dst, mp, row, bar, dep, maps.zero);
                if ((RT_SEL >> (tl + (n & 8))) & 1) {
                    if (n != V0_AT + 1) tile_keep(mp, row);
                    else if ((opq(tid) & 31) < 8)
                        asm volatile("cp.async.bulk.prefetch.L2.global.L2::cache_hint [%0], 256, %1;"
                                     ::"l"(static_cast<const char*>(maps.vp) + (size_t)(row + 4 + 6 * (opq(tid) & 31)) * 128), "l"(POL_EN) : "memory");
                }
            };
            auto refill1 = [&](int s, uint32_t dep, bool vph = false) { issue1(s + (!vph || s < V0_AT ? 3 : 2), dep, vph); };
#define LANE_IDS const int tl = opq(tid), lane = tl & 31, g = lane >> 2, t = lane & 3; (void)tl; (void)lane; (void)g; (void)t;
            const uint32_t xl = sb + SM_XL + wu * XSTR;
            if (layer == 0) {
#pragma unroll 1
                for (int s = ph ? Q_AT : 0; s < (ph ? 5 : Q_AT); s++) {
                    LANE_IDS
                    const uint32_t tile = SLOT1(s);
                    mbar_wait(BAR1(s), PAR1(s));
                    const uint32_t scl = s == 0 ? pack_scale(tile, lane, xl + 8) : lds32(xl + 8);
                    pack_tile<false>(tile, s, 3, scl, xl, lane, [](int, uint32_t (&)[3]) {});
#pragma unroll
                    for (int n = 0; n < 5; n++) {
                        if (s == n) {
#pragma unroll
                            for (int m = 0; m < 3; m++) {
                                const uint32_t a = tile + K_OFF(2 * m);
                                lds128(a, kq[9 * n + 3 * m][0], kq[9 * n + 3 * m][1], kq[9 * n + 3 * m][2], kq[9 * n + 3 * m][3]);
                                lds128(a ^ 64, kq[9 * n + 3 * m + 1][0], kq[9 * n + 3 * m + 1][1], kq[9 * n + 3 * m + 1][2], kq[9 * n + 3 * m + 1][3]);
                                lds128(a + 3072, kq[9 * n + 3 * m + 2][0], kq[9 * n + 3 * m + 2][1], kq[9 * n + 3 * m + 2][2], kq[9 * n + 3 * m + 2][3]);
                            }
                        }
                    }
                    __syncwarp();
                    refill1(s, lds32(tile));
                }
                if (!ph) continue;
            }
            {
                if (wu < 2) {
                    const int tl = min(opq(tid), 47);
                    const int w = 2 * tl;
                    const uint32_t pos = opq(sb + SM_QS + 4 * (((w >> 2) & 3) * 24 + 2 * (w >> 4) + ((w >> 1) & 1)));
                    uint4 v[4];
                    float mean, inv;
                    ln_stats(opq(sb + SM_ST), mean, inv);
                    for (int it = 0; it < SPIN_CAP; it++) {
#pragma unroll
                        for (int k = 0; k < 4; k++) v[k] = ld_pkt(&g_scr.hx[(h * 4 + k) * 48 + tl]);
                        if (all_odd(v[0].w, v[1].w, v[2].w, v[3].w)) break;
                    }
                    sts32(pos, f_(pack2(inv * ((f_(v[0].x) + f_(v[1].x)) + (f_(v[2].x) + f_(v[3].x))), inv * ((f_(v[0].y) + f_(v[1].y)) + (f_(v[2].y) + f_(v[3].y))))));
                    sts32(pos + 48, f_(pack2(inv * ((f_(v[0].z) + f_(v[1].z)) + (f_(v[2].z) + f_(v[3].z))), inv * ((f_(v[0].w) + f_(v[1].w)) + (f_(v[2].w) + f_(v[3].w))))));
                }
            }
            if (layer) PC(29);
            __syncthreads();
            if (layer) PC(30);
            PROF_T(2 + layer * 16);
#define V1_REST(p) ((p) < 6 ? sb + SM_Q + v1_pos(3 * wu + ((p) >> 1)) + 256 * ((p) & 1) : ((sb + SM_R + wu * 784 + 127) & ~127u) - 1536 + 256 * (p))
#define V1_LOAD(bar) if (elect_one()) tma2d(V1_REST(6), &maps.vr, 0, row0 / 6 + 14, bar, POL_EF);
#define V1_EXPECT(bar) { if ((opq(tid) & 31) == 0) asm volatile("mbarrier.expect_tx.relaxed.cta.shared::cta.b64 [%0], 512;" ::"r"(bar) : "memory"); }
            if (layer == 1 && !(wu & 2)) tile_load(xtile, &maps.k, row0 + 5 * 48, xb, 0, 0);
            if (layer == 1 && wu >= 4) idle(STAG);
            {
                uint32_t qf[12];
                int t;
                {
                    const int lane = opq(tid) & 31;
                    t = lane & 3;
                    const uint32_t qa = sb + SM_QS + (2 * t + ((lane >> 2) & 1)) * 48;
#pragma unroll
                    for (int i = 0; i < 3; i++) lds128(qa + 16 * i, qf[4 * i], qf[4 * i + 1], qf[4 * i + 2], qf[4 * i + 3]);
                }
                const uint32_t sq = lds32(xl + 8) - 64u * 0x00800080u;
#pragma unroll
                for (int i = 0; i < 12; i++) qf[i] = bmul2(qf[i], sq);
#define KR_STEP(tau, m) \
                    _Pragma("unroll") for (int i = 2 * (m); i < 2 * (m) + 2; i++) { \
                        const int q0 = 9 * tau + 3 * (i >> 1), r = i & 1; \
                        uint32_t w[4]; \
                        unpack8(kq[q0][2 * r], kq[q0][2 * r + 1], kq[q0 + 2][r], w); \
                        mma16816(cA, w[0], w[1], w[2], w[3], qf[2 * i], qf[2 * i + 1]); \
                        unpack8(kq[q0 + 1][2 * r], kq[q0 + 1][2 * r + 1], kq[q0 + 2][2 + r], w); \
                        mma16816(cB, w[0], w[1], w[2], w[3], qf[2 * i], qf[2 * i + 1]); \
                    }
#define KR_BEGIN float cA[4] = {0.f, 0.f, 0.f, 0.f}, cB[4] = {0.f, 0.f, 0.f, 0.f};
#define KR_END(tau) \
                    const float sA = (cA[0] + cA[3]) * 18446744073709551616.f, sB = (cB[0] + cB[3]) * 18446744073709551616.f; \
                    if (t == (tau & 3)) { if (tau < 4) { sc0 = sA; sc1 = sB; } else { sc2 = sA; sc3 = sB; } }
#define KR_SCORES(tau) { KR_BEGIN KR_STEP(tau, 0) KR_STEP(tau, 1) KR_STEP(tau, 2) KR_END(tau) }
                uint32_t va[3];
                {
                    const int lane = opq(tid) & 31, g = lane >> 2, t = lane & 3;
#pragma unroll
                    for (int i = 0; i < 3; i++) va[i] = ring + V_OFF(2 * i);
                }
#define V_STG(n) _Pragma("unroll") for (int j = 3 * (n); j < 3 * (n) + 3; j++) { \
                    const int i = (j % 12) >> 1; \
                    lds128p(((i & 1) ? (va[i >> 1] ^ 16) + 128 : va[i >> 1]) + (j / 12) * TILE + (j & 1) * 3072, layer, kq[j][0], kq[j][1], kq[j][2], kq[j][3]); }
                uint32_t dep = 0;
                {
                    KR_BEGIN
                    KR_STEP(0, 0) V_STG(0) KR_STEP(0, 1) V_STG(1) KR_STEP(0, 2) V_STG(2)
                    KR_END(0)
                }
                {
                    KR_BEGIN
                    KR_STEP(1, 0) V_STG(3)
                    __syncwarp();
                    dep = lds32(ring);
                    if (layer == 1) tile_load(ring, &maps.k, row0 + 6 * 48, rb, dep, maps.zero);
                    KR_STEP(1, 1) V_STG(4) KR_STEP(1, 2) V_STG(5)
                    KR_END(1)
                }
                {
                    KR_BEGIN
                    KR_STEP(2, 0) V_STG(6) KR_STEP(2, 1) V_STG(7)
                    __syncwarp();
                    dep = lds32(ring + TILE);
                    KR_STEP(2, 2)
                    if (layer == 1) {
                        V1_EXPECT(rb + 8)
                        tile_load(ring + TILE, &maps.k, row0 + 7 * 48, rb + 8, dep, maps.zero);
                        V1_LOAD(rb + 8)
                    }
                    KR_END(2)
                }
#pragma unroll 1
                for (int s = 5; s < 8; s++) {
                    {
                        LANE_IDS
                        const uint32_t tile = !layer ? SLOT1(s) : s == 5 ? xtile : ring + (s - 6) * TILE, tb = !layer ? BAR1(s) : s == 5 ? xb : rb + (s - 6) * 8;
                        const float ur = f_((318u << 23) - (lds32(xl + 8) << 16));
                        mbar_wait(tb, layer ? PAR2(s - 5) : PAR1(s));
                        if (layer) PROF_T(29 + s);
                        float cA[4] = {0.f, 0.f, 0.f, 0.f}, cB[4] = {0.f, 0.f, 0.f, 0.f};
#pragma unroll
                        for (int i = 0; i < 6; i++) {
                            uint32_t a0, a1, a2, a3;
                            lds128(tile + K_OFF(i), a0, a1, a2, a3);
                            mma16816(cA, a0, a1, a2, a3, qf[2 * i], qf[2 * i + 1]);
                            lds128(tile + K_OFF(i) + 3072, a0, a1, a2, a3);
                            mma16816(cB, a0, a1, a2, a3, qf[2 * i], qf[2 * i + 1]);
                        }
                        __syncwarp();
                        const uint32_t last = lds32(tile);
                        if (layer) tile_load(tile, &maps.v, row0 + (s - 2) * 48, tb, last, maps.zero);
                        else refill1(s, last);
                        if (t == (s & 3)) { sc2 = (cA[0] + cA[3]) * ur; sc3 = (cB[0] + cB[3]) * ur; }
                    }
                    if (s == 5) KR_SCORES(3)
                    if (s == 6) {
                        KR_SCORES(4)
                        const int lane = opq(tid) & 31;
                        const uint32_t nx = min(lds32(xl), (uint32_t)XCAP);
#pragma unroll 1
                        for (uint32_t n = 0; n < nx; n++) {
                            const uint32_t id = lds32(xl + 16 + 4 * n);
                            const uint32_t qo = 96 * ((id >> 7) & 3) + 48 * ((id >> 1) & 1) + 16 * ((id >> 5) & 3) + (id & 12) + 2 * (id & 1);
                            const float cr = bf_hi(id) * f_(lds16(sb + SM_QS + qo) << 16);
                            const int d = (int)(16 * ((id >> 9) & 7) + 4 * ((id >> 12) & 3) + ((id >> 13) & 2) + ((id >> 4) & 1) + ((id >> 8) & 128)) - 4 * lane;
                            if (d == 0) sc0 += cr;
                            if (d == 1) sc1 += cr;
                            if (d == 2) sc2 += cr;
                            if (d == 3) sc3 += cr;
                        }
                    }
                }
#undef KR_SCORES
#undef KR_STEP
#undef KR_BEGIN
#undef KR_END
#undef V_STG
                {
                    LANE_IDS
                    if (lds32(xl) > XCAP || !__all_sync(0xffffffffu, (fabsf(sc0) + fabsf(sc1)) + (fabsf(sc2) + fabsf(sc3)) < INFINITY)) {
                        const uint32_t qa = sb + SM_QS + (2 * t + (g & 1)) * 48;
#pragma unroll
                        for (int i = 0; i < 3; i++) lds128(qa + 16 * i, qf[4 * i], qf[4 * i + 1], qf[4 * i + 2], qf[4 * i + 3]);
                        const uint4* kg = reinterpret_cast<const uint4*>(static_cast<const char*>(maps.kp) + (size_t)row0 * 128) + ((g >> 1) + 4 * (g & 1)) * 24 + t;
#pragma unroll 1
                        for (int s = 0; s < 8; s++) {
                            float cA[4] = {0.f, 0.f, 0.f, 0.f}, cB[4] = {0.f, 0.f, 0.f, 0.f};
#pragma unroll
                            for (int i = 0; i < 6; i++) {
                                uint4 u = ldg128(kg + s * 384 + 4 * i);
                                mma16816v(cA, u.x, u.y, u.z, u.w, qf[2 * i], qf[2 * i + 1]);
                                u = ldg128(kg + s * 384 + 4 * i + 192);
                                mma16816v(cB, u.x, u.y, u.z, u.w, qf[2 * i], qf[2 * i + 1]);
                            }
                            if (t == s) { sc0 = cA[0] + cA[3]; sc1 = cB[0] + cB[3]; }
                            if (t + 4 == s) { sc2 = cA[0] + cA[3]; sc3 = cB[0] + cB[3]; }
                        }
                    }
                }
            }
            mw = warp_max(fmaxf(fmaxf(sc0, sc1), fmaxf(sc2, sc3)));
            pk0 = pack2(ex2((sc0 - mw) * SC), ex2((sc1 - mw) * SC));
            pk1 = pack2(ex2((sc2 - mw) * SC), ex2((sc3 - mw) * SC));
            sc2 = (bf_lo(pk0) + bf_hi(pk0)) + (bf_lo(pk1) + bf_hi(pk1));
            sc2 = (float)__reduce_add_sync(0xffffffffu, __float2uint_rn(sc2 * 16777216.f)) * (1.0f / 16777216.f);
            if ((opq(tid) & 31) == 0) st_pkt2(&g_scr.mx[h * 32 + c * 8 + wu], __float_as_uint(mw), (__float_as_uint(sc2) & ~3u) | tag);
            auto head_factor = [&]() {
                const int lane = opq(tid) & 31;
                int it = 0;
                while (!__all_sync(0xffffffffu, (__float_as_uint(sc1) & 3u) == tag) && ++it < SPIN_CAP) {
                    const uint2 mv = ld_pkt2(&g_scr.mx[h * 32 + lane]); sc0 = f_(mv.x); sc1 = f_(mv.y);
                }
                const float e = ex2((sc0 - warp_max(sc0)) * SC);
                const uint32_t d = __reduce_add_sync(0xffffffffu, __float2uint_rn(sc1 * e * 524288.f));
                sc3 = __shfl_sync(0xffffffffu, e, c * 8 + wu) * 524288.f * rcp((float)d);
            };
#pragma unroll
            for (int s = 0; s < 3; s++) { acc[s][0] = acc[s][1] = acc[s][2] = acc[s][3] = 0.f; }
#define P_CONSTS \
                const uint32_t sel0 = g == 0 ? 0x4410u : (g == 1 ? 0x1044u : 0x4444u); \
                const uint32_t sel1 = g == 2 ? 0x4410u : (g == 3 ? 0x1044u : 0x4444u); \
                const int src00 = 4 * (t < 2 ? 4 * t : 4 * (t - 2) + 1);
#define P_FRAGS(tau) \
                const uint32_t pk = ((tau) & 4) ? pk1 : pk0; \
                const uint32_t w0 = __shfl_sync(0xffffffffu, pk, src00 + ((tau) & 3)); \
                const uint32_t w1 = __shfl_sync(0xffffffffu, pk, src00 + ((tau) & 3) + 8); \
                uint32_t pb[4][2]; \
                _Pragma("unroll") for (int j = 0; j < 4; j++) { \
                    const uint32_t src = ((j & 1) ? w1 : w0) >> ((j >> 1) * 16); \
                    pb[j][0] = __byte_perm(src, 0, sel0); pb[j][1] = __byte_perm(src, 0, sel1); \
                }
            if (layer == 0) {
#pragma unroll 1
                for (int s = 8; s < 16; s++) {
                    LANE_IDS
                    P_CONSTS
                    if (s == 13) { const uint2 mv = ld_pkt2(&g_scr.mx[h * 32 + lane]); sc0 = f_(mv.x); sc1 = f_(mv.y); }
                    P_FRAGS(V_SEQ(s))
                    mbar_wait(BAR1(s), PAR1(s));
                    const uint32_t tile = SLOT1(s);
#pragma unroll
                    for (int j = 0; j < 4; j++) {
#pragma unroll
                        for (int u = 0; u < 3; u++) {
                            uint32_t a0, a1, a2, a3;
                            lds128(tile + (j >> 1) * 3072 + V_OFF(3 * (j & 1) + u), a0, a1, a2, a3);
                            mma16816(acc[u], a0, a1, a2, a3, pb[j][0], pb[j][1]);

                        }
                    }
                    __syncwarp();
                    if (s < V0_AT || (s > V0_AT + 1 && s < 14)) refill1(s, lds32(tile), true);
                    if (s == V0_AT || s == V0_AT + 1) {
                        {
                            const uint32_t ar = sb + SM_R + wu * 784 + 32 * g + 16 * t;
                            if (t < 2) {
#pragma unroll
                                for (int u = 0; u < 3; u++) sts128(ar + 256 * u, __float_as_uint(acc[u][0]), __float_as_uint(acc[u][1]), __float_as_uint(acc[u][2]), __float_as_uint(acc[u][3]));
                            }
                        }
                        const uint32_t scl = s == V0_AT ? pack_scale(tile, lane, xl + 12) : lds32(xl + 12);
                        pack_tile<true>(tile, s + 8 - V0_AT, V0_AT + 3 - s, scl, xl, lane, [&](int m, uint32_t (&d)[3]) {
                            if (s != V0_AT && m == 0) {
#pragma unroll
                                for (int k = 0; k < 3; k++) d[k] = ring + 3072 + V_OFF(2 * k + 1);
                            }
                        });
                        if (s != V0_AT) {
                            lds128(tile + V_OFF(2), kq[45][0], kq[45][1], kq[45][2], kq[45][3]);
                            lds128(tile + V_OFF(3), kq[46][0], kq[46][1], kq[46][2], kq[46][3]);
                            lds128(tile + V_OFF(2) + 3072, kq[47][0], kq[47][1], kq[47][2], kq[47][3]);
                            __syncwarp();
                            issue1(V0_AT + 3, lds32(tile));
                        }
                        const int ln = opq(tid) & 31;
                        const uint32_t ar = sb + SM_R + wu * 784 + 8 * (ln & 28) + 16 * (ln & 1);
#pragma unroll
                        for (int u = 0; u < 3; u++) {
                            uint32_t a0, a1, a2, a3;
                            lds128(ar + 256 * u, a0, a1, a2, a3);
                            acc[u][0] = f_(a0); acc[u][1] = f_(a1); acc[u][2] = f_(a2); acc[u][3] = f_(a3);
                        }
                    }
                    if (s == 13) head_factor();
                    if (s >= 14 && elect_one()) {
                        if (atomicAdd(reinterpret_cast<unsigned*>(misc + 3), 1u) == 14u && (int)(now_ns() - lds32(xl + 4)) >= 0) {
                            PROF_X(47);
                            load_wo(maps, sb + SM_B, h, c, wbar, 6, WO_KEEP);
                            atomicAdd(reinterpret_cast<unsigned*>(misc + 3), 256u);
                        }
                    }
                }
            } else {
                LANE_IDS
                P_CONSTS
#pragma unroll
                for (int k = 0; k < 4; k++) lds128(V1_REST(t + 4 * (k >> 1)) + 16 * g + 128 * (k & 1), kq[36 + k][0], kq[36 + k][1], kq[36 + k][2], kq[36 + k][3]);
#pragma unroll 1
                for (int i = 3; i < 8; i++) {
                    const uint32_t tile = i > 3 ? ring + (i & 1) * TILE : xtile, tb = i > 3 ? rb + (i & 1) * 8 : xb;
                    if (i == 6) { const uint2 mv = ld_pkt2(&g_scr.mx[h * 32 + lane]); sc0 = f_(mv.x); sc1 = f_(mv.y); }
                    if (i == 7) head_factor();
                    if (i == PK_AT) {
                uint32_t nx, nk, ik, iv;
                lds128(xl, nx, nk, ik, iv);
                if (nx <= XCAP) {
                    const uint32_t pks = bmul2(pk0, iv);
#pragma unroll
                    for (int s = 0; s < 2; s++) {
                        const uint32_t pk1 = 0, pk0 = pks;
                        P_FRAGS(s)
#pragma unroll
                        for (int j = 0; j < 4; j++) {
#pragma unroll
                            for (int u = 0; u < 3; u++) {
                                const int i = 3 * (j & 1) + u, m = i >> 1, r = i & 1, hf = j >> 1;
                                if (s == 1 && m == 2) continue;
                                const int ql = s == 0 ? 4 * m + 2 * hf : m == 0 ? 3 + 4 * hf : 45 + hf, qc = s == 0 ? 4 * m + 1 : m == 0 ? 11 : 47;
                                uint32_t w[4];
                                unpack8(kq[ql][2 * r], kq[ql][2 * r + 1], kq[qc][2 * hf + r], w);
                                mma16816(acc[u], w[0], w[1], w[2], w[3], pb[j][0], pb[j][1]);
                            }
                        }
                    }
#pragma unroll 1
                    for (uint32_t n = 0; n < nx; n++) {
                        const uint32_t id = lds32(xl + 16 + 4 * n);
                        const int i = ((id >> 4) & 6) + ((id >> 3) & 1), key = ((id >> 6) & 6) + (i >= 3);
                        const uint32_t pw = __shfl_sync(0xffffffffu, pk0, 8 * (key & 3) + (key & 4) + ((id >> 12) & 3));
                        const float cr = bf_hi(id) * ((id & 16) ? bf_hi(pw) : bf_lo(pw));
                        const int d = (int)(64 * ((id >> 9) & 7) + 4 * (id & 4) + 4 * (i >= 3 ? i - 3 : i) + (id & 3) + ((~id >> 5) & 1024)) - 16 * lane;
#pragma unroll
                        for (int k = 0; k < 12; k++) if (d == k) acc[k >> 2][k & 3] += cr;
                    }
                } else {
                    const uint4* vg = reinterpret_cast<const uint4*>(static_cast<const char*>(maps.vp) + (size_t)row0 * 128) + 48 * t + g;
#pragma unroll 1
                    for (int s = 0; s < 2; s++) {
                        P_FRAGS(s)
#pragma unroll
                        for (int j = 0; j < 4; j++) {
#pragma unroll
                            for (int u = 0; u < 3; u++) {
                                if (s == 1 && (j & 1) && u) continue;
                                const uint4 w = ldg128(vg + 384 * s + 192 * (j >> 1) + 24 * (j & 1) + 8 * u);
                                mma16816v(acc[u], w.x, w.y, w.z, w.w, pb[j][0], pb[j][1]);
                            }
                        }
                    }
                }
#pragma unroll
                for (int s = 2; s > 0; s--) {
                    P_FRAGS(s)
#pragma unroll
                    for (int j = 0; j < 4; j++) {
#pragma unroll
                        for (int u = 0; u < 3; u++) {
                            if (s == 1 && !((j & 1) && u)) continue;
                            const int k = s == 2 ? 12 + 2 * (3 * (j & 1) + u) + (j >> 1) : 35 + (j >> 1) * 2 + u;
                            mma16816(acc[u], kq[k][0], kq[k][1], kq[k][2], kq[k][3], pb[j][0], pb[j][1]);
                        }
                    }
                }
                    }
                    P_FRAGS(i)
                    mbar_wait(tb, PAR2(i));
                    PROF_T(34 + i);
#pragma unroll
                    for (int k = 0; k < 6; k++) {
                        const uint32_t a = tile + V_OFF(k);
                        lds128(a, kq[24 + k][0], kq[24 + k][1], kq[24 + k][2], kq[24 + k][3]);
                        lds128(a + 3072, kq[30 + k][0], kq[30 + k][1], kq[30 + k][2], kq[30 + k][3]);
                    }
#pragma unroll
                    for (int j = 0; j < 4; j++) {
#pragma unroll
                        for (int u = 0; u < 3; u++) {
                            const int k = 24 + 6 * (j >> 1) + 3 * (j & 1) + u;
                            mma16816(acc[u], kq[k][0], kq[k][1], kq[k][2], kq[k][3], pb[j][0], pb[j][1]);
                        }
                    }
                    __syncwarp();
                    if (wu < L1R && i == 5 - (wu & 1)) tile_load_l1(tile, maps.vp, row0 + (i + 2) * 48, tb, lane);
                    else if (i == 4 || i == 5) tile_load(tile, &maps.v, row0 + (i + 2) * 48, tb, lds32(tile), maps.zero);
                    if (i == WO_AT1 && HAS_FFN && elect_one()) {
                        if (atomicAdd(reinterpret_cast<unsigned*>(misc + 2), 1u) == 7u) {
                            PROF_X(63);
                            load_wo(maps, sb + SM_Q, h, c, wbar, KEEP4 && __float_as_uint(misc[1]) >= DN0 ? 5 : 6, -1);
                        }
                    }
                }
            }
#undef P_FRAGS
#undef P_CONSTS
#undef LANE_IDS
        }
        PROF_T(3 + layer * 16);
        PC(layer * 32 + 1);

        {
            const int lane = opq(tid) & 31;
            const uint32_t a = sb + SM_R + wu * 784 + 8 * (lane & 28) + 16 * (lane & 1);
#pragma unroll
            for (int u = 0; u < 3; u++) sts128p(a + 256 * u, acc[u][0] * sc3, acc[u][1] * sc3, acc[u][2] * sc3, acc[u][3] * sc3, lane & 2);
        }
        const uint32_t role1 = layer ? lds32(sb + SM_MISC + 4) : DN0 + NDN;
        const uint32_t pc = opq(sb + SM_R + 16 * opq(tid));
        uint4* const px0 = opq(&g_scr.hx[b * 48 + opq(tid)]);
        __syncthreads();
        PROF_T(4 + layer * 16);
        PC(layer * 32 + 2);
        float4 o = make_float4(0.f, 0.f, 0.f, 0.f);
        if (wu < 2) {
            float4 v[8];
#pragma unroll
            for (int w = 0; w < 8; w++) v[w] = lds4f(pc + w * 784);
            o.x = ((v[0].x + v[1].x) + (v[2].x + v[3].x)) + ((v[4].x + v[5].x) + (v[6].x + v[7].x));
            o.y = ((v[0].y + v[1].y) + (v[2].y + v[3].y)) + ((v[4].y + v[5].y) + (v[6].y + v[7].y));
            o.z = ((v[0].z + v[1].z) + (v[2].z + v[3].z)) + ((v[4].z + v[5].z) + (v[6].z + v[7].z));
            o.w = ((v[0].w + v[1].w) + (v[2].w + v[3].w)) + ((v[4].w + v[5].w) + (v[6].w + v[7].w));
            o.w = f_(__float_as_uint(o.w) & ~1u);
            st_pktp(px0, __float_as_uint(o.x), __float_as_uint(o.y), __float_as_uint(o.z), __float_as_uint(o.w), threadIdx.x < 48);
        }
        uint32_t ticket = 0;
        if (layer == 0 && tid == 224)
            asm volatile("atom.relaxed.gpu.global.inc.u32 %0, [%1], 0x7fffffff;" : "=r"(ticket) : "l"(g_scr.ticket + 8 + (b >> 3)) : "memory");
        if (layer == 0 && tid == 224 && lds32(sb + SM_MISC + 12) < 256u) {
            int it = 0;
            while ((int)(now_ns() - lds32(sb + SM_XL + 4)) < 0 && ++it < SPIN_CAP) {}
            PROF_X(47);
            load_wo(maps, sb + SM_B, h, c, wbar, 6, WO_KEEP);
        }
        uint32_t pr;
        uint4* pacc;
        {
            const int tid = opq(threadIdx.x), warp = tid >> 5, lane = tid & 31, g = lane >> 2, t = lane & 3, mat = lane >> 3, r8 = lane & 7;
            const int kg = warp >> 1, mg = warp & 1;
            const bool wo2 = role1 < DN0 + NDN;
            const uint32_t aw2 = 40960 + (wo2 && KEEP4 && role1 >= DN0 && kg >= 2 ? SM_B - SM_Q : 0);
            uint32_t aw[5];
#pragma unroll
            for (int i = 0; i < 5; i++) {
                const uint32_t lin = ((mat >> 1) * 8 + r8) * 320 + 64 * i + 32 * mg + 16 * (mat & 1);
                aw[i] = sb + (wo2 ? SM_Q : SM_B) + 5120 * kg + (lin ^ ((lin >> 3) & 48));
            }
#define CXE 0
            const uint32_t ao = pin(sb + SM_OS + 96 * kg + 16 * t), dw = pin(sb + SM_R + 16 * (16 * mg + g) + 4 * kg);
            pr = pin(sb + SM_R + 48 * tid); pacc = pin(&g_scr.acc[layer][acc_pos(54 * c + tid)]);
            const int w = 2 * min(tid, 47);
            const uint32_t d0 = pin(sb + SM_OS + 4 * (24 * ((w >> 3) & 3) + ((w >> 2) & 1) + (w < 64 ? 4 * (w & 3) + 2 * (w >> 5) : 16 + 2 * (w & 3))));
            const uint32_t d1 = pin(d0 + (w < 64 ? 16 : 8));
            const uint4* pp[3];
#pragma unroll
            for (int k = 0; k < 3; k++) pp[k] = pin(&g_scr.hx[(h * 4 + ((c + 1 + k) & 3)) * 48 + min(tid, 47)]);
            uint4 v3[3];
#pragma unroll
            for (int k = 0; k < 3; k++) v3[k] = make_uint4(0u, 0u, 0u, 1u);
            if ((PRE1 & 8) && layer) {
#pragma unroll
                for (int ks = 0; ks < 3; ks++) {
                    mbar_wait(wbar + 8 * ks, wo2);
#pragma unroll
                    for (int i = 0; i < 5; i++) ldsm4t(aw[i] + (ks == 2 ? aw2 : 20480 * ks), kq[3 * i + ks]);
                    if (ks == CXE && wu < 2) {
#pragma unroll
                        for (int k = 0; k < 3; k++) v3[k] = ld_pkt(pp[k]);
                    }
                }
                PROF_T(50);
            }
            if (wu < 2) {
                for (int it = 0; any_odd(v3[0].w, v3[1].w, v3[2].w) && it < SPIN_CAP; it++) {
#pragma unroll
                    for (int k = 0; k < 3; k++) v3[k] = ld_pkt(pp[k]);
                }
                o.x = (o.x + f_(v3[0].x)) + (f_(v3[1].x) + f_(v3[2].x)); o.y = (o.y + f_(v3[0].y)) + (f_(v3[1].y) + f_(v3[2].y));
                o.z = (o.z + f_(v3[0].z)) + (f_(v3[1].z) + f_(v3[2].z)); o.w = (o.w + f_(v3[0].w)) + (f_(v3[1].w) + f_(v3[2].w));
                sts32p(d0, f_(pack2(o.x, o.y)), tid >= 48);
                sts32p(d1, f_(pack2(o.z, o.w)), tid >= 48);
            }
            PC(layer * 32 + 3);
            __syncthreads();
            PROF_T(5 + layer * 16);
            PC(layer * 32 + 5);
            if (tid == 224 && layer == 0) {
                if (ticket >= 6 + ((b >> 3) & 1)) ticket = DN0 + NDN;
                else asm volatile("atom.relaxed.gpu.global.inc.u32 %0, [%1], 0x7fffffff;" : "=r"(ticket) : "l"(g_scr.ticket) : "memory");
            }
            uint32_t ob[6];
            lds128(ao, ob[0], ob[1], ob[2], ob[3]);
            lds64(ao + 64 - 8 * t, ob[4], ob[5]);
            float cc[5][4];
#pragma unroll
            for (int i = 0; i < 5; i++) cc[i][0] = cc[i][1] = cc[i][2] = cc[i][3] = 0.f;
            if ((PRE1 & 8) && layer) {
#pragma unroll
                for (int ks = 0; ks < 3; ks++) {
#pragma unroll
                    for (int i = 0; i < 5; i++) mma16816(cc[i], kq[3 * i + ks][0], kq[3 * i + ks][1], kq[3 * i + ks][2], kq[3 * i + ks][3], ob[2 * ks], ob[2 * ks + 1]);
                }
            } else {
#pragma unroll
                for (int ks = 0; ks < 3; ks++) {
                    mbar_wait(wbar + 8 * ks, wo2);
                    if (ks == 2) { PC(layer * 32 + 4); PROF_T(48 + layer * 2); }
                    uint32_t a[5][4];
#pragma unroll
                    for (int i = 0; i < 5; i++) ldsm4t(aw[i] + (ks == 2 ? aw2 : 20480 * ks), a[i]);
#pragma unroll
                    for (int i = 0; i < 5; i++) mma16816(cc[i], a[i][0], a[i][1], a[i][2], a[i][3], ob[2 * ks], ob[2 * ks + 1]);
                }
            }
            if (t == 0) {
#pragma unroll
                for (int i = 0; i < 5; i++) { sts32(dw + 512 * i, cc[i][0]); sts32(dw + 512 * i + 128, cc[i][2]); }
            }
        }
        PC(layer * 32 + 6);
        __syncthreads();
        PROF_T(6 + layer * 16);
        PC(layer * 32 + 7);
        if (tid < 54) {
            const float4 v0 = lds4f(pr), v1 = lds4f(pr + 16), v2 = lds4f(pr + 32);
            const float y0 = (v0.x + v0.y) + (v0.z + v0.w), y1 = (v1.x + v1.y) + (v1.z + v1.w), y2 = (v2.x + v2.y) + (v2.z + v2.w);
            red_pkt(pacc, y0, tid == 53 ? 0.f : y1, tid == 53 ? 0.f : y2);
        }
        if (tid == 224 && layer == 0) {
            misc[1] = __uint_as_float(ticket);
            if (ticket < DN0 + NDN && (ticket < NG || !DNTH)) load_ffn(maps, ticket, sb + SM_B, fbar);
        }
        PROF_T(7 + layer * 16);
        PC(layer * 32 + 8);
        __syncthreads();
        const int role = (int)__float_as_uint(misc[1]);
        PC(layer * 32 + 9);
        const uint32_t fbase = sb + SM_B;
        const uint32_t DONE32 = 0x42000000u;
        if (role < NG) {
            const int tid = opq(threadIdx.x), warp = tid >> 5, lane = tid & 31, g = lane >> 2, t = lane & 3, mat = lane >> 3, r8 = lane & 7;
            const uint32_t ag = fbase + (80 * warp + (mat >> 1) * 8 + r8) * 96 + (((mat & 1) ^ (r8 >> 2)) << 4);
            constexpr int GI = 32, GK = 16 * 96;
            const bool on = (g & 1) == (t >> 1), isx = on && g < 2;
            const uint32_t pm = opq(isx ? sb + SM_XS + 160 * warp + 16 * t : sb + (on ? SM_ONE : SM_ZERO)), pm2 = opq(pm + 128 - (isx ? 8 * t : 0));
            const uint32_t dg = opq(sb + SM_R + 4 * (2 * (warp * 48 + g) + t)), ds = opq(sb + SM_ST + 8 * warp + (lane < 16 ? 4 : 0));
            const bool ws = (lane & 15) == 0, lo = lane < 16;
            uint32_t pre[6][4];
            float s1 = 0.f, s2 = 0.f;
            {
                bool hx = false;
                int it = 0;
                const int cq = wu >> 1, odd = wu & 1, r = min(26 * odd + lane, 26 + 27 * odd), c0 = 3 * r - 80 * odd, k0 = 160 * cq + 3 * r;
                const uint4* px = &g_scr.acc[layer][acc_pos(54 * cq + r)];
                const bool act = lane <= 26 + odd;
                const bool on0 = act && c0 >= 0, on1 = act && c0 + 1 >= 0 && c0 + 1 < 80, on2 = act && c0 + 2 < 80;
                const uint32_t w0 = sb + SM_XS + 4 * xpos(k0 >> 1), w1 = sb + SM_XS + 4 * xpos(min((k0 >> 1) + 1, DM / 2 - 1));
                const uint32_t e0 = w0 + 2 * (k0 & 1), e1 = (k0 & 1) ? w1 : w0 + 2, e2 = w1 + 2 * (k0 & 1);
                auto sts16 = [](uint32_t a, uint32_t x, bool on) {
                    asm volatile("{\n.reg .pred p;\nsetp.ne.u32 p, %2, 0;\n@p st.shared.u16 [%0], %1;\n}" ::"r"(a), "h"((unsigned short)x), "r"((uint32_t)on) : "memory");
                };
                const float x0 = on0 ? f_(lds16(e0) << 16) : 0.f, x1 = on1 ? f_(lds16(e1) << 16) : 0.f, x2 = on2 ? f_(lds16(e2) << 16) : 0.f;
                auto take_x = [&](const uint4 v) {
                    if (__all_sync(0xffffffffu, v.w == DONE32)) {
                        hx = true;
                        const uint32_t a = pack2(f_(v.x), f_(v.y)), p = pack2(x0 + bf_lo(a), x1 + bf_hi(a)), q = pack2(x2 + bfr(f_(v.z)), 0.f);
                        sts16(e0, p, on0); sts16(e1, p >> 16, on1); sts16(e2, q, on2);
                        const float y0 = on0 ? bf_lo(p) : 0.f, y1 = on1 ? bf_hi(p) : 0.f, y2 = on2 ? bf_lo(q) : 0.f;
                        s1 = y0 + (y1 + y2); s2 = y0 * y0 + (y1 * y1 + y2 * y2);
                    }
                };
                auto try_x = [&]() { take_x(ld_pkt(px)); };
                while (!mbar_test(fbar, 0) && ++it < SPIN_CAP) { if (!hx) try_x(); }
                uint4 v0 = make_uint4(0u, 0u, 0u, 0u);
                if ((PRE1 & 4) && !hx) v0 = ld_pkt(px);
#pragma unroll
                for (int n = 0; n < 6; n++) ldsm4t(ag + (n % 3) * GI + (n / 3) * GK, pre[n]);
                if ((PRE1 & 1) && layer) {
#pragma unroll
                    for (int n = 6; n < 15; n++) ldsm4t(ag + (n % 3) * GI + (n / 3) * GK, kq[n - 6]);
                }
                if ((PRE1 & 4) && !hx) take_x(v0);
                PC(layer * 32 + 10);
                for (; !hx && it < SPIN_CAP; it++) try_x();
                PC(layer * 32 + 11);
            __syncwarp();
            PC(layer * 32 + 12);
            PROF_T(9 + layer * 16);
            float sv = lo ? s1 : s2, cc[3][4];
            if ((PRE1 & 1) && layer) gemv15r(cc, pre, kq, pm, pm2, sv, lo ? s2 : s1);
            else gemv15<GK>(cc, pre, [&](int i) { return ag + i * GI; }, pm, pm2, sv, lo ? s2 : s1);
#pragma unroll
            for (int i = 0; i < 3; i++) { sts32p(dg + 128 * i, cc[i][0] + cc[i][3], t & 2); sts32p(dg + 128 * i + 64, cc[i][1] + cc[i][2], t & 2); }
            if (ws) sts32(ds, sv);
            const uint32_t pg = opq(sb + SM_R + 8 * (24 * warp + (lane < 24 ? lane : 0))), st = opq(sb + SM_ST);
            uint4* const ph = opq(lane < 24 && lane % 6 == 0 ? &g_scr.ah[role * 8 + 4 * warp + lane / 6] : nullptr);
            PC(layer * 32 + 13);
            __syncthreads();
            PC(layer * 32 + 14);
            PROF_T(43 + layer * 16);
            if (wu < 2) {
                float mean, inv;
                ln_stats(st, mean, inv);
                float2 v[8];
#pragma unroll
                for (int w = 0; w < 8; w++) v[w] = lds2f(pg + w * 384);
                const float gx = ((v[0].x + v[1].x) + (v[2].x + v[3].x)) + ((v[4].x + v[5].x) + (v[6].x + v[7].x));
                const float gs = ((v[0].y + v[1].y) + (v[2].y + v[3].y)) + ((v[4].y + v[5].y) + (v[6].y + v[7].y));
                float ga = inv * (gx - mean * gs);
                if (role < NG / 2) { ga = bfr(ga); ga *= rcp(1.0f + ex2(-1.4426950408889634f * ga)); }
                const uint32_t wd = pack2(ga, __shfl_down_sync(0xffffffffu, ga, 1));
                const uint32_t wa = __shfl_down_sync(0xffffffffu, wd, 2), wb = __shfl_down_sync(0xffffffffu, wd, 4);
                if (ph) st_pkt(ph, wd, wa, wb, tag);
            }
            if (HOLD & 2) __syncthreads();
            }
            PROF_T(10 + layer * 16);
            PC(layer * 32 + 15);
        } else if (role < DN0 + NDN) {
            const int j = role - DN0;
            const int tid = opq(threadIdx.x), warp = tid >> 5, lane = tid & 31, g = lane >> 2, t = lane & 3, mat = lane >> 3, r8 = lane & 7;
            float xres = 0.f;
            uint32_t xr0 = 0, xr1 = 0;
            if (wu == 0) {
                const int col = 16 * j + (lane & 15), cc = col / 160, r = col - 160 * cc, e = r % 3;
                const uint4* px = &g_scr.acc[layer][acc_pos(54 * cc + r / 3)];
                const float x0 = __bfloat162float(reinterpret_cast<const __nv_bfloat16*>(xs32)[2 * xpos(col >> 1) + (col & 1)]);
                uint4 v;
                int it = 0;
                bool ld = DNTH && layer == 0;
                do {
                    v = ld_pkt(px);
                    if (ld && f_(__shfl_sync(0xffffffffu, v.w, 0)) >= (float)DNTH) { ld = false; if (lane == 0) load_ffn(maps, role, sb + SM_B, fbar); }
                } while (!__all_sync(0xffffffffu, v.w == DONE32) && ++it < SPIN_CAP);
                if (ld && lane == 0) load_ffn(maps, role, sb + SM_B, fbar);
                xres = x0 + bfr(f_(e == 0 ? v.x : (e == 1 ? v.y : v.z)));
                const int p4 = 4 * (lane & 3);
                xr0 = pack2(__shfl_sync(0xffffffffu, xres, p4), __shfl_sync(0xffffffffu, xres, p4 + 1));
                xr1 = pack2(__shfl_sync(0xffffffffu, xres, p4 + 2), __shfl_sync(0xffffffffu, xres, p4 + 3));
            }
            PC(layer * 32 + 17);
            PROF_T(9 + layer * 16);
            const uint32_t ad = fbase + (192 * warp + (mat >> 1) * 8 + r8) * 32 + (((mat & 1) ^ (r8 >> 2)) << 4);
            uint32_t* hs = reinterpret_cast<uint32_t*>(rr) + warp * 96;
            uint32_t pre[NPRE][4];
            {
                uint32_t pos[3];
#pragma unroll
                for (int i = 0; i < 3; i++) { const int w = 3 * lane + i; pos[i] = pin(sb + SM_R + 384 * warp + 4 * ((w & ~15) + 4 * (w & 3) + ((w >> 2) & 1) + ((w >> 2) & 2))); }
                uint4 v = make_uint4(0u, 0u, 0u, 0u), u = v;
                if (layer == 0) { v = ld_pkt(&g_scr.ah[tid]); u = ld_pkt(&g_scr.ah[256 + tid]); }
                mbar_wait(fbar, 0);
#pragma unroll
                for (int n = 0; n < NPRE; n++) ldsm4t(ad + n * 512, pre[n]);
                if ((PRE1 & 2) && layer) {
#pragma unroll
                    for (int n = NPRE; n < 12; n++) ldsm4t(ad + n * 512, kq[12 + n]);
                }
                PC(layer * 32 + 18);
                int it = 0;
                for (; any_ne(v.w, u.w, tag) && it < SPIN_CAP; it++) { v = ld_pkt(&g_scr.ah[tid]); u = ld_pkt(&g_scr.ah[256 + tid]); }
                PC(layer * 32 + 19);
                sts32(pos[0], f_(bmul2(v.x, u.x))); sts32(pos[1], f_(bmul2(v.y, u.y))); sts32(pos[2], f_(bmul2(v.z, u.z)));
            __syncwarp();
            PROF_T(11 + layer * 16);
            PC(layer * 32 + 20);
            float ca[4] = {0.f, 0.f, 0.f, 0.f}, cb[4] = {0.f, 0.f, 0.f, 0.f};
            if ((PRE1 & 2) && layer) {
                float cc[4] = {0.f, 0.f, 0.f, 0.f}, cd[4] = {0.f, 0.f, 0.f, 0.f};
#pragma unroll
                for (int jj = 0; jj < 6; jj++) {
                    const uint4 hv = *reinterpret_cast<const uint4*>(hs + 16 * jj + 4 * t);
                    const uint32_t (&f0)[4] = 2 * jj < NPRE ? pre[2 * jj < NPRE ? 2 * jj : 0] : kq[12 + 2 * jj];
                    const uint32_t (&f1)[4] = 2 * jj + 1 < NPRE ? pre[2 * jj + 1 < NPRE ? 2 * jj + 1 : 0] : kq[13 + 2 * jj];
                    if (jj & 1) { mma16816(cc, f0[0], f0[1], f0[2], f0[3], hv.x, hv.y); mma16816(cd, f1[0], f1[1], f1[2], f1[3], hv.z, hv.w); }
                    else { mma16816(ca, f0[0], f0[1], f0[2], f0[3], hv.x, hv.y); mma16816(cb, f1[0], f1[1], f1[2], f1[3], hv.z, hv.w); }
                }
#pragma unroll
                for (int e = 0; e < 4; e++) { ca[e] += cc[e]; cb[e] += cd[e]; }
            } else {
#pragma unroll
                for (int jj = 0; jj < 6; jj++) {
                    const uint4 hv = *reinterpret_cast<const uint4*>(hs + 16 * jj + 4 * t);
                    uint32_t a[4];
                    if (2 * jj < NPRE) { a[0] = pre[2 * jj][0]; a[1] = pre[2 * jj][1]; a[2] = pre[2 * jj][2]; a[3] = pre[2 * jj][3]; }
                    else ldsm4t(ad + 2 * jj * 512, a);
                    mma16816(ca, a[0], a[1], a[2], a[3], hv.x, hv.y);
                    if (2 * jj + 1 < NPRE) { a[0] = pre[2 * jj + 1][0]; a[1] = pre[2 * jj + 1][1]; a[2] = pre[2 * jj + 1][2]; a[3] = pre[2 * jj + 1][3]; }
                    else ldsm4t(ad + (2 * jj + 1) * 512, a);
                    mma16816(cb, a[0], a[1], a[2], a[3], hv.z, hv.w);
                }
            }
            if (t == 0) { rr[768 + warp * 16 + g] = ca[0] + cb[0]; rr[768 + warp * 16 + 8 + g] = ca[2] + cb[2]; }
            const uint32_t pd = opq(sb + SM_R + 3072 + 16 * (lane & 3));
            uint4* const py = opq(&g_scr.ay[j * 4 + lane]);
            uint2* const po = opq(reinterpret_cast<uint2*>(out + 16 * j) + lane);
            PC(layer * 32 + 21);
            __syncthreads();
            PC(layer * 32 + 22);
            if (wu == 0) {
                float4 p[8];
#pragma unroll
                for (int w = 0; w < 8; w++) p[w] = lds4f(pd + 64 * w);
                const uint32_t y0 = pack2(((p[0].x + p[1].x) + (p[2].x + p[3].x)) + ((p[4].x + p[5].x) + (p[6].x + p[7].x)),
                                          ((p[0].y + p[1].y) + (p[2].y + p[3].y)) + ((p[4].y + p[5].y) + (p[6].y + p[7].y)));
                const uint32_t y1 = pack2(((p[0].z + p[1].z) + (p[2].z + p[3].z)) + ((p[4].z + p[5].z) + (p[6].z + p[7].z)),
                                          ((p[0].w + p[1].w) + (p[2].w + p[3].w)) + ((p[4].w + p[5].w) + (p[6].w + p[7].w)));
                uint32_t wd, wn;
                asm("add.rn.bf16x2 %0, %1, %2;" : "=r"(wd) : "r"(xr0), "r"(y0));
                asm("add.rn.bf16x2 %0, %1, %2;" : "=r"(wn) : "r"(xr1), "r"(y1));
                asm volatile("{\n.reg .pred p;\nsetp.ne.u32 p, %3, 0;\n@p st.global.v2.u32 [%0], {%1,%2};\n}" ::"l"(po), "r"(wd), "r"(wn), "r"((uint32_t)(layer && tid < 4)) : "memory");
                st_pktp(py, wd, wn, 0, tag, tid < 4);
            }
            if (HOLD & 1) __syncthreads();
            }
            PROF_T(12 + layer * 16);
            PC(layer * 32 + 23);
        }
    }
}

typedef CUresult (*EncodeFn)(CUtensorMap*, CUtensorMapDataType, cuuint32_t, void*, const cuuint64_t*, const cuuint64_t*, const cuuint32_t*,
                             const cuuint32_t*, CUtensorMapInterleave, CUtensorMapSwizzle, CUtensorMapL2promotion, CUtensorMapFloatOOBfill);

void make_map(EncodeFn enc, CUtensorMap* m, const void* base, int rank, uint64_t d0, uint64_t d1, uint64_t d2, uint64_t s1, uint64_t s2,
              uint32_t b0, uint32_t b1, uint32_t b2, CUtensorMapSwizzle sw, CUtensorMapL2promotion pr = CU_TENSOR_MAP_L2_PROMOTION_NONE) {
    cuuint64_t dims[3] = {d0, d1, d2};
    cuuint64_t strides[2] = {s1, s2};
    cuuint32_t box[3] = {b0, b1, b2};
    cuuint32_t es[3] = {1, 1, 1};
    enc(m, CU_TENSOR_MAP_DATA_TYPE_BFLOAT16, rank, const_cast<void*>(base), dims, strides, box, es, CU_TENSOR_MAP_INTERLEAVE_NONE, sw,
        pr, CU_TENSOR_MAP_FLOAT_OOB_FILL_NONE);
}

}

extern "C" void kernel_launch(void* const* d_in, const int* in_sizes, int n_in, void* d_out, int out_size) {
    (void)in_sizes; (void)n_in; (void)out_size;
    static EncodeFn enc = nullptr;
    if (!enc) {
        void* fn = nullptr;
        cudaDriverEntryPointQueryResult qr;
        cudaGetDriverEntryPoint("cuTensorMapEncodeTiled", &fn, cudaEnableDefault, &qr);
        enc = reinterpret_cast<EncodeFn>(fn);
        cudaFuncSetAttribute(decode_kernel, cudaFuncAttributeMaxDynamicSharedMemorySize, SM_TOTAL);
    }
    Maps maps;
    make_map(enc, &maps.k, d_in[1], 2, 64, (uint64_t)NH * SK * 3, 1, 128, 0, 64, 48, 1, CU_TENSOR_MAP_SWIZZLE_128B);
    make_map(enc, &maps.v, d_in[2], 2, 64, (uint64_t)NH * SK * 3, 1, 128, 0, 64, 48, 1, CU_TENSOR_MAP_SWIZZLE_128B);
    make_map(enc, &maps.wq, d_in[3], 3, 64, DM, NH * DH / 64, NH * DH * 2, 128, 64, 160, 3, CU_TENSOR_MAP_SWIZZLE_128B);
    make_map(enc, &maps.wo, d_in[4], 3, 32, DM / 32, NH * DH, 64, DM * 2, 32, 5, 32, CU_TENSOR_MAP_SWIZZLE_64B);
    make_map(enc, &maps.vr, (const char*)d_in[2] + 512, 2, 128, (uint64_t)NH * SK / 2, 1, 768, 0, 128, 2, 1, CU_TENSOR_MAP_SWIZZLE_NONE);
    constexpr int GW = 48;
    make_map(enc, &maps.w1, d_in[6], 3, FF, 160, 4, FF * 2, 160 * FF * 2, GW, 160, 4, CU_TENSOR_MAP_SWIZZLE_NONE);
    make_map(enc, &maps.w3, d_in[7], 3, FF, 160, 4, FF * 2, 160 * FF * 2, GW, 160, 4, CU_TENSOR_MAP_SWIZZLE_NONE);
    make_map(enc, &maps.w2, d_in[8], 3, DM, 256, 6, DM * 2, 256 * DM * 2, 16, 256, 6, CU_TENSOR_MAP_SWIZZLE_32B, CU_TENSOR_MAP_L2_PROMOTION_L2_128B);
    maps.vp = d_in[2];
    maps.kp = d_in[1];
    maps.zero = 0;
    decode_kernel<<<NCTA, NT, SM_TOTAL, cudaStreamPerThread>>>(maps, (const __nv_bfloat16*)d_in[0], (__nv_bfloat16*)d_out);
}
```
